```python
import torch

def _softmax(x, axis=-1):
    return torch.softmax(x, dim=axis)
def _gelu(x):
    return torch.nn.functional.gelu(x, approximate="tanh")
def _silu(x):
    return torch.nn.functional.silu(x)
def _sigmoid(x):
    return torch.sigmoid(x)
def _layernorm(x, axis=-1, eps=1e-5):
    m = x.mean(dim=axis, keepdim=True)
    v = x.var(dim=axis, keepdim=True, unbiased=False)
    return (x - m) / torch.sqrt(v + eps)
def _scatter_add(tgt, idx, src, axis=0):
    return tgt.clone().index_add_(axis, idx, src)
def _segment_sum(src, seg, n):
    out = torch.zeros((n,) + src.shape[1:], dtype=src.dtype)
    return out.index_add_(0, seg, src)
def _pad(x, pw):
    flat = tuple(v for pair in reversed(pw) for v in pair)
    return torch.nn.functional.pad(x, flat)

kernel_name = 'sequential_preLN__softmax_full_mha__glu_gated_reglu__prompt'

def setup_inputs():

    _w = (lambda a: (lambda t: t.to(torch.bfloat16) if t.is_floating_point() else t)(torch.as_tensor(a)))
    def _A_setup():
        B, S, D = 1, 2048, 640
        return {
            "x": _w((lambda *s: torch.randn(*s, dtype=torch.bfloat16) * 0.05)(B, S, D)),
            "wqkv": _w((lambda *s: torch.randn(*s, dtype=torch.bfloat16) * 0.05)(D, 3 * D)),
            "wo": _w((lambda *s: torch.randn(*s, dtype=torch.bfloat16) * 0.05)(D, D)),
        }
    _A_in = _A_setup()

    def _B_setup():
        B, S, D, F = 1, 2048, 640, 1536
        return {
            "x": _w((lambda *s: torch.randn(*s, dtype=torch.bfloat16) * 0.05)(B, S, D)),
            "W_gate": _w((lambda *s: torch.randn(*s, dtype=torch.bfloat16) * 0.4)(D, F) * (2.0 / D) ** 0.5),
            "W_up": _w((lambda *s: torch.randn(*s, dtype=torch.bfloat16) * 0.4)(D, F) * (2.0 / D) ** 0.5),
            "W_down": _w((lambda *s: torch.randn(*s, dtype=torch.bfloat16) * 0.4)(F, D) * (1.0 / F) ** 0.5),
        }
    _B_in = _B_setup()

    return {
        "A_x": _A_in["x"],
        "A_wqkv": _A_in["wqkv"],
        "A_wo": _A_in["wo"],
        "B_x": _B_in["x"],
        "B_W_gate": _B_in["W_gate"],
        "B_W_up": _B_in["W_up"],
        "B_W_down": _B_in["W_down"],
    }

def reference(A_x, A_wqkv, A_wo, B_x, B_W_gate, B_W_up, B_W_down):
    def _A_ref(x, wqkv, wo):
        B, S, D = x.shape
        H = 32; Dh = D // H
        qkv = (lambda x, *d: x.permute(*d))((x @ wqkv).reshape(B, S, 3, H, Dh), 2, 0, 3, 1, 4)
        q, k, v = qkv[0], qkv[1], qkv[2]
        scale = Dh ** -0.5
        scores = torch.einsum("bhqd,bhkd->bhqk", q, k) * scale
        p = _softmax(scores, axis=-1)
        o = torch.einsum("bhqk,bhkd->bhqd", p, v)
        return (lambda x, *d: x.permute(*d))(o, 0, 2, 1, 3).reshape(B, S, D) @ wo

    def _B_ref(x, W_gate, W_up, W_down):
        gate = torch.einsum("bsd,df->bsf", x, W_gate)
        up = torch.einsum("bsd,df->bsf", x, W_up)
        gate = gate * (lambda x, dt: x.to(dt))(gate > 0, gate.dtype)
        h = gate * up
        return torch.einsum("bsf,fd->bsd", h, W_down)

    x = A_x
    h = x + _A_ref(_layernorm(x, axis=-1), A_wqkv, A_wo)
    h2 = h + _B_ref(_layernorm(h, axis=-1), B_W_gate, B_W_up, B_W_down)
    return h2
```

```cpp
#include <cuda_runtime.h>
#include <cuda_bf16.h>
#include <cuda.h>
#include <stdint.h>

constexpr int S_LEN = 2048, DM = 640, NH = 32, DH = 20, DFF = 1536;

__device__ __align__(1024) __nv_bfloat16 g_q[S_LEN * DM];
__device__ __align__(1024) __nv_bfloat16 g_k[NH * S_LEN * 24];
__device__ __align__(1024) __nv_bfloat16 g_v[NH * S_LEN * 24];
__device__ __align__(1024) __nv_bfloat16 g_o[S_LEN * DM];
__device__ __align__(1024) __nv_bfloat16 g_h[S_LEN * DM];
__device__ __align__(1024) __nv_bfloat16 g_act[S_LEN * DFF];
__device__ float g_kn[8 * NH * 2];
__device__ float2 g_stat1[S_LEN];
__device__ float g_cs_qkv[3 * DM];
__device__ float g_cs_g[DFF];
__device__ float g_cs_u[DFF];
__device__ float2 g_part2[S_LEN * 10];

__device__ __forceinline__ uint32_t smem_u32(const void* p) { return (uint32_t)__cvta_generic_to_shared(p); }
__device__ __forceinline__ void mbar_init(uint32_t bar, uint32_t cnt) { asm volatile("mbarrier.init.shared::cta.b64 [%0], %1;" :: "r"(bar), "r"(cnt)); }
__device__ __forceinline__ void mbar_expect_tx(uint32_t bar, uint32_t bytes) { asm volatile("mbarrier.arrive.expect_tx.shared::cta.b64 _, [%0], %1;" :: "r"(bar), "r"(bytes) : "memory"); }
__device__ __forceinline__ void mbar_arrive(uint32_t bar) { asm volatile("mbarrier.arrive.shared::cta.b64 _, [%0];" :: "r"(bar) : "memory"); }
__device__ __forceinline__ void mbar_wait(uint32_t bar, uint32_t parity) {
  uint32_t done;
  uint32_t spins = 0;
  do {
    asm volatile("{\n.reg .pred P1;\nmbarrier.try_wait.parity.shared::cta.b64 P1, [%1], %2;\nselp.u32 %0, 1, 0, P1;\n}" : "=r"(done) : "r"(bar), "r"(parity) : "memory");
  } while (!done && ++spins < (1u << 24));
}
__device__ __forceinline__ void bulk_g2s(uint32_t dst, const void* src, uint32_t bytes, uint32_t bar) {
  asm volatile("cp.async.bulk.shared::cluster.global.mbarrier::complete_tx::bytes [%0], [%1], %2, [%3];" :: "r"(dst), "l"(src), "r"(bytes), "r"(bar) : "memory");
}
__device__ __forceinline__ void tma_2d(uint32_t dst, const CUtensorMap* tm, int c0, int c1, uint32_t bar) {
  asm volatile("cp.async.bulk.tensor.2d.shared::cluster.global.mbarrier::complete_tx::bytes [%0], [%1, {%3, %4}], [%2];"
               :: "r"(dst), "l"(tm), "r"(bar), "r"(c0), "r"(c1) : "memory");
}
__device__ __forceinline__ void wgmma_fence() { asm volatile("wgmma.fence.sync.aligned;" ::: "memory"); }
__device__ __forceinline__ void wgmma_commit() { asm volatile("wgmma.commit_group.sync.aligned;" ::: "memory"); }
template <int N> __device__ __forceinline__ void wgmma_wait() { asm volatile("wgmma.wait_group.sync.aligned %0;" :: "n"(N) : "memory"); }
__device__ __forceinline__ void pdl_wait() { asm volatile("griddepcontrol.wait;" ::: "memory"); }
__device__ __forceinline__ void pdl_launch() { asm volatile("griddepcontrol.launch_dependents;" ::: "memory"); }
__device__ __forceinline__ void named_bar(int id, int n) { asm volatile("bar.sync %0, %1;" :: "r"(id), "r"(n) : "memory"); }
__device__ __forceinline__ uint64_t make_desc(uint32_t addr, uint32_t lbo, uint32_t sbo, uint32_t swz) {
  return (uint64_t)((addr & 0x3FFFF) >> 4) | ((uint64_t)(lbo >> 4) << 16) | ((uint64_t)(sbo >> 4) << 32) | ((uint64_t)swz << 62);
}
__device__ __forceinline__ uint32_t pack_bf16(float lo, float hi) { uint32_t r; asm("cvt.rn.bf16x2.f32 %0, %1, %2;" : "=r"(r) : "f"(hi), "f"(lo)); return r; }
__device__ __forceinline__ float bf_lo(uint32_t u) { return __uint_as_float(u << 16); }
__device__ __forceinline__ float bf_hi(uint32_t u) { return __uint_as_float(u & 0xffff0000u); }
__device__ __forceinline__ float bf_round(float x) { return __bfloat162float(__float2bfloat16_rn(x)); }
__device__ __forceinline__ float ex2_mufu(float x) { float y; asm("ex2.approx.ftz.f32 %0, %1;" : "=f"(y) : "f"(x)); return y; }

__device__ __forceinline__ void wgmma_ss_n64(float (&d)[32], uint64_t da, uint64_t db, int scale_d) {
  asm volatile("{\n.reg .pred p;\nsetp.ne.b32 p, %34, 0;\n"
    "wgmma.mma_async.sync.aligned.m64n64k16.f32.bf16.bf16 {%0,%1,%2,%3,%4,%5,%6,%7,%8,%9,%10,%11,%12,%13,%14,%15,%16,%17,%18,%19,%20,%21,%22,%23,%24,%25,%26,%27,%28,%29,%30,%31}, %32, %33, p, 1, 1, 0, 1;\n}\n"
    : "+f"(d[0]),"+f"(d[1]),"+f"(d[2]),"+f"(d[3]),"+f"(d[4]),"+f"(d[5]),"+f"(d[6]),"+f"(d[7]),"+f"(d[8]),"+f"(d[9]),"+f"(d[10]),"+f"(d[11]),"+f"(d[12]),"+f"(d[13]),"+f"(d[14]),"+f"(d[15]),"+f"(d[16]),"+f"(d[17]),"+f"(d[18]),"+f"(d[19]),"+f"(d[20]),"+f"(d[21]),"+f"(d[22]),"+f"(d[23]),"+f"(d[24]),"+f"(d[25]),"+f"(d[26]),"+f"(d[27]),"+f"(d[28]),"+f"(d[29]),"+f"(d[30]),"+f"(d[31])
    : "l"(da), "l"(db), "r"(scale_d));
}
__device__ __forceinline__ void wgmma_ss_n128(float (&d)[64], uint64_t da, uint64_t db, int scale_d) {
  asm volatile("{\n.reg .pred p;\nsetp.ne.b32 p, %66, 0;\n"
    "wgmma.mma_async.sync.aligned.m64n128k16.f32.bf16.bf16 {%0,%1,%2,%3,%4,%5,%6,%7,%8,%9,%10,%11,%12,%13,%14,%15,%16,%17,%18,%19,%20,%21,%22,%23,%24,%25,%26,%27,%28,%29,%30,%31,%32,%33,%34,%35,%36,%37,%38,%39,%40,%41,%42,%43,%44,%45,%46,%47,%48,%49,%50,%51,%52,%53,%54,%55,%56,%57,%58,%59,%60,%61,%62,%63}, %64, %65, p, 1, 1, 0, 1;\n}\n"
    : "+f"(d[0]),"+f"(d[1]),"+f"(d[2]),"+f"(d[3]),"+f"(d[4]),"+f"(d[5]),"+f"(d[6]),"+f"(d[7]),"+f"(d[8]),"+f"(d[9]),"+f"(d[10]),"+f"(d[11]),"+f"(d[12]),"+f"(d[13]),"+f"(d[14]),"+f"(d[15]),"+f"(d[16]),"+f"(d[17]),"+f"(d[18]),"+f"(d[19]),"+f"(d[20]),"+f"(d[21]),"+f"(d[22]),"+f"(d[23]),"+f"(d[24]),"+f"(d[25]),"+f"(d[26]),"+f"(d[27]),"+f"(d[28]),"+f"(d[29]),"+f"(d[30]),"+f"(d[31]),"+f"(d[32]),"+f"(d[33]),"+f"(d[34]),"+f"(d[35]),"+f"(d[36]),"+f"(d[37]),"+f"(d[38]),"+f"(d[39]),"+f"(d[40]),"+f"(d[41]),"+f"(d[42]),"+f"(d[43]),"+f"(d[44]),"+f"(d[45]),"+f"(d[46]),"+f"(d[47]),"+f"(d[48]),"+f"(d[49]),"+f"(d[50]),"+f"(d[51]),"+f"(d[52]),"+f"(d[53]),"+f"(d[54]),"+f"(d[55]),"+f"(d[56]),"+f"(d[57]),"+f"(d[58]),"+f"(d[59]),"+f"(d[60]),"+f"(d[61]),"+f"(d[62]),"+f"(d[63])
    : "l"(da), "l"(db), "r"(scale_d));
}
__device__ __forceinline__ void wgmma_ss_n192(float (&d)[96], uint64_t da, uint64_t db, int scale_d) {
  asm volatile("{\n.reg .pred p;\nsetp.ne.b32 p, %98, 0;\n"
    "wgmma.mma_async.sync.aligned.m64n192k16.f32.bf16.bf16 {%0,%1,%2,%3,%4,%5,%6,%7,%8,%9,%10,%11,%12,%13,%14,%15,%16,%17,%18,%19,%20,%21,%22,%23,%24,%25,%26,%27,%28,%29,%30,%31,%32,%33,%34,%35,%36,%37,%38,%39,%40,%41,%42,%43,%44,%45,%46,%47,%48,%49,%50,%51,%52,%53,%54,%55,%56,%57,%58,%59,%60,%61,%62,%63,%64,%65,%66,%67,%68,%69,%70,%71,%72,%73,%74,%75,%76,%77,%78,%79,%80,%81,%82,%83,%84,%85,%86,%87,%88,%89,%90,%91,%92,%93,%94,%95}, %96, %97, p, 1, 1, 0, 1;\n}\n"
    : "+f"(d[0]),"+f"(d[1]),"+f"(d[2]),"+f"(d[3]),"+f"(d[4]),"+f"(d[5]),"+f"(d[6]),"+f"(d[7]),"+f"(d[8]),"+f"(d[9]),"+f"(d[10]),"+f"(d[11]),"+f"(d[12]),"+f"(d[13]),"+f"(d[14]),"+f"(d[15]),"+f"(d[16]),"+f"(d[17]),"+f"(d[18]),"+f"(d[19]),"+f"(d[20]),"+f"(d[21]),"+f"(d[22]),"+f"(d[23]),"+f"(d[24]),"+f"(d[25]),"+f"(d[26]),"+f"(d[27]),"+f"(d[28]),"+f"(d[29]),"+f"(d[30]),"+f"(d[31]),"+f"(d[32]),"+f"(d[33]),"+f"(d[34]),"+f"(d[35]),"+f"(d[36]),"+f"(d[37]),"+f"(d[38]),"+f"(d[39]),"+f"(d[40]),"+f"(d[41]),"+f"(d[42]),"+f"(d[43]),"+f"(d[44]),"+f"(d[45]),"+f"(d[46]),"+f"(d[47]),"+f"(d[48]),"+f"(d[49]),"+f"(d[50]),"+f"(d[51]),"+f"(d[52]),"+f"(d[53]),"+f"(d[54]),"+f"(d[55]),"+f"(d[56]),"+f"(d[57]),"+f"(d[58]),"+f"(d[59]),"+f"(d[60]),"+f"(d[61]),"+f"(d[62]),"+f"(d[63]),"+f"(d[64]),"+f"(d[65]),"+f"(d[66]),"+f"(d[67]),"+f"(d[68]),"+f"(d[69]),"+f"(d[70]),"+f"(d[71]),"+f"(d[72]),"+f"(d[73]),"+f"(d[74]),"+f"(d[75]),"+f"(d[76]),"+f"(d[77]),"+f"(d[78]),"+f"(d[79]),"+f"(d[80]),"+f"(d[81]),"+f"(d[82]),"+f"(d[83]),"+f"(d[84]),"+f"(d[85]),"+f"(d[86]),"+f"(d[87]),"+f"(d[88]),"+f"(d[89]),"+f"(d[90]),"+f"(d[91]),"+f"(d[92]),"+f"(d[93]),"+f"(d[94]),"+f"(d[95])
    : "l"(da), "l"(db), "r"(scale_d));
}
__device__ __forceinline__ void wgmma_rs_n64(float (&d)[32], uint32_t a0, uint32_t a1, uint32_t a2, uint32_t a3, uint64_t db, int scale_d) {
  asm volatile("{\n.reg .pred p;\nsetp.ne.b32 p, %37, 0;\n"
    "wgmma.mma_async.sync.aligned.m64n64k16.f32.bf16.bf16 {%0,%1,%2,%3,%4,%5,%6,%7,%8,%9,%10,%11,%12,%13,%14,%15,%16,%17,%18,%19,%20,%21,%22,%23,%24,%25,%26,%27,%28,%29,%30,%31}, {%32,%33,%34,%35}, %36, p, 1, 1, 0;\n}\n"
    : "+f"(d[0]),"+f"(d[1]),"+f"(d[2]),"+f"(d[3]),"+f"(d[4]),"+f"(d[5]),"+f"(d[6]),"+f"(d[7]),"+f"(d[8]),"+f"(d[9]),"+f"(d[10]),"+f"(d[11]),"+f"(d[12]),"+f"(d[13]),"+f"(d[14]),"+f"(d[15]),"+f"(d[16]),"+f"(d[17]),"+f"(d[18]),"+f"(d[19]),"+f"(d[20]),"+f"(d[21]),"+f"(d[22]),"+f"(d[23]),"+f"(d[24]),"+f"(d[25]),"+f"(d[26]),"+f"(d[27]),"+f"(d[28]),"+f"(d[29]),"+f"(d[30]),"+f"(d[31])
    : "r"(a0), "r"(a1), "r"(a2), "r"(a3), "l"(db), "r"(scale_d));
}
__device__ __forceinline__ void wgmma_rs_n24_tb(float (&d)[12], uint32_t a0, uint32_t a1, uint32_t a2, uint32_t a3, uint64_t db, int scale_d) {
  asm volatile("{\n.reg .pred p;\nsetp.ne.b32 p, %17, 0;\n"
    "wgmma.mma_async.sync.aligned.m64n24k16.f32.bf16.bf16 {%0,%1,%2,%3,%4,%5,%6,%7,%8,%9,%10,%11}, {%12,%13,%14,%15}, %16, p, 1, 1, 1;\n}\n"
    : "+f"(d[0]),"+f"(d[1]),"+f"(d[2]),"+f"(d[3]),"+f"(d[4]),"+f"(d[5]),"+f"(d[6]),"+f"(d[7]),"+f"(d[8]),"+f"(d[9]),"+f"(d[10]),"+f"(d[11])
    : "r"(a0), "r"(a1), "r"(a2), "r"(a3), "l"(db), "r"(scale_d));
}

constexpr int PRE_ROW_BLOCKS = 64;
constexpr int PRE_COL_BLOCKS = (3 * DM + 2 * DFF) / 64;
__device__ __forceinline__ float2 ln_finish(float mean, float var) {
  float mb = bf_round(mean);
  float s = bf_round(sqrtf(bf_round(bf_round(var) + 1e-5f)));
  return make_float2(mb, 1.0f / s);
}
__global__ void __launch_bounds__(256) pre_kernel(const __nv_bfloat16* __restrict__ x, const __nv_bfloat16* __restrict__ wqkv,
                                                  const __nv_bfloat16* __restrict__ wg, const __nv_bfloat16* __restrict__ wu) {
  pdl_launch();
  const int tid = threadIdx.x, lane = tid & 31, warp = tid >> 5;
  if (blockIdx.x < PRE_COL_BLOCKS) {
    __shared__ float red[32][65];
    int c0 = blockIdx.x * 64;
    const __nv_bfloat16* w; float* dst; int ld;
    if (c0 < 3 * DM) { w = wqkv; dst = g_cs_qkv; ld = 3 * DM; }
    else if (c0 < 3 * DM + DFF) { w = wg; dst = g_cs_g; ld = DFF; c0 -= 3 * DM; }
    else { w = wu; dst = g_cs_u; ld = DFF; c0 -= 3 * DM + DFF; }
    const int cg = tid & 7, r0 = tid >> 3;
    float acc[8];
#pragma unroll
    for (int i = 0; i < 8; i++) acc[i] = 0.f;
#pragma unroll 5
    for (int r = r0; r < DM; r += 32) {
      uint4 v = __ldg((const uint4*)(w + (size_t)r * ld + c0 + cg * 8));
      acc[0] += bf_lo(v.x); acc[1] += bf_hi(v.x); acc[2] += bf_lo(v.y); acc[3] += bf_hi(v.y);
      acc[4] += bf_lo(v.z); acc[5] += bf_hi(v.z); acc[6] += bf_lo(v.w); acc[7] += bf_hi(v.w);
    }
#pragma unroll
    for (int i = 0; i < 8; i++) red[r0][cg * 8 + i] = acc[i];
    __syncthreads();
    if (tid < 64) {
      float s = 0.f;
#pragma unroll
      for (int r = 0; r < 32; r++) s += red[r][tid];
      dst[c0 + tid] = s;
    }
  } else {
    const int rb = blockIdx.x - PRE_COL_BLOCKS;
#pragma unroll
    for (int i = 0; i < 4; i++) {
      const int row = rb * 32 + warp * 4 + i;
      const uint4* p = (const uint4*)(x + (size_t)row * DM);
      uint4 v0 = __ldg(p + lane), v1 = __ldg(p + 32 + lane), v2 = make_uint4(0, 0, 0, 0);
      if (lane < 16) v2 = __ldg(p + 64 + lane);
      float f[24];
      uint32_t u[12] = {v0.x, v0.y, v0.z, v0.w, v1.x, v1.y, v1.z, v1.w, v2.x, v2.y, v2.z, v2.w};
#pragma unroll
      for (int j = 0; j < 12; j++) { f[2 * j] = bf_lo(u[j]); f[2 * j + 1] = bf_hi(u[j]); }
      float s = 0.f;
#pragma unroll
      for (int j = 0; j < 24; j++) s += f[j];
#pragma unroll
      for (int o = 16; o; o >>= 1) s += __shfl_xor_sync(~0u, s, o);
      const float mean = s * (1.0f / DM);
      float q = 0.f;
#pragma unroll
      for (int j = 0; j < 16; j++) { float d = f[j] - mean; q += d * d; }
      if (lane < 16) {
#pragma unroll
        for (int j = 16; j < 24; j++) { float d = f[j] - mean; q += d * d; }
      }
#pragma unroll
      for (int o = 16; o; o >>= 1) q += __shfl_xor_sync(~0u, q, o);
      if (lane == 0) g_stat1[row] = ln_finish(mean, q * (1.0f / DM));
    }
  }
}

enum { EPI_QKV = 0, EPI_WO = 1, EPI_GLU = 2, EPI_DOWN = 3 };
template <int N> struct WG;
template <> struct WG<64>  { static __device__ __forceinline__ void mma(float (&d)[32], uint64_t a, uint64_t b, int s) { wgmma_ss_n64(d, a, b, s); } };
template <> struct WG<128> { static __device__ __forceinline__ void mma(float (&d)[64], uint64_t a, uint64_t b, int s) { wgmma_ss_n128(d, a, b, s); } };
template <> struct WG<192> { static __device__ __forceinline__ void mma(float (&d)[96], uint64_t a, uint64_t b, int s) { wgmma_ss_n192(d, a, b, s); } };

template <int BM, int BN, int NB, int STAGES> struct GemmCfg {
  static constexpr int A_BYTES = BM * 128;
  static constexpr int B_BYTES = NB * (BN / 64) * 8192;
  static constexpr int STAGE_BYTES = A_BYTES + B_BYTES;
  static constexpr int SMEM = STAGES * STAGE_BYTES + 1024   + 256   + 4096  ;
};

constexpr float QSCALE = 0.22360679774997896f * 1.4426950408889634f;

template <int BM, int BN, int NB, int KDIM, int STAGES, int EPI, int MINB>
__global__ void __launch_bounds__(EPI == EPI_GLU ? 384 : 288, MINB) gemm_kernel(const __grid_constant__ CUtensorMap tmA, const __grid_constant__ CUtensorMap tmB0,
                                                         const __grid_constant__ CUtensorMap tmB1,
                                                         const __nv_bfloat16* __restrict__ resid, __nv_bfloat16* __restrict__ out) {
  using Cfg = GemmCfg<BM, BN, NB, STAGES>;
  constexpr int MB = BM / 128;
  constexpr int KT = KDIM / 64;
  extern __shared__ uint8_t smem_raw[];
  const uint32_t sbase = (smem_u32(smem_raw) + 1023u) & ~1023u;
  uint8_t* sptr = smem_raw + (sbase - smem_u32(smem_raw));
  const uint32_t sbar = sbase + STAGES * Cfg::STAGE_BYTES;
  const int tid = threadIdx.x, warp = tid >> 5, lane = tid & 31;
  const int n0 = blockIdx.x * BN, m0 = blockIdx.y * BM;
  if (tid == 0) {
    for (int i = 0; i < STAGES; i++) { mbar_init(sbar + 8 * i, 1); mbar_init(sbar + 8 * (STAGES + i), 8); }
    asm volatile("fence.mbarrier_init.release.cluster;" ::: "memory");
  }
  __syncthreads();
  pdl_launch();
  if (warp >= 8) {
    if constexpr (EPI == EPI_GLU) asm volatile("setmaxnreg.dec.sync.aligned.u32 40;");
    if (warp == 8 && lane == 0) {
      auto load_b = [&](int kt, int s) {
        const uint32_t sb = sbase + s * Cfg::STAGE_BYTES + Cfg::A_BYTES;
#pragma unroll
        for (int j = 0; j < BN / 64; j++) {
          tma_2d(sb + j * 8192, &tmB0, n0 + j * 64, kt * 64, sbar + 8 * s);
          if (NB == 2) tma_2d(sb + (BN / 64 + j) * 8192, &tmB1, n0 + j * 64, kt * 64, sbar + 8 * s);
        }
      };
      for (int s = 0; s < STAGES; s++) { mbar_expect_tx(sbar + 8 * s, Cfg::STAGE_BYTES); load_b(s, s); }
      if (EPI != EPI_QKV) pdl_wait();
      for (int s = 0; s < STAGES; s++) tma_2d(sbase + s * Cfg::STAGE_BYTES, &tmA, s * 64, m0, sbar + 8 * s);
      for (int kt = STAGES; kt < KT; kt++) {
        const int s = kt % STAGES;
        mbar_wait(sbar + 8 * (STAGES + s), ((kt / STAGES) - 1) & 1);
        mbar_expect_tx(sbar + 8 * s, Cfg::STAGE_BYTES);
        tma_2d(sbase + s * Cfg::STAGE_BYTES, &tmA, kt * 64, m0, sbar + 8 * s);
        load_b(kt, s);
      }
    }
    if constexpr (EPI == EPI_GLU) {
      if (warp > 8) {
        float2* s_st = (float2*)(sptr + STAGES * Cfg::STAGE_BYTES + 256);
        float* s_cs = (float*)(sptr + STAGES * Cfg::STAGE_BYTES + 256 + 1024);
        pdl_wait();
        for (int r = tid - 288; r < BM; r += 96) {
          const float2* pp = &g_part2[(m0 + r) * 10];
          float s = 0.f;
#pragma unroll
          for (int i = 0; i < 10; i++) s += pp[i].x;
          const float mean = s * (1.0f / DM);
          float q = 0.f;
#pragma unroll
          for (int i = 0; i < 10; i++) { const float2 p = pp[i]; const float d = p.x * (1.0f / 64.f) - mean; q += p.y + 64.f * d * d; }
          s_st[r] = ln_finish(mean, q * (1.0f / DM));
        }
        for (int c = tid - 288; c < BN; c += 96) { s_cs[c] = g_cs_g[n0 + c]; s_cs[BN + c] = g_cs_u[n0 + c]; }
        __threadfence_block();
        asm volatile("bar.arrive 2, 352;" ::: "memory");
      }
    }
    return;
  }
  if constexpr (EPI == EPI_GLU) asm volatile("setmaxnreg.inc.sync.aligned.u32 232;");
  const int wg = warp >> 2, g = lane >> 2, t = lane & 3;
  float acc[MB][NB][BN / 2];
#pragma unroll
  for (int mb = 0; mb < MB; mb++)
#pragma unroll
    for (int nb = 0; nb < NB; nb++)
#pragma unroll
      for (int i = 0; i < BN / 2; i++) acc[mb][nb][i] = 0.f;
  for (int kt = 0; kt < KT; kt++) {
    const int s = kt % STAGES;
    mbar_wait(sbar + 8 * s, (kt / STAGES) & 1);
    const uint32_t sa = sbase + s * Cfg::STAGE_BYTES + wg * (MB * 64 * 128);
    const uint32_t sb = sbase + s * Cfg::STAGE_BYTES + Cfg::A_BYTES;
    wgmma_fence();
#pragma unroll
    for (int ks = 0; ks < 4; ks++) {
#pragma unroll
      for (int mb = 0; mb < MB; mb++) {
        const uint64_t da = make_desc(sa + mb * 8192 + ks * 32, 16, 1024, 1);
#pragma unroll
        for (int nb = 0; nb < NB; nb++) {
          const uint64_t db = make_desc(sb + nb * (BN / 64) * 8192 + ks * 2048, 8192, 1024, 1);
          WG<BN>::mma(acc[mb][nb], da, db, 1);
        }
      }
    }
    wgmma_commit();
    wgmma_wait<1>();
    if (kt > 0 && lane == 0) mbar_arrive(sbar + 8 * (STAGES + (kt - 1) % STAGES));
  }
  wgmma_wait<0>();
#pragma unroll
  for (int mb = 0; mb < MB; mb++)
#pragma unroll
    for (int nb = 0; nb < NB; nb++)
#pragma unroll
      for (int i = 0; i < BN / 2; i++) asm volatile("" : "+f"(acc[mb][nb][i]) :: "memory");
  pdl_wait();
  named_bar(1, 256);
  constexpr int LDS = BN * 2 + 16;
  const int ctid = tid;

  if constexpr (EPI == EPI_QKV) {
    const int sec = n0 / DM;
#pragma unroll
    for (int mb = 0; mb < MB; mb++) {
      const int r0 = wg * (MB * 64) + mb * 64 + (warp & 3) * 16 + g;
      const float2 st0 = g_stat1[m0 + r0], st1 = g_stat1[m0 + r0 + 8];
      const float sc0 = sec == 0 ? st0.y * QSCALE : st0.y, sc1 = sec == 0 ? st1.y * QSCALE : st1.y;
#pragma unroll
      for (int j = 0; j < BN / 8; j++) {
        const float2 cs = *(const float2*)&g_cs_qkv[n0 + j * 8 + 2 * t];
        const float* a = &acc[mb][0][4 * j];
        *(uint32_t*)(sptr + r0 * LDS + j * 16 + t * 4) = pack_bf16((a[0] - st0.x * cs.x) * sc0, (a[1] - st0.x * cs.y) * sc0);
        *(uint32_t*)(sptr + (r0 + 8) * LDS + j * 16 + t * 4) = pack_bf16((a[2] - st1.x * cs.x) * sc1, (a[3] - st1.x * cs.y) * sc1);
      }
    }
    named_bar(1, 256);
    if (sec == 0) {
#pragma unroll
      for (int i = 0; i < BM * (BN / 8) / 256; i++) {
        const int idx = i * 256 + ctid, r = idx / (BN / 8), c = idx % (BN / 8);
        *(uint4*)(g_q + (size_t)(m0 + r) * DM + n0 + c * 8) = *(const uint4*)(sptr + r * LDS + c * 16);
      }
    } else {
      __nv_bfloat16* dst = sec == 1 ? g_k : g_v;
      const int cbase = n0 - sec * DM;
#pragma unroll 4
      for (int i = 0; i < BM * (BN / 4) / 256; i++) {
        const int idx = i * 256 + ctid;
        const int half = idx & 1, r8 = (idx >> 1) & 7, rest = idx >> 4;
        const int pq = rest % (BN / 8), rg = rest / (BN / 8);
        const int r = rg * 8 + r8, cq = pq * 2 + half;
        const int col = cbase + cq * 4, h = col / DH, qd = (col % DH) >> 2;
        const uint2 v = *(const uint2*)(sptr + r * LDS + cq * 8);
        const int j = m0 + r;
        uint8_t* p = (uint8_t*)dst + ((size_t)h * S_LEN * 24 + (j >> 3) * 192 + (qd >> 1) * 64 + (j & 7) * 8 + (qd & 1) * 4) * 2;
        if (qd == 4) *(uint4*)p = make_uint4(v.x, v.y, 0x00003f80u, 0u);
        else *(uint2*)p = v;
      }
      if (sec == 1) {
        __shared__ unsigned int s_kn[8];
        if (ctid < 8) s_kn[ctid] = 0u;
        named_bar(1, 256);
        const int hfirst = cbase / DH, hlast = (cbase + BN - 1) / DH;
        for (int hh = hfirst; hh <= hlast; hh++) {
          const int c_lo = max(hh * DH, cbase) - cbase, c_hi = min(hh * DH + DH, cbase + BN) - cbase;
          float mx = 0.f;
          for (int r = ctid; r < BM; r += 256) {
            float s = 0.f;
            for (int c = c_lo; c < c_hi; c += 4) {
              const uint2 v = *(const uint2*)(sptr + r * LDS + c * 2);
              s += bf_lo(v.x) * bf_lo(v.x) + bf_hi(v.x) * bf_hi(v.x) + bf_lo(v.y) * bf_lo(v.y) + bf_hi(v.y) * bf_hi(v.y);
            }
            mx = (s > mx || s != s) ? s : mx;
          }
          unsigned int mb_ = __float_as_uint(mx) & 0x7fffffffu;
          mb_ = __reduce_max_sync(~0u, mb_);
          if (lane == 0) atomicMax(&s_kn[hh - hfirst], mb_);
        }
        named_bar(1, 256);
        if (ctid <= hlast - hfirst) {
          const int hh = hfirst + ctid;
          const bool starts_here = hh * DH >= cbase, ends_here = hh * DH + DH <= cbase + BN;
          const float v = __uint_as_float(s_kn[ctid]);
          float* o = &g_kn[(blockIdx.y * NH + hh) * 2];
          if (starts_here) { o[0] = v; if (ends_here) o[1] = 0.f; }
          else o[1] = v;
        }
      }
    }
  } else if constexpr (EPI == EPI_WO || EPI == EPI_DOWN) {
    const int r0 = wg * 64 + (warp & 3) * 16 + g;
#pragma unroll
    for (int j = 0; j < BN / 8; j++) {
      const float* a = &acc[0][0][4 * j];
      *(uint32_t*)(sptr + r0 * LDS + j * 16 + t * 4) = pack_bf16(a[0], a[1]);
      *(uint32_t*)(sptr + (r0 + 8) * LDS + j * 16 + t * 4) = pack_bf16(a[2], a[3]);
    }
    named_bar(1, 256);
#pragma unroll
    for (int i = 0; i < BM * (BN / 8) / 256; i++) {
      const int idx = i * 256 + ctid, r = idx / (BN / 8), c = idx % (BN / 8);
      const uint4 a = *(const uint4*)(sptr + r * LDS + c * 16);
      const size_t go = (size_t)(m0 + r) * DM + n0 + c * 8;
      const uint4 b = *(const uint4*)(resid + go);
      uint4 o;
      o.x = pack_bf16(bf_lo(a.x) + bf_lo(b.x), bf_hi(a.x) + bf_hi(b.x));
      o.y = pack_bf16(bf_lo(a.y) + bf_lo(b.y), bf_hi(a.y) + bf_hi(b.y));
      o.z = pack_bf16(bf_lo(a.z) + bf_lo(b.z), bf_hi(a.z) + bf_hi(b.z));
      o.w = pack_bf16(bf_lo(a.w) + bf_lo(b.w), bf_hi(a.w) + bf_hi(b.w));
      *(uint4*)(out + go) = o;
      if constexpr (EPI == EPI_WO) {
        static_assert(BN == 64, "stats assume 8 lanes per row");
        const float f[8] = {bf_lo(o.x), bf_hi(o.x), bf_lo(o.y), bf_hi(o.y), bf_lo(o.z), bf_hi(o.z), bf_lo(o.w), bf_hi(o.w)};
        float s = 0.f;
#pragma unroll
        for (int k = 0; k < 8; k++) s += f[k];
        s += __shfl_xor_sync(~0u, s, 1); s += __shfl_xor_sync(~0u, s, 2); s += __shfl_xor_sync(~0u, s, 4);
        const float mu = s * (1.0f / 64.f);
        float q = 0.f;
#pragma unroll
        for (int k = 0; k < 8; k++) { const float d = f[k] - mu; q += d * d; }
        q += __shfl_xor_sync(~0u, q, 1); q += __shfl_xor_sync(~0u, q, 2); q += __shfl_xor_sync(~0u, q, 4);
        if (c == 0) g_part2[(m0 + r) * 10 + blockIdx.x] = make_float2(s, q);
      }
    }
  } else {
    const int r0 = wg * 64 + (warp & 3) * 16 + g;
    const float2* s_st = (const float2*)(sptr + STAGES * Cfg::STAGE_BYTES + 256);
    const float* s_cs = (const float*)(sptr + STAGES * Cfg::STAGE_BYTES + 256 + 1024);
    named_bar(2, 352);
    float2 st[2] = {s_st[r0], s_st[r0 + 8]};
#pragma unroll
    for (int j = 0; j < BN / 8; j++) {
      const float2 cg = *(const float2*)&s_cs[j * 8 + 2 * t], cu = *(const float2*)&s_cs[BN + j * 8 + 2 * t];
      const float* a = &acc[0][0][4 * j];
      const float* b = &acc[0][1][4 * j];
      float v[4];
#pragma unroll
      for (int e = 0; e < 4; e++) {
        const float2 s_ = st[e >> 1];
        const float gt = bf_round((a[e] - s_.x * ((e & 1) ? cg.y : cg.x)) * s_.y);
        const float up = bf_round((b[e] - s_.x * ((e & 1) ? cu.y : cu.x)) * s_.y);
        v[e] = (gt > 0.f ? gt : 0.f) * up;
      }
      *(uint32_t*)(sptr + r0 * LDS + j * 16 + t * 4) = pack_bf16(v[0], v[1]);
      *(uint32_t*)(sptr + (r0 + 8) * LDS + j * 16 + t * 4) = pack_bf16(v[2], v[3]);
    }
    named_bar(1, 256);
#pragma unroll
    for (int i = 0; i < BM * (BN / 8) / 256; i++) {
      const int idx = i * 256 + ctid, r = idx / (BN / 8), c = idx % (BN / 8);
      *(uint4*)(out + (size_t)(m0 + r) * DFF + n0 + c * 8) = *(const uint4*)(sptr + r * LDS + c * 16);
    }
  }
}

#define POLY_NUM 5
__device__ __forceinline__ float ex2_poly(float x, int shl23) {
  const float MAGIC = 12582912.f;
  const float tt = x + MAGIC;
  const float f = x - (tt - MAGIC);
  float p = fmaf(0.0013276472454890609f, f, 0.009675540961325169f);
  p = fmaf(p, f, 0.05550713092088699f);
  p = fmaf(p, f, 0.24022120237350464f);
  p = fmaf(p, f, 0.6931469440460205f);
  p = fmaf(p, f, 1.0000001192092896f);
  return __int_as_float(__float_as_int(tt) * shl23 + __float_as_int(p));
}
constexpr int KV_BYTES = S_LEN * 48;
constexpr int ATT_SMEM = 2 * KV_BYTES + 256;

__global__ void __launch_bounds__(512, 1) attn_kernel(int shl23) {
  extern __shared__ __align__(1024) uint8_t smem[];
  const int h = blockIdx.x >> 2, qb = blockIdx.x & 3;
  const uint32_t sK = smem_u32(smem), sV = sK + KV_BYTES, sBar = sV + KV_BYTES;
  const int tid = threadIdx.x;
  if (tid == 0) {
    for (int i = 0; i < 8; i++) mbar_init(sBar + 8 * i, 1);
    asm volatile("fence.mbarrier_init.release.cluster;" ::: "memory");
  }
  pdl_launch();
  pdl_wait();
  if (tid == 0) {
    const uint8_t* gk = (const uint8_t*)(g_k + (size_t)h * S_LEN * 24);
    const uint8_t* gv = (const uint8_t*)(g_v + (size_t)h * S_LEN * 24);
    for (int i = 0; i < 8; i++) {
      mbar_expect_tx(sBar + 8 * i, 2 * 12288);
      bulk_g2s(sK + i * 12288, gk + i * 12288, 12288, sBar + 8 * i);
      bulk_g2s(sV + i * 12288, gv + i * 12288, 12288, sBar + 8 * i);
    }
  }
  __syncthreads();
  const int wg = tid >> 7, warp = (tid >> 5) & 3, lane = tid & 31, g = lane >> 2, t = lane & 3;
  float ka = 0.f, kb = 0.f;
#pragma unroll
  for (int i = 0; i < 8; i++) {
    const float2 v = *(const float2*)&g_kn[(i * NH + h) * 2];
    ka = (v.x > ka || v.x != v.x) ? v.x : ka;
    kb = (v.y > kb || v.y != v.y) ? v.y : kb;
  }
  const float kn = sqrtf(ka + kb);
  for (int it = 0; it < 2; it++) {
    const int q0 = qb * 512 + (it * 4 + wg) * 64 + warp * 16;
    uint32_t qa[4], qc[4];
    const uint32_t* qr0 = (const uint32_t*)(g_q + (size_t)(q0 + g) * DM + h * DH);
    const uint32_t* qr1 = (const uint32_t*)(g_q + (size_t)(q0 + g + 8) * DM + h * DH);
    qa[0] = qr0[t]; qa[1] = qr1[t]; qa[2] = qr0[t + 4]; qa[3] = qr1[t + 4];
    qc[0] = (t < 2) ? qr0[t + 8] : 0u; qc[1] = (t < 2) ? qr1[t + 8] : 0u; qc[2] = 0; qc[3] = 0;
    auto sq = [](uint32_t u) { const float a = bf_lo(u), b = bf_hi(u); return a * a + b * b; };
    float n0 = sq(qa[0]) + sq(qa[2]) + sq(qc[0]);
    float n1 = sq(qa[1]) + sq(qa[3]) + sq(qc[1]);
    n0 += __shfl_xor_sync(~0u, n0, 1); n0 += __shfl_xor_sync(~0u, n0, 2);
    n1 += __shfl_xor_sync(~0u, n1, 1); n1 += __shfl_xor_sync(~0u, n1, 2);
    const float m0 = ceilf(sqrtf(n0) * kn * 1.001f) + 1.f, m1 = ceilf(sqrtf(n1) * kn * 1.001f) + 1.f;
    const bool unsafe = !(m0 <= 62.f && m1 <= 62.f);
    uint32_t any_unsafe;
    asm volatile("{\n.reg .pred p, q;\nsetp.ne.u32 p, %1, 0;\nbarrier.cta.red.or.pred q, %2, 128, p;\nselp.u32 %0, 1, 0, q;\n}"
                 : "=r"(any_unsafe) : "r"((uint32_t)unsafe), "r"(1 + wg) : "memory");
    float O[12];
    float S[32];
    if (!__any_sync(~0u, any_unsafe)) {
      if (t == 2) { qc[0] = pack_bf16(-m0, 0.f); qc[1] = pack_bf16(-m1, 0.f); }
      for (int j = 0; j < 32; j++) {
        if (it == 0 && (j & 3) == 0) mbar_wait(sBar + 8 * (j >> 2), 0);
        const uint64_t dk = make_desc(sK + j * 8 * 384, 128, 384, 0);
        wgmma_fence();
        wgmma_rs_n64(S, qa[0], qa[1], qa[2], qa[3], dk, 0);
        wgmma_rs_n64(S, qc[0], qc[1], qc[2], qc[3], dk + (256 >> 4), 1);
        wgmma_commit();
        wgmma_wait<0>();
        uint32_t P[16];
#pragma unroll
        for (int i = 0; i < 16; i++) {
          const bool usepoly = ((i + 1) * POLY_NUM / 16) != (i * POLY_NUM / 16);
          float a, b;
          if (usepoly) { a = ex2_poly(S[2 * i], shl23); b = ex2_poly(S[2 * i + 1], shl23); }
          else { a = ex2_mufu(S[2 * i]); b = ex2_mufu(S[2 * i + 1]); }
          P[i] = pack_bf16(a, b);
        }
        wgmma_fence();
        const uint64_t dv = make_desc(sV + j * 8 * 384, 384, 128, 0);
#pragma unroll
        for (int ks = 0; ks < 4; ks++)
          wgmma_rs_n24_tb(O, P[4 * ks], P[4 * ks + 1], P[4 * ks + 2], P[4 * ks + 3], dv + ((ks * 768) >> 4), (j | ks) != 0);
        wgmma_commit();
      }
    } else {
      float mx0 = -INFINITY, mx1 = -INFINITY;
      for (int j = 0; j < 32; j++) {
        if (it == 0 && (j & 3) == 0) mbar_wait(sBar + 8 * (j >> 2), 0);
        const uint64_t dk = make_desc(sK + j * 8 * 384, 128, 384, 0);
        wgmma_fence();
        wgmma_rs_n64(S, qa[0], qa[1], qa[2], qa[3], dk, 0);
        wgmma_rs_n64(S, qc[0], qc[1], qc[2], qc[3], dk + (256 >> 4), 1);
        wgmma_commit();
        wgmma_wait<0>();
#pragma unroll
        for (int i = 0; i < 8; i++) {
          mx0 = fmaxf(mx0, fmaxf(S[4 * i], S[4 * i + 1]));
          mx1 = fmaxf(mx1, fmaxf(S[4 * i + 2], S[4 * i + 3]));
        }
      }
      mx0 = fmaxf(mx0, __shfl_xor_sync(~0u, mx0, 1)); mx0 = fmaxf(mx0, __shfl_xor_sync(~0u, mx0, 2));
      mx1 = fmaxf(mx1, __shfl_xor_sync(~0u, mx1, 1)); mx1 = fmaxf(mx1, __shfl_xor_sync(~0u, mx1, 2));
      for (int j = 0; j < 32; j++) {
        const uint64_t dk = make_desc(sK + j * 8 * 384, 128, 384, 0);
        wgmma_fence();
        wgmma_rs_n64(S, qa[0], qa[1], qa[2], qa[3], dk, 0);
        wgmma_rs_n64(S, qc[0], qc[1], qc[2], qc[3], dk + (256 >> 4), 1);
        wgmma_commit();
        wgmma_wait<0>();
        uint32_t P[16];
#pragma unroll
        for (int i = 0; i < 8; i++) {
          P[2 * i] = pack_bf16(ex2_mufu(S[4 * i] - mx0), ex2_mufu(S[4 * i + 1] - mx0));
          P[2 * i + 1] = pack_bf16(ex2_mufu(S[4 * i + 2] - mx1), ex2_mufu(S[4 * i + 3] - mx1));
        }
        wgmma_fence();
        const uint64_t dv = make_desc(sV + j * 8 * 384, 384, 128, 0);
#pragma unroll
        for (int ks = 0; ks < 4; ks++)
          wgmma_rs_n24_tb(O, P[4 * ks], P[4 * ks + 1], P[4 * ks + 2], P[4 * ks + 3], dv + ((ks * 768) >> 4), (j | ks) != 0);
        wgmma_commit();
      }
    }
    wgmma_wait<0>();
#pragma unroll
    for (int i = 0; i < 12; i++) asm volatile("" : "+f"(O[i]) :: "memory");
    const float l0 = __shfl_sync(~0u, O[8], (lane & ~3) | 2), l1 = __shfl_sync(~0u, O[10], (lane & ~3) | 2);
    const float r0 = 1.f / l0, r1 = 1.f / l1;
    uint32_t* o0 = (uint32_t*)(g_o + (size_t)(q0 + g) * DM + h * DH);
    uint32_t* o1 = (uint32_t*)(g_o + (size_t)(q0 + g + 8) * DM + h * DH);
    o0[t] = pack_bf16(O[0] * r0, O[1] * r0); o1[t] = pack_bf16(O[2] * r1, O[3] * r1);
    o0[t + 4] = pack_bf16(O[4] * r0, O[5] * r0); o1[t + 4] = pack_bf16(O[6] * r1, O[7] * r1);
    if (t < 2) { o0[t + 8] = pack_bf16(O[8] * r0, O[9] * r0); o1[t + 8] = pack_bf16(O[10] * r1, O[11] * r1); }
  }
}

typedef CUresult (*EncodeFn)(CUtensorMap*, CUtensorMapDataType, cuuint32_t, void*, const cuuint64_t*, const cuuint64_t*, const cuuint32_t*,
                             const cuuint32_t*, CUtensorMapInterleave, CUtensorMapSwizzle, CUtensorMapL2promotion, CUtensorMapFloatOOBfill);
static EncodeFn get_encode() {
  static EncodeFn fn = nullptr;
  if (!fn) {
    void* p = nullptr; cudaDriverEntryPointQueryResult st;
    cudaGetDriverEntryPoint("cuTensorMapEncodeTiled", &p, cudaEnableDefault, &st);
    fn = (EncodeFn)p;
  }
  return fn;
}
static CUtensorMap make_map(const void* ptr, int rows, int cols, int box_rows) {
  CUtensorMap m;
  cuuint64_t dims[2] = {(cuuint64_t)cols, (cuuint64_t)rows};
  cuuint64_t strides[1] = {(cuuint64_t)cols * 2};
  cuuint32_t box[2] = {64, (cuuint32_t)box_rows};
  cuuint32_t es[2] = {1, 1};
  get_encode()(&m, CU_TENSOR_MAP_DATA_TYPE_BFLOAT16, 2, const_cast<void*>(ptr), dims, strides, box, es, CU_TENSOR_MAP_INTERLEAVE_NONE,
               CU_TENSOR_MAP_SWIZZLE_128B, CU_TENSOR_MAP_L2_PROMOTION_L2_128B, CU_TENSOR_MAP_FLOAT_OOB_FILL_NONE);
  return m;
}
template <typename... KArgs, typename... Args>
static void launch(void (*kern)(KArgs...), dim3 grid, dim3 block, size_t smem, bool pdl, Args... args) {
  cudaLaunchConfig_t cfg = {};
  cfg.gridDim = grid; cfg.blockDim = block; cfg.dynamicSmemBytes = smem; cfg.stream = cudaStreamPerThread;
  cudaLaunchAttribute at[1];
  at[0].id = cudaLaunchAttributeProgrammaticStreamSerialization;
  at[0].val.programmaticStreamSerializationAllowed = 1;
  cfg.attrs = at; cfg.numAttrs = pdl ? 1 : 0;
  cudaLaunchKernelEx(&cfg, kern, KArgs(args)...);
}

extern "C" void kernel_launch(void* const* d_in, const int* in_sizes, int n_in, void* d_out, int out_size) {
  const __nv_bfloat16* x = (const __nv_bfloat16*)d_in[0];
  const __nv_bfloat16* wqkv = (const __nv_bfloat16*)d_in[1];
  const __nv_bfloat16* wo = (const __nv_bfloat16*)d_in[2];
  const __nv_bfloat16* wgate = (const __nv_bfloat16*)d_in[4];
  const __nv_bfloat16* wup = (const __nv_bfloat16*)d_in[5];
  const __nv_bfloat16* wdown = (const __nv_bfloat16*)d_in[6];
  __nv_bfloat16* out = (__nv_bfloat16*)d_out;
  void *p_o, *p_h, *p_act;
  cudaGetSymbolAddress(&p_o, g_o); cudaGetSymbolAddress(&p_h, g_h); cudaGetSymbolAddress(&p_act, g_act);

  auto kA = gemm_kernel<256, 128, 1, DM, 4, EPI_QKV, 1>;
  auto kC = gemm_kernel<128, 64, 1, DM, 4, EPI_WO, 2>;
  auto kD = gemm_kernel<128, 192, 2, DM, 3, EPI_GLU, 1>;
  auto kE = gemm_kernel<128, 64, 1, DFF, 4, EPI_DOWN, 2>;
  constexpr int smA = GemmCfg<256, 128, 1, 4>::SMEM, smC = GemmCfg<128, 64, 1, 4>::SMEM, smD = GemmCfg<128, 192, 2, 3>::SMEM;
  cudaFuncSetAttribute(kA, cudaFuncAttributeMaxDynamicSharedMemorySize, smA);
  cudaFuncSetAttribute(kC, cudaFuncAttributeMaxDynamicSharedMemorySize, smC);
  cudaFuncSetAttribute(kD, cudaFuncAttributeMaxDynamicSharedMemorySize, smD);
  cudaFuncSetAttribute(kE, cudaFuncAttributeMaxDynamicSharedMemorySize, smC);
  cudaFuncSetAttribute(attn_kernel, cudaFuncAttributeMaxDynamicSharedMemorySize, ATT_SMEM);

  const CUtensorMap tm_x = make_map(x, S_LEN, DM, 256), tm_wqkv = make_map(wqkv, DM, 3 * DM, 64);
  const CUtensorMap tm_o = make_map(p_o, S_LEN, DM, 128), tm_wo = make_map(wo, DM, DM, 64);
  const CUtensorMap tm_h = make_map(p_h, S_LEN, DM, 128), tm_wg = make_map(wgate, DM, DFF, 64), tm_wu = make_map(wup, DM, DFF, 64);
  const CUtensorMap tm_act = make_map(p_act, S_LEN, DFF, 128), tm_wd = make_map(wdown, DFF, DM, 64);

  launch(pre_kernel, dim3(PRE_COL_BLOCKS + PRE_ROW_BLOCKS), dim3(256), 0, false, x, wqkv, wgate, wup);
  launch(kA, dim3(15, 8), dim3(288), smA, true, tm_x, tm_wqkv, tm_wqkv, (const __nv_bfloat16*)nullptr, (__nv_bfloat16*)nullptr);
  launch(attn_kernel, dim3(128), dim3(512), ATT_SMEM, true, 0x800000);
  launch(kC, dim3(10, 16), dim3(288), smC, true, tm_o, tm_wo, tm_wo, x, (__nv_bfloat16*)p_h);
  launch(kD, dim3(8, 16), dim3(384), smD, true, tm_h, tm_wg, tm_wu, (const __nv_bfloat16*)nullptr, (__nv_bfloat16*)p_act);
  launch(kE, dim3(10, 16), dim3(288), smC, true, tm_act, tm_wd, tm_wd, (const __nv_bfloat16*)p_h, out);
}
```

```cpp
#include <cuda_runtime.h>
#include <cuda_bf16.h>
#include <cuda.h>
#include <stdint.h>

constexpr int S_LEN = 2048, DM = 640, NH = 32, DH = 20, DFF = 1536;

__device__ __align__(1024) __nv_bfloat16 g_q[S_LEN * DM];
__device__ __align__(1024) __nv_bfloat16 g_k[NH * S_LEN * 24];
__device__ __align__(1024) __nv_bfloat16 g_v[NH * S_LEN * 24];
__device__ __align__(1024) __nv_bfloat16 g_o[S_LEN * DM];
__device__ __align__(1024) __nv_bfloat16 g_h[S_LEN * DM];
__device__ __align__(1024) __nv_bfloat16 g_act[S_LEN * DFF];
__device__ float g_kn[8 * NH * 2];
__device__ float2 g_stat1[S_LEN];
__device__ float g_cs_qkv[3 * DM];
__device__ float g_cs_g[DFF];
__device__ float g_cs_u[DFF];
__device__ float2 g_part2[S_LEN * 10];

#define TS_BEGIN(k)
#define TS_END(k)
#define TS_MID(k, i)
__device__ __forceinline__ uint32_t smem_u32(const void* p) { return (uint32_t)__cvta_generic_to_shared(p); }
__device__ __forceinline__ void mbar_init(uint32_t bar, uint32_t cnt) { asm volatile("mbarrier.init.shared::cta.b64 [%0], %1;" :: "r"(bar), "r"(cnt)); }
__device__ __forceinline__ void mbar_expect_tx(uint32_t bar, uint32_t bytes) { asm volatile("mbarrier.arrive.expect_tx.shared::cta.b64 _, [%0], %1;" :: "r"(bar), "r"(bytes) : "memory"); }
__device__ __forceinline__ void mbar_arrive(uint32_t bar) { asm volatile("mbarrier.arrive.shared::cta.b64 _, [%0];" :: "r"(bar) : "memory"); }
__device__ __forceinline__ void mbar_wait(uint32_t bar, uint32_t parity) {
  uint32_t done;
  uint32_t spins = 0;
  do {
    asm volatile("{\n.reg .pred P1;\nmbarrier.try_wait.parity.shared::cta.b64 P1, [%1], %2;\nselp.u32 %0, 1, 0, P1;\n}" : "=r"(done) : "r"(bar), "r"(parity) : "memory");
  } while (!done && ++spins < (1u << 24));
}
__device__ __forceinline__ void bulk_g2s(uint32_t dst, const void* src, uint32_t bytes, uint32_t bar) {
  asm volatile("cp.async.bulk.shared::cluster.global.mbarrier::complete_tx::bytes [%0], [%1], %2, [%3];" :: "r"(dst), "l"(src), "r"(bytes), "r"(bar) : "memory");
}
__device__ __forceinline__ void tma_2d(uint32_t dst, const CUtensorMap* tm, int c0, int c1, uint32_t bar) {
  asm volatile("cp.async.bulk.tensor.2d.shared::cluster.global.mbarrier::complete_tx::bytes [%0], [%1, {%3, %4}], [%2];"
               :: "r"(dst), "l"(tm), "r"(bar), "r"(c0), "r"(c1) : "memory");
}
__device__ __forceinline__ void tma_2d_mc(uint32_t dst, const CUtensorMap* tm, int c0, int c1, uint32_t bar, uint16_t mask) {
  asm volatile("cp.async.bulk.tensor.2d.shared::cluster.global.mbarrier::complete_tx::bytes.multicast::cluster [%0], [%1, {%3, %4}], [%2], %5;"
               :: "r"(dst), "l"(tm), "r"(bar), "r"(c0), "r"(c1), "h"(mask) : "memory");
}
__device__ __forceinline__ void mbar_arrive_remote(uint32_t bar, uint32_t rank) {
  asm volatile("{\n.reg .b32 ra;\nmapa.shared::cluster.u32 ra, %0, %1;\nmbarrier.arrive.release.cluster.shared::cluster.b64 _, [ra];\n}" :: "r"(bar), "r"(rank) : "memory");
}
__device__ __forceinline__ void cluster_arrive() { asm volatile("barrier.cluster.arrive.release.aligned;" ::: "memory"); }
__device__ __forceinline__ void cluster_wait() { asm volatile("barrier.cluster.wait.acquire.aligned;" ::: "memory"); }
__device__ __forceinline__ void wgmma_fence() { asm volatile("wgmma.fence.sync.aligned;" ::: "memory"); }
__device__ __forceinline__ void wgmma_commit() { asm volatile("wgmma.commit_group.sync.aligned;" ::: "memory"); }
template <int N> __device__ __forceinline__ void wgmma_wait() { asm volatile("wgmma.wait_group.sync.aligned %0;" :: "n"(N) : "memory"); }
__device__ __forceinline__ void pdl_wait() { asm volatile("griddepcontrol.wait;" ::: "memory"); }
__device__ __forceinline__ void pdl_launch() { asm volatile("griddepcontrol.launch_dependents;" ::: "memory"); }
__device__ __forceinline__ void named_bar(int id, int n) { asm volatile("bar.sync %0, %1;" :: "r"(id), "r"(n) : "memory"); }
__device__ __forceinline__ uint64_t make_desc(uint32_t addr, uint32_t lbo, uint32_t sbo, uint32_t swz) {
  return (uint64_t)((addr & 0x3FFFF) >> 4) | ((uint64_t)(lbo >> 4) << 16) | ((uint64_t)(sbo >> 4) << 32) | ((uint64_t)swz << 62);
}
__device__ __forceinline__ uint32_t pack_bf16(float lo, float hi) { uint32_t r; asm("cvt.rn.bf16x2.f32 %0, %1, %2;" : "=r"(r) : "f"(hi), "f"(lo)); return r; }
__device__ __forceinline__ float bf_lo(uint32_t u) { return __uint_as_float(u << 16); }
__device__ __forceinline__ float bf_hi(uint32_t u) { return __uint_as_float(u & 0xffff0000u); }
__device__ __forceinline__ float bf_round(float x) { return __bfloat162float(__float2bfloat16_rn(x)); }
__device__ __forceinline__ float ex2_mufu(float x) { float y; asm("ex2.approx.ftz.f32 %0, %1;" : "=f"(y) : "f"(x)); return y; }

__device__ __forceinline__ void wgmma_ss_n64(float (&d)[32], uint64_t da, uint64_t db, int scale_d) {
  asm volatile("{\n.reg .pred p;\nsetp.ne.b32 p, %34, 0;\n"
    "wgmma.mma_async.sync.aligned.m64n64k16.f32.bf16.bf16 {%0,%1,%2,%3,%4,%5,%6,%7,%8,%9,%10,%11,%12,%13,%14,%15,%16,%17,%18,%19,%20,%21,%22,%23,%24,%25,%26,%27,%28,%29,%30,%31}, %32, %33, p, 1, 1, 0, 1;\n}\n"
    : "+f"(d[0]),"+f"(d[1]),"+f"(d[2]),"+f"(d[3]),"+f"(d[4]),"+f"(d[5]),"+f"(d[6]),"+f"(d[7]),"+f"(d[8]),"+f"(d[9]),"+f"(d[10]),"+f"(d[11]),"+f"(d[12]),"+f"(d[13]),"+f"(d[14]),"+f"(d[15]),"+f"(d[16]),"+f"(d[17]),"+f"(d[18]),"+f"(d[19]),"+f"(d[20]),"+f"(d[21]),"+f"(d[22]),"+f"(d[23]),"+f"(d[24]),"+f"(d[25]),"+f"(d[26]),"+f"(d[27]),"+f"(d[28]),"+f"(d[29]),"+f"(d[30]),"+f"(d[31])
    : "l"(da), "l"(db), "r"(scale_d));
}
__device__ __forceinline__ void wgmma_ss_n128(float (&d)[64], uint64_t da, uint64_t db, int scale_d) {
  asm volatile("{\n.reg .pred p;\nsetp.ne.b32 p, %66, 0;\n"
    "wgmma.mma_async.sync.aligned.m64n128k16.f32.bf16.bf16 {%0,%1,%2,%3,%4,%5,%6,%7,%8,%9,%10,%11,%12,%13,%14,%15,%16,%17,%18,%19,%20,%21,%22,%23,%24,%25,%26,%27,%28,%29,%30,%31,%32,%33,%34,%35,%36,%37,%38,%39,%40,%41,%42,%43,%44,%45,%46,%47,%48,%49,%50,%51,%52,%53,%54,%55,%56,%57,%58,%59,%60,%61,%62,%63}, %64, %65, p, 1, 1, 0, 1;\n}\n"
    : "+f"(d[0]),"+f"(d[1]),"+f"(d[2]),"+f"(d[3]),"+f"(d[4]),"+f"(d[5]),"+f"(d[6]),"+f"(d[7]),"+f"(d[8]),"+f"(d[9]),"+f"(d[10]),"+f"(d[11]),"+f"(d[12]),"+f"(d[13]),"+f"(d[14]),"+f"(d[15]),"+f"(d[16]),"+f"(d[17]),"+f"(d[18]),"+f"(d[19]),"+f"(d[20]),"+f"(d[21]),"+f"(d[22]),"+f"(d[23]),"+f"(d[24]),"+f"(d[25]),"+f"(d[26]),"+f"(d[27]),"+f"(d[28]),"+f"(d[29]),"+f"(d[30]),"+f"(d[31]),"+f"(d[32]),"+f"(d[33]),"+f"(d[34]),"+f"(d[35]),"+f"(d[36]),"+f"(d[37]),"+f"(d[38]),"+f"(d[39]),"+f"(d[40]),"+f"(d[41]),"+f"(d[42]),"+f"(d[43]),"+f"(d[44]),"+f"(d[45]),"+f"(d[46]),"+f"(d[47]),"+f"(d[48]),"+f"(d[49]),"+f"(d[50]),"+f"(d[51]),"+f"(d[52]),"+f"(d[53]),"+f"(d[54]),"+f"(d[55]),"+f"(d[56]),"+f"(d[57]),"+f"(d[58]),"+f"(d[59]),"+f"(d[60]),"+f"(d[61]),"+f"(d[62]),"+f"(d[63])
    : "l"(da), "l"(db), "r"(scale_d));
}
__device__ __forceinline__ void wgmma_ss_n192(float (&d)[96], uint64_t da, uint64_t db, int scale_d) {
  asm volatile("{\n.reg .pred p;\nsetp.ne.b32 p, %98, 0;\n"
    "wgmma.mma_async.sync.aligned.m64n192k16.f32.bf16.bf16 {%0,%1,%2,%3,%4,%5,%6,%7,%8,%9,%10,%11,%12,%13,%14,%15,%16,%17,%18,%19,%20,%21,%22,%23,%24,%25,%26,%27,%28,%29,%30,%31,%32,%33,%34,%35,%36,%37,%38,%39,%40,%41,%42,%43,%44,%45,%46,%47,%48,%49,%50,%51,%52,%53,%54,%55,%56,%57,%58,%59,%60,%61,%62,%63,%64,%65,%66,%67,%68,%69,%70,%71,%72,%73,%74,%75,%76,%77,%78,%79,%80,%81,%82,%83,%84,%85,%86,%87,%88,%89,%90,%91,%92,%93,%94,%95}, %96, %97, p, 1, 1, 0, 1;\n}\n"
    : "+f"(d[0]),"+f"(d[1]),"+f"(d[2]),"+f"(d[3]),"+f"(d[4]),"+f"(d[5]),"+f"(d[6]),"+f"(d[7]),"+f"(d[8]),"+f"(d[9]),"+f"(d[10]),"+f"(d[11]),"+f"(d[12]),"+f"(d[13]),"+f"(d[14]),"+f"(d[15]),"+f"(d[16]),"+f"(d[17]),"+f"(d[18]),"+f"(d[19]),"+f"(d[20]),"+f"(d[21]),"+f"(d[22]),"+f"(d[23]),"+f"(d[24]),"+f"(d[25]),"+f"(d[26]),"+f"(d[27]),"+f"(d[28]),"+f"(d[29]),"+f"(d[30]),"+f"(d[31]),"+f"(d[32]),"+f"(d[33]),"+f"(d[34]),"+f"(d[35]),"+f"(d[36]),"+f"(d[37]),"+f"(d[38]),"+f"(d[39]),"+f"(d[40]),"+f"(d[41]),"+f"(d[42]),"+f"(d[43]),"+f"(d[44]),"+f"(d[45]),"+f"(d[46]),"+f"(d[47]),"+f"(d[48]),"+f"(d[49]),"+f"(d[50]),"+f"(d[51]),"+f"(d[52]),"+f"(d[53]),"+f"(d[54]),"+f"(d[55]),"+f"(d[56]),"+f"(d[57]),"+f"(d[58]),"+f"(d[59]),"+f"(d[60]),"+f"(d[61]),"+f"(d[62]),"+f"(d[63]),"+f"(d[64]),"+f"(d[65]),"+f"(d[66]),"+f"(d[67]),"+f"(d[68]),"+f"(d[69]),"+f"(d[70]),"+f"(d[71]),"+f"(d[72]),"+f"(d[73]),"+f"(d[74]),"+f"(d[75]),"+f"(d[76]),"+f"(d[77]),"+f"(d[78]),"+f"(d[79]),"+f"(d[80]),"+f"(d[81]),"+f"(d[82]),"+f"(d[83]),"+f"(d[84]),"+f"(d[85]),"+f"(d[86]),"+f"(d[87]),"+f"(d[88]),"+f"(d[89]),"+f"(d[90]),"+f"(d[91]),"+f"(d[92]),"+f"(d[93]),"+f"(d[94]),"+f"(d[95])
    : "l"(da), "l"(db), "r"(scale_d));
}
__device__ __forceinline__ void wgmma_rs_n64(float (&d)[32], uint32_t a0, uint32_t a1, uint32_t a2, uint32_t a3, uint64_t db, int scale_d) {
  asm volatile("{\n.reg .pred p;\nsetp.ne.b32 p, %37, 0;\n"
    "wgmma.mma_async.sync.aligned.m64n64k16.f32.bf16.bf16 {%0,%1,%2,%3,%4,%5,%6,%7,%8,%9,%10,%11,%12,%13,%14,%15,%16,%17,%18,%19,%20,%21,%22,%23,%24,%25,%26,%27,%28,%29,%30,%31}, {%32,%33,%34,%35}, %36, p, 1, 1, 0;\n}\n"
    : "+f"(d[0]),"+f"(d[1]),"+f"(d[2]),"+f"(d[3]),"+f"(d[4]),"+f"(d[5]),"+f"(d[6]),"+f"(d[7]),"+f"(d[8]),"+f"(d[9]),"+f"(d[10]),"+f"(d[11]),"+f"(d[12]),"+f"(d[13]),"+f"(d[14]),"+f"(d[15]),"+f"(d[16]),"+f"(d[17]),"+f"(d[18]),"+f"(d[19]),"+f"(d[20]),"+f"(d[21]),"+f"(d[22]),"+f"(d[23]),"+f"(d[24]),"+f"(d[25]),"+f"(d[26]),"+f"(d[27]),"+f"(d[28]),"+f"(d[29]),"+f"(d[30]),"+f"(d[31])
    : "r"(a0), "r"(a1), "r"(a2), "r"(a3), "l"(db), "r"(scale_d));
}
__device__ __forceinline__ void wgmma_rs_n24_tb(float (&d)[12], uint32_t a0, uint32_t a1, uint32_t a2, uint32_t a3, uint64_t db, int scale_d) {
  asm volatile("{\n.reg .pred p;\nsetp.ne.b32 p, %17, 0;\n"
    "wgmma.mma_async.sync.aligned.m64n24k16.f32.bf16.bf16 {%0,%1,%2,%3,%4,%5,%6,%7,%8,%9,%10,%11}, {%12,%13,%14,%15}, %16, p, 1, 1, 1;\n}\n"
    : "+f"(d[0]),"+f"(d[1]),"+f"(d[2]),"+f"(d[3]),"+f"(d[4]),"+f"(d[5]),"+f"(d[6]),"+f"(d[7]),"+f"(d[8]),"+f"(d[9]),"+f"(d[10]),"+f"(d[11])
    : "r"(a0), "r"(a1), "r"(a2), "r"(a3), "l"(db), "r"(scale_d));
}

constexpr int PRE_ROW_BLOCKS = 64;
constexpr int PRE_COL_BLOCKS = (3 * DM + 2 * DFF) / 64;
__device__ __forceinline__ float2 ln_finish(float mean, float var) {
  float mb = bf_round(mean);
  float s = bf_round(sqrtf(bf_round(bf_round(var) + 1e-5f)));
  return make_float2(mb, 1.0f / s);
}
__global__ void __launch_bounds__(256) pre_kernel(const __nv_bfloat16* __restrict__ x, const __nv_bfloat16* __restrict__ wqkv,
                                                  const __nv_bfloat16* __restrict__ wg, const __nv_bfloat16* __restrict__ wu) {
  TS_BEGIN(0);
  pdl_launch();
  const int tid = threadIdx.x, lane = tid & 31, warp = tid >> 5;
  if (blockIdx.x < PRE_COL_BLOCKS) {
    __shared__ float red[32][65];
    int c0 = blockIdx.x * 64;
    const __nv_bfloat16* w; float* dst; int ld;
    if (c0 < 3 * DM) { w = wqkv; dst = g_cs_qkv; ld = 3 * DM; }
    else if (c0 < 3 * DM + DFF) { w = wg; dst = g_cs_g; ld = DFF; c0 -= 3 * DM; }
    else { w = wu; dst = g_cs_u; ld = DFF; c0 -= 3 * DM + DFF; }
    const int cg = tid & 7, r0 = tid >> 3;
    float acc[8];
#pragma unroll
    for (int i = 0; i < 8; i++) acc[i] = 0.f;
#pragma unroll 5
    for (int r = r0; r < DM; r += 32) {
      uint4 v = __ldg((const uint4*)(w + (size_t)r * ld + c0 + cg * 8));
      acc[0] += bf_lo(v.x); acc[1] += bf_hi(v.x); acc[2] += bf_lo(v.y); acc[3] += bf_hi(v.y);
      acc[4] += bf_lo(v.z); acc[5] += bf_hi(v.z); acc[6] += bf_lo(v.w); acc[7] += bf_hi(v.w);
    }
#pragma unroll
    for (int i = 0; i < 8; i++) red[r0][cg * 8 + i] = acc[i];
    __syncthreads();
    if (tid < 64) {
      float s = 0.f;
#pragma unroll
      for (int r = 0; r < 32; r++) s += red[r][tid];
      dst[c0 + tid] = s;
    }
  } else {
    const int rb = blockIdx.x - PRE_COL_BLOCKS;
#pragma unroll
    for (int i = 0; i < 4; i++) {
      const int row = rb * 32 + warp * 4 + i;
      const uint4* p = (const uint4*)(x + (size_t)row * DM);
      uint4 v0 = __ldg(p + lane), v1 = __ldg(p + 32 + lane), v2 = make_uint4(0, 0, 0, 0);
      if (lane < 16) v2 = __ldg(p + 64 + lane);
      float f[24];
      uint32_t u[12] = {v0.x, v0.y, v0.z, v0.w, v1.x, v1.y, v1.z, v1.w, v2.x, v2.y, v2.z, v2.w};
#pragma unroll
      for (int j = 0; j < 12; j++) { f[2 * j] = bf_lo(u[j]); f[2 * j + 1] = bf_hi(u[j]); }
      float s = 0.f;
#pragma unroll
      for (int j = 0; j < 24; j++) s += f[j];
#pragma unroll
      for (int o = 16; o; o >>= 1) s += __shfl_xor_sync(~0u, s, o);
      const float mean = s * (1.0f / DM);
      float q = 0.f;
#pragma unroll
      for (int j = 0; j < 16; j++) { float d = f[j] - mean; q += d * d; }
      if (lane < 16) {
#pragma unroll
        for (int j = 16; j < 24; j++) { float d = f[j] - mean; q += d * d; }
      }
#pragma unroll
      for (int o = 16; o; o >>= 1) q += __shfl_xor_sync(~0u, q, o);
      if (lane == 0) g_stat1[row] = ln_finish(mean, q * (1.0f / DM));
    }
  }
  TS_END(0);
}

enum { EPI_QKV = 0, EPI_WO = 1, EPI_GLU = 2, EPI_DOWN = 3 };
template <int N> struct WG;
template <> struct WG<64>  { static __device__ __forceinline__ void mma(float (&d)[32], uint64_t a, uint64_t b, int s) { wgmma_ss_n64(d, a, b, s); } };
template <> struct WG<128> { static __device__ __forceinline__ void mma(float (&d)[64], uint64_t a, uint64_t b, int s) { wgmma_ss_n128(d, a, b, s); } };
template <> struct WG<192> { static __device__ __forceinline__ void mma(float (&d)[96], uint64_t a, uint64_t b, int s) { wgmma_ss_n192(d, a, b, s); } };

template <int BM, int BN, int NB, int STAGES> struct GemmCfg {
  static constexpr int A_BYTES = BM * 128;
  static constexpr int B_BYTES = NB * (BN / 64) * 8192;
  static constexpr int STAGE_BYTES = A_BYTES + B_BYTES;
  static constexpr int SMEM = STAGES * STAGE_BYTES + 1024   + 256   + 4096  ;
};

constexpr float QSCALE = 0.22360679774997896f * 1.4426950408889634f;

template <int BM, int BN, int NB, int KDIM, int STAGES, int EPI, int MINB, int CN, int CM>
__global__ void __launch_bounds__(EPI == EPI_GLU ? 384 : 288, MINB) gemm_kernel(const __grid_constant__ CUtensorMap tmA, const __grid_constant__ CUtensorMap tmB0,
                                                         const __grid_constant__ CUtensorMap tmB1,
                                                         const __nv_bfloat16* __restrict__ resid, __nv_bfloat16* __restrict__ out) {
  using Cfg = GemmCfg<BM, BN, NB, STAGES>;
  constexpr int MB = BM / 128;
  constexpr int KT = KDIM / 64;
  extern __shared__ uint8_t smem_raw[];
  const uint32_t sbase = (smem_u32(smem_raw) + 1023u) & ~1023u;
  uint8_t* sptr = smem_raw + (sbase - smem_u32(smem_raw));
  const uint32_t sbar = sbase + STAGES * Cfg::STAGE_BYTES;
  const int tid = threadIdx.x, warp = tid >> 5, lane = tid & 31;
  const int n0 = blockIdx.x * BN, m0 = blockIdx.y * BM;
  TS_BEGIN(EPI == EPI_QKV ? 1 : EPI + 2);
  constexpr int NCL = CN + CM - 1;
  const int cx = blockIdx.x % CN, cy = blockIdx.y % CM;
  if (tid == 0) {
    for (int i = 0; i < STAGES; i++) { mbar_init(sbar + 8 * i, 1); mbar_init(sbar + 8 * (STAGES + i), 2 * NCL); }
    asm volatile("fence.mbarrier_init.release.cluster;" ::: "memory");
  }
  __syncthreads();
  if constexpr (CN * CM > 1) { cluster_arrive(); cluster_wait(); }
  pdl_launch();
  if (warp >= 8) {
    if constexpr (EPI == EPI_GLU) asm volatile("setmaxnreg.dec.sync.aligned.u32 40;");
    if (warp == 8 && lane == 0) {
      uint16_t maskA = 0, maskB = 0;
#pragma unroll
      for (int i = 0; i < CN; i++) maskA |= (uint16_t)(1u << (cy * CN + i));
#pragma unroll
      for (int j = 0; j < CM; j++) maskB |= (uint16_t)(1u << (j * CN + cx));
      auto load_a = [&](int kt, int s) {
        const uint32_t dst = sbase + s * Cfg::STAGE_BYTES + cx * (BM / CN) * 128;
        if constexpr (CN > 1) tma_2d_mc(dst, &tmA, kt * 64, m0 + cx * (BM / CN), sbar + 8 * s, maskA);
        else tma_2d(dst, &tmA, kt * 64, m0, sbar + 8 * s);
      };
      auto load_b = [&](int kt, int s) {
        const uint32_t sb = sbase + s * Cfg::STAGE_BYTES + Cfg::A_BYTES;
        constexpr int NBOX = NB * (BN / 64);
        if constexpr (CM > 1 && NBOX % CM != 0) {
#pragma unroll
          for (int j = 0; j < NBOX; j++)
            tma_2d_mc(sb + j * 8192 + cy * (64 / CM) * 128, (NB == 2 && j >= BN / 64) ? &tmB1 : &tmB0, n0 + (j % (BN / 64)) * 64, kt * 64 + cy * (64 / CM), sbar + 8 * s, maskB);
        } else {
#pragma unroll
          for (int j = 0; j < NBOX; j++) {
            const CUtensorMap* tm = (NB == 2 && j >= BN / 64) ? &tmB1 : &tmB0;
            if constexpr (CM > 1) { if (j % CM == cy) tma_2d_mc(sb + j * 8192, tm, n0 + (j % (BN / 64)) * 64, kt * 64, sbar + 8 * s, maskB); }
            else tma_2d(sb + j * 8192, tm, n0 + (j % (BN / 64)) * 64, kt * 64, sbar + 8 * s);
          }
        }
      };
      for (int s = 0; s < STAGES; s++) { mbar_expect_tx(sbar + 8 * s, Cfg::STAGE_BYTES); load_b(s, s); }
      if (EPI != EPI_QKV) pdl_wait();
      for (int s = 0; s < STAGES; s++) load_a(s, s);
      for (int kt = STAGES; kt < KT; kt++) {
        const int s = kt % STAGES;
        mbar_wait(sbar + 8 * (STAGES + s), ((kt / STAGES) - 1) & 1);
        mbar_expect_tx(sbar + 8 * s, Cfg::STAGE_BYTES);
        load_a(kt, s);
        load_b(kt, s);
      }
    }
    if constexpr (EPI == EPI_GLU) {
      if (warp > 8) {
        float2* s_st = (float2*)(sptr + STAGES * Cfg::STAGE_BYTES + 256);
        float* s_cs = (float*)(sptr + STAGES * Cfg::STAGE_BYTES + 256 + 1024);
        pdl_wait();
        for (int r = tid - 288; r < BM; r += 96) {
          const float2* pp = &g_part2[(m0 + r) * 10];
          float s = 0.f;
#pragma unroll
          for (int i = 0; i < 10; i++) s += pp[i].x;
          const float mean = s * (1.0f / DM);
          float q = 0.f;
#pragma unroll
          for (int i = 0; i < 10; i++) { const float2 p = pp[i]; const float d = p.x * (1.0f / 64.f) - mean; q += p.y + 64.f * d * d; }
          s_st[r] = ln_finish(mean, q * (1.0f / DM));
        }
        for (int c = tid - 288; c < BN; c += 96) { s_cs[c] = g_cs_g[n0 + c]; s_cs[BN + c] = g_cs_u[n0 + c]; }
        __threadfence_block();
        asm volatile("bar.arrive 2, 352;" ::: "memory");
      }
    }
    if constexpr (CN * CM > 1) { __syncwarp(); cluster_arrive(); cluster_wait(); }
    return;
  }
  if constexpr (EPI == EPI_GLU) asm volatile("setmaxnreg.inc.sync.aligned.u32 232;");
  const int wg = warp >> 2, g = lane >> 2, t = lane & 3;
  float acc[MB][NB][BN / 2];
#pragma unroll
  for (int mb = 0; mb < MB; mb++)
#pragma unroll
    for (int nb = 0; nb < NB; nb++)
#pragma unroll
      for (int i = 0; i < BN / 2; i++) acc[mb][nb][i] = 0.f;
  for (int kt = 0; kt < KT; kt++) {
    const int s = kt % STAGES;
    mbar_wait(sbar + 8 * s, (kt / STAGES) & 1);
    if (kt == 0) TS_MID(EPI == EPI_QKV ? 1 : EPI + 2, 0);
    const uint32_t sa = sbase + s * Cfg::STAGE_BYTES + wg * (MB * 64 * 128);
    const uint32_t sb = sbase + s * Cfg::STAGE_BYTES + Cfg::A_BYTES;
    wgmma_fence();
#pragma unroll
    for (int ks = 0; ks < 4; ks++) {
#pragma unroll
      for (int mb = 0; mb < MB; mb++) {
        const uint64_t da = make_desc(sa + mb * 8192 + ks * 32, 16, 1024, 1);
#pragma unroll
        for (int nb = 0; nb < NB; nb++) {
          const uint64_t db = make_desc(sb + nb * (BN / 64) * 8192 + ks * 2048, 8192, 1024, 1);
          WG<BN>::mma(acc[mb][nb], da, db, 1);
        }
      }
    }
    wgmma_commit();
    wgmma_wait<1>();
    if (kt > 0 && kt - 1 + STAGES < KT && (tid & 127) < NCL) {
      const uint32_t eb = sbar + 8 * (STAGES + (kt - 1) % STAGES);
      if constexpr (CN * CM > 1) {
        const int i = tid & 127;
        const uint32_t rank = i < CN ? cy * CN + i : ((i - CN + (i - CN >= cy ? 1 : 0)) * CN + cx);
        mbar_arrive_remote(eb, rank);
      } else mbar_arrive(eb);
    }
  }
  wgmma_wait<0>();
#pragma unroll
  for (int mb = 0; mb < MB; mb++)
#pragma unroll
    for (int nb = 0; nb < NB; nb++)
#pragma unroll
      for (int i = 0; i < BN / 2; i++) asm volatile("" : "+f"(acc[mb][nb][i]) :: "memory");
  if constexpr (CN * CM > 1) cluster_arrive();
  TS_MID(EPI == EPI_QKV ? 1 : EPI + 2, 1);
  pdl_wait();
  TS_MID(EPI == EPI_QKV ? 1 : EPI + 2, 2);
  named_bar(1, 256);
  constexpr int LDS = BN * 2 + 16;
  const int ctid = tid;

  if constexpr (EPI == EPI_QKV) {
    const int sec = n0 / DM;
#pragma unroll
    for (int mb = 0; mb < MB; mb++) {
      const int r0 = wg * (MB * 64) + mb * 64 + (warp & 3) * 16 + g;
      const float2 st0 = g_stat1[m0 + r0], st1 = g_stat1[m0 + r0 + 8];
      const float sc0 = sec == 0 ? st0.y * QSCALE : st0.y, sc1 = sec == 0 ? st1.y * QSCALE : st1.y;
#pragma unroll
      for (int j = 0; j < BN / 8; j++) {
        const float2 cs = *(const float2*)&g_cs_qkv[n0 + j * 8 + 2 * t];
        const float* a = &acc[mb][0][4 * j];
        *(uint32_t*)(sptr + r0 * LDS + j * 16 + t * 4) = pack_bf16((a[0] - st0.x * cs.x) * sc0, (a[1] - st0.x * cs.y) * sc0);
        *(uint32_t*)(sptr + (r0 + 8) * LDS + j * 16 + t * 4) = pack_bf16((a[2] - st1.x * cs.x) * sc1, (a[3] - st1.x * cs.y) * sc1);
      }
    }
    named_bar(1, 256);
    if (sec == 0) {
#pragma unroll
      for (int i = 0; i < BM * (BN / 8) / 256; i++) {
        const int idx = i * 256 + ctid, r = idx / (BN / 8), c = idx % (BN / 8);
        *(uint4*)(g_q + (size_t)(m0 + r) * DM + n0 + c * 8) = *(const uint4*)(sptr + r * LDS + c * 16);
      }
    } else {
      __nv_bfloat16* dst = sec == 1 ? g_k : g_v;
      const int cbase = n0 - sec * DM;
#pragma unroll 4
      for (int i = 0; i < BM * (BN / 4) / 256; i++) {
        const int idx = i * 256 + ctid;
        const int half = idx & 1, r8 = (idx >> 1) & 7, rest = idx >> 4;
        const int pq = rest % (BN / 8), rg = rest / (BN / 8);
        const int r = rg * 8 + r8, cq = pq * 2 + half;
        const int col = cbase + cq * 4, h = col / DH, qd = (col % DH) >> 2;
        const uint2 v = *(const uint2*)(sptr + r * LDS + cq * 8);
        const int j = m0 + r;
        uint8_t* p = (uint8_t*)dst + ((size_t)h * S_LEN * 24 + (j >> 3) * 192 + (qd >> 1) * 64 + (j & 7) * 8 + (qd & 1) * 4) * 2;
        if (qd == 4) *(uint4*)p = make_uint4(v.x, v.y, 0x00003f80u, 0u);
        else *(uint2*)p = v;
      }
      if (sec == 1) {
        __shared__ unsigned int s_kn[8];
        if (ctid < 8) s_kn[ctid] = 0u;
        named_bar(1, 256);
        const int hfirst = cbase / DH, hlast = (cbase + BN - 1) / DH;
        for (int hh = hfirst; hh <= hlast; hh++) {
          const int c_lo = max(hh * DH, cbase) - cbase, c_hi = min(hh * DH + DH, cbase + BN) - cbase;
          float mx = 0.f;
          for (int r = ctid; r < BM; r += 256) {
            float s = 0.f;
            for (int c = c_lo; c < c_hi; c += 4) {
              const uint2 v = *(const uint2*)(sptr + r * LDS + c * 2);
              s += bf_lo(v.x) * bf_lo(v.x) + bf_hi(v.x) * bf_hi(v.x) + bf_lo(v.y) * bf_lo(v.y) + bf_hi(v.y) * bf_hi(v.y);
            }
            mx = (s > mx || s != s) ? s : mx;
          }
          unsigned int mb_ = __float_as_uint(mx) & 0x7fffffffu;
          mb_ = __reduce_max_sync(~0u, mb_);
          if (lane == 0) atomicMax(&s_kn[hh - hfirst], mb_);
        }
        named_bar(1, 256);
        if (ctid <= hlast - hfirst) {
          const int hh = hfirst + ctid;
          const bool starts_here = hh * DH >= cbase, ends_here = hh * DH + DH <= cbase + BN;
          const float v = __uint_as_float(s_kn[ctid]);
          float* o = &g_kn[(blockIdx.y * NH + hh) * 2];
          if (starts_here) { o[0] = v; if (ends_here) o[1] = 0.f; }
          else o[1] = v;
        }
      }
    }
  } else if constexpr (EPI == EPI_WO || EPI == EPI_DOWN) {
    const int r0 = wg * 64 + (warp & 3) * 16 + g;
#pragma unroll
    for (int j = 0; j < BN / 8; j++) {
      const float* a = &acc[0][0][4 * j];
      *(uint32_t*)(sptr + r0 * LDS + j * 16 + t * 4) = pack_bf16(a[0], a[1]);
      *(uint32_t*)(sptr + (r0 + 8) * LDS + j * 16 + t * 4) = pack_bf16(a[2], a[3]);
    }
    named_bar(1, 256);
#pragma unroll
    for (int i = 0; i < BM * (BN / 8) / 256; i++) {
      const int idx = i * 256 + ctid, r = idx / (BN / 8), c = idx % (BN / 8);
      const uint4 a = *(const uint4*)(sptr + r * LDS + c * 16);
      const size_t go = (size_t)(m0 + r) * DM + n0 + c * 8;
      const uint4 b = *(const uint4*)(resid + go);
      uint4 o;
      o.x = pack_bf16(bf_lo(a.x) + bf_lo(b.x), bf_hi(a.x) + bf_hi(b.x));
      o.y = pack_bf16(bf_lo(a.y) + bf_lo(b.y), bf_hi(a.y) + bf_hi(b.y));
      o.z = pack_bf16(bf_lo(a.z) + bf_lo(b.z), bf_hi(a.z) + bf_hi(b.z));
      o.w = pack_bf16(bf_lo(a.w) + bf_lo(b.w), bf_hi(a.w) + bf_hi(b.w));
      *(uint4*)(out + go) = o;
      if constexpr (EPI == EPI_WO) {
        static_assert(BN == 64, "stats assume 8 lanes per row");
        const float f[8] = {bf_lo(o.x), bf_hi(o.x), bf_lo(o.y), bf_hi(o.y), bf_lo(o.z), bf_hi(o.z), bf_lo(o.w), bf_hi(o.w)};
        float s = 0.f;
#pragma unroll
        for (int k = 0; k < 8; k++) s += f[k];
        s += __shfl_xor_sync(~0u, s, 1); s += __shfl_xor_sync(~0u, s, 2); s += __shfl_xor_sync(~0u, s, 4);
        const float mu = s * (1.0f / 64.f);
        float q = 0.f;
#pragma unroll
        for (int k = 0; k < 8; k++) { const float d = f[k] - mu; q += d * d; }
        q += __shfl_xor_sync(~0u, q, 1); q += __shfl_xor_sync(~0u, q, 2); q += __shfl_xor_sync(~0u, q, 4);
        if (c == 0) g_part2[(m0 + r) * 10 + blockIdx.x] = make_float2(s, q);
      }
    }
  } else {
    const int r0 = wg * 64 + (warp & 3) * 16 + g;
    const float2* s_st = (const float2*)(sptr + STAGES * Cfg::STAGE_BYTES + 256);
    const float* s_cs = (const float*)(sptr + STAGES * Cfg::STAGE_BYTES + 256 + 1024);
    named_bar(2, 352);
    float2 st[2] = {s_st[r0], s_st[r0 + 8]};
#pragma unroll
    for (int j = 0; j < BN / 8; j++) {
      const float2 cg = *(const float2*)&s_cs[j * 8 + 2 * t], cu = *(const float2*)&s_cs[BN + j * 8 + 2 * t];
      const float* a = &acc[0][0][4 * j];
      const float* b = &acc[0][1][4 * j];
      float v[4];
#pragma unroll
      for (int e = 0; e < 4; e++) {
        const float2 s_ = st[e >> 1];
        const float gt = bf_round((a[e] - s_.x * ((e & 1) ? cg.y : cg.x)) * s_.y);
        const float up = bf_round((b[e] - s_.x * ((e & 1) ? cu.y : cu.x)) * s_.y);
        v[e] = (gt > 0.f ? gt : 0.f) * up;
      }
      *(uint32_t*)(sptr + r0 * LDS + j * 16 + t * 4) = pack_bf16(v[0], v[1]);
      *(uint32_t*)(sptr + (r0 + 8) * LDS + j * 16 + t * 4) = pack_bf16(v[2], v[3]);
    }
    named_bar(1, 256);
#pragma unroll
    for (int i = 0; i < BM * (BN / 8) / 256; i++) {
      const int idx = i * 256 + ctid, r = idx / (BN / 8), c = idx % (BN / 8);
      *(uint4*)(out + (size_t)(m0 + r) * DFF + n0 + c * 8) = *(const uint4*)(sptr + r * LDS + c * 16);
    }
  }
  if constexpr (CN * CM > 1) cluster_wait();
  TS_END(EPI == EPI_QKV ? 1 : EPI + 2);
}

#define POLY_NUM 5
__device__ __forceinline__ float ex2_poly(float x, int shl23) {
  const float MAGIC = 12582912.f;
  const float tt = x + MAGIC;
  const float f = x - (tt - MAGIC);
  float p = fmaf(0.0013276472454890609f, f, 0.009675540961325169f);
  p = fmaf(p, f, 0.05550713092088699f);
  p = fmaf(p, f, 0.24022120237350464f);
  p = fmaf(p, f, 0.6931469440460205f);
  p = fmaf(p, f, 1.0000001192092896f);
  return __int_as_float(__float_as_int(tt) * shl23 + __float_as_int(p));
}
constexpr int KV_BYTES = S_LEN * 48;
constexpr int ATT_SMEM = 2 * KV_BYTES + 256;

__global__ void __launch_bounds__(512, 1) attn_kernel(int shl23) {
  extern __shared__ __align__(1024) uint8_t smem[];
  const int h = blockIdx.x >> 2, qb = blockIdx.x & 3;
  const uint32_t sK = smem_u32(smem), sV = sK + KV_BYTES, sBar = sV + KV_BYTES;
  const int tid = threadIdx.x;
  TS_BEGIN(2);
  if (tid == 0) {
    for (int i = 0; i < 8; i++) mbar_init(sBar + 8 * i, 1);
    asm volatile("fence.mbarrier_init.release.cluster;" ::: "memory");
  }
  pdl_launch();
  pdl_wait();
  if (tid == 0) {
    const uint8_t* gk = (const uint8_t*)(g_k + (size_t)h * S_LEN * 24);
    const uint8_t* gv = (const uint8_t*)(g_v + (size_t)h * S_LEN * 24);
    for (int i = 0; i < 8; i++) {
      mbar_expect_tx(sBar + 8 * i, 2 * 12288);
      bulk_g2s(sK + i * 12288, gk + i * 12288, 12288, sBar + 8 * i);
      bulk_g2s(sV + i * 12288, gv + i * 12288, 12288, sBar + 8 * i);
    }
  }
  __syncthreads();
  const int wg = tid >> 7, warp = (tid >> 5) & 3, lane = tid & 31, g = lane >> 2, t = lane & 3;
  float ka = 0.f, kb = 0.f;
#pragma unroll
  for (int i = 0; i < 8; i++) {
    const float2 v = *(const float2*)&g_kn[(i * NH + h) * 2];
    ka = (v.x > ka || v.x != v.x) ? v.x : ka;
    kb = (v.y > kb || v.y != v.y) ? v.y : kb;
  }
  const float kn = sqrtf(ka + kb);
  for (int it = 0; it < 2; it++) {
    const int q0 = qb * 512 + (it * 4 + wg) * 64 + warp * 16;
    uint32_t qa[4], qc[4];
    const uint32_t* qr0 = (const uint32_t*)(g_q + (size_t)(q0 + g) * DM + h * DH);
    const uint32_t* qr1 = (const uint32_t*)(g_q + (size_t)(q0 + g + 8) * DM + h * DH);
    qa[0] = qr0[t]; qa[1] = qr1[t]; qa[2] = qr0[t + 4]; qa[3] = qr1[t + 4];
    qc[0] = (t < 2) ? qr0[t + 8] : 0u; qc[1] = (t < 2) ? qr1[t + 8] : 0u; qc[2] = 0; qc[3] = 0;
    auto sq = [](uint32_t u) { const float a = bf_lo(u), b = bf_hi(u); return a * a + b * b; };
    float n0 = sq(qa[0]) + sq(qa[2]) + sq(qc[0]);
    float n1 = sq(qa[1]) + sq(qa[3]) + sq(qc[1]);
    n0 += __shfl_xor_sync(~0u, n0, 1); n0 += __shfl_xor_sync(~0u, n0, 2);
    n1 += __shfl_xor_sync(~0u, n1, 1); n1 += __shfl_xor_sync(~0u, n1, 2);
    const float m0 = ceilf(sqrtf(n0) * kn * 1.001f) + 1.f, m1 = ceilf(sqrtf(n1) * kn * 1.001f) + 1.f;
    const bool unsafe = !(m0 <= 62.f && m1 <= 62.f);
    uint32_t any_unsafe;
    asm volatile("{\n.reg .pred p, q;\nsetp.ne.u32 p, %1, 0;\nbarrier.cta.red.or.pred q, %2, 128, p;\nselp.u32 %0, 1, 0, q;\n}"
                 : "=r"(any_unsafe) : "r"((uint32_t)unsafe), "r"(1 + wg) : "memory");
    float O[12];
    float S[32];
    if (!__any_sync(~0u, any_unsafe)) {
      if (t == 2) { qc[0] = pack_bf16(-m0, 0.f); qc[1] = pack_bf16(-m1, 0.f); }
      for (int j = 0; j < 32; j++) {
        if (it == 0 && (j & 3) == 0) mbar_wait(sBar + 8 * (j >> 2), 0);
        const uint64_t dk = make_desc(sK + j * 8 * 384, 128, 384, 0);
        wgmma_fence();
        wgmma_rs_n64(S, qa[0], qa[1], qa[2], qa[3], dk, 0);
        wgmma_rs_n64(S, qc[0], qc[1], qc[2], qc[3], dk + (256 >> 4), 1);
        wgmma_commit();
        wgmma_wait<0>();
        uint32_t P[16];
#pragma unroll
        for (int i = 0; i < 16; i++) {
          const bool usepoly = ((i + 1) * POLY_NUM / 16) != (i * POLY_NUM / 16);
          float a, b;
          if (usepoly) { a = ex2_poly(S[2 * i], shl23); b = ex2_poly(S[2 * i + 1], shl23); }
          else { a = ex2_mufu(S[2 * i]); b = ex2_mufu(S[2 * i + 1]); }
          P[i] = pack_bf16(a, b);
        }
        wgmma_fence();
        const uint64_t dv = make_desc(sV + j * 8 * 384, 384, 128, 0);
#pragma unroll
        for (int ks = 0; ks < 4; ks++)
          wgmma_rs_n24_tb(O, P[4 * ks], P[4 * ks + 1], P[4 * ks + 2], P[4 * ks + 3], dv + ((ks * 768) >> 4), (j | ks) != 0);
        wgmma_commit();
      }
    } else {
      float mx0 = -INFINITY, mx1 = -INFINITY;
      for (int j = 0; j < 32; j++) {
        if (it == 0 && (j & 3) == 0) mbar_wait(sBar + 8 * (j >> 2), 0);
        const uint64_t dk = make_desc(sK + j * 8 * 384, 128, 384, 0);
        wgmma_fence();
        wgmma_rs_n64(S, qa[0], qa[1], qa[2], qa[3], dk, 0);
        wgmma_rs_n64(S, qc[0], qc[1], qc[2], qc[3], dk + (256 >> 4), 1);
        wgmma_commit();
        wgmma_wait<0>();
#pragma unroll
        for (int i = 0; i < 8; i++) {
          mx0 = fmaxf(mx0, fmaxf(S[4 * i], S[4 * i + 1]));
          mx1 = fmaxf(mx1, fmaxf(S[4 * i + 2], S[4 * i + 3]));
        }
      }
      mx0 = fmaxf(mx0, __shfl_xor_sync(~0u, mx0, 1)); mx0 = fmaxf(mx0, __shfl_xor_sync(~0u, mx0, 2));
      mx1 = fmaxf(mx1, __shfl_xor_sync(~0u, mx1, 1)); mx1 = fmaxf(mx1, __shfl_xor_sync(~0u, mx1, 2));
      for (int j = 0; j < 32; j++) {
        const uint64_t dk = make_desc(sK + j * 8 * 384, 128, 384, 0);
        wgmma_fence();
        wgmma_rs_n64(S, qa[0], qa[1], qa[2], qa[3], dk, 0);
        wgmma_rs_n64(S, qc[0], qc[1], qc[2], qc[3], dk + (256 >> 4), 1);
        wgmma_commit();
        wgmma_wait<0>();
        uint32_t P[16];
#pragma unroll
        for (int i = 0; i < 8; i++) {
          P[2 * i] = pack_bf16(ex2_mufu(S[4 * i] - mx0), ex2_mufu(S[4 * i + 1] - mx0));
          P[2 * i + 1] = pack_bf16(ex2_mufu(S[4 * i + 2] - mx1), ex2_mufu(S[4 * i + 3] - mx1));
        }
        wgmma_fence();
        const uint64_t dv = make_desc(sV + j * 8 * 384, 384, 128, 0);
#pragma unroll
        for (int ks = 0; ks < 4; ks++)
          wgmma_rs_n24_tb(O, P[4 * ks], P[4 * ks + 1], P[4 * ks + 2], P[4 * ks + 3], dv + ((ks * 768) >> 4), (j | ks) != 0);
        wgmma_commit();
      }
    }
    wgmma_wait<0>();
#pragma unroll
    for (int i = 0; i < 12; i++) asm volatile("" : "+f"(O[i]) :: "memory");
    const float l0 = __shfl_sync(~0u, O[8], (lane & ~3) | 2), l1 = __shfl_sync(~0u, O[10], (lane & ~3) | 2);
    const float r0 = 1.f / l0, r1 = 1.f / l1;
    uint32_t* o0 = (uint32_t*)(g_o + (size_t)(q0 + g) * DM + h * DH);
    uint32_t* o1 = (uint32_t*)(g_o + (size_t)(q0 + g + 8) * DM + h * DH);
    o0[t] = pack_bf16(O[0] * r0, O[1] * r0); o1[t] = pack_bf16(O[2] * r1, O[3] * r1);
    o0[t + 4] = pack_bf16(O[4] * r0, O[5] * r0); o1[t + 4] = pack_bf16(O[6] * r1, O[7] * r1);
    if (t < 2) { o0[t + 8] = pack_bf16(O[8] * r0, O[9] * r0); o1[t + 8] = pack_bf16(O[10] * r1, O[11] * r1); }
  }
  TS_END(2);
}

typedef CUresult (*EncodeFn)(CUtensorMap*, CUtensorMapDataType, cuuint32_t, void*, const cuuint64_t*, const cuuint64_t*, const cuuint32_t*,
                             const cuuint32_t*, CUtensorMapInterleave, CUtensorMapSwizzle, CUtensorMapL2promotion, CUtensorMapFloatOOBfill);
static EncodeFn get_encode() {
  static EncodeFn fn = nullptr;
  if (!fn) {
    void* p = nullptr; cudaDriverEntryPointQueryResult st;
    cudaGetDriverEntryPoint("cuTensorMapEncodeTiled", &p, cudaEnableDefault, &st);
    fn = (EncodeFn)p;
  }
  return fn;
}
static CUtensorMap make_map(const void* ptr, int rows, int cols, int box_rows) {
  CUtensorMap m;
  cuuint64_t dims[2] = {(cuuint64_t)cols, (cuuint64_t)rows};
  cuuint64_t strides[1] = {(cuuint64_t)cols * 2};
  cuuint32_t box[2] = {64, (cuuint32_t)box_rows};
  cuuint32_t es[2] = {1, 1};
  get_encode()(&m, CU_TENSOR_MAP_DATA_TYPE_BFLOAT16, 2, const_cast<void*>(ptr), dims, strides, box, es, CU_TENSOR_MAP_INTERLEAVE_NONE,
               CU_TENSOR_MAP_SWIZZLE_128B, CU_TENSOR_MAP_L2_PROMOTION_L2_128B, CU_TENSOR_MAP_FLOAT_OOB_FILL_NONE);
  return m;
}
template <typename... KArgs, typename... Args>
static void launch(void (*kern)(KArgs...), dim3 grid, dim3 block, size_t smem, bool pdl, dim3 cluster, Args... args) {
  cudaLaunchConfig_t cfg = {};
  cfg.gridDim = grid; cfg.blockDim = block; cfg.dynamicSmemBytes = smem; cfg.stream = cudaStreamPerThread;
  cudaLaunchAttribute at[2];
  int na = 0;
  if (pdl) { at[na].id = cudaLaunchAttributeProgrammaticStreamSerialization; at[na].val.programmaticStreamSerializationAllowed = 1; na++; }
  if (cluster.x * cluster.y > 1) { at[na].id = cudaLaunchAttributeClusterDimension; at[na].val.clusterDim.x = cluster.x; at[na].val.clusterDim.y = cluster.y; at[na].val.clusterDim.z = 1; na++; }
  cfg.attrs = at; cfg.numAttrs = na;
  cudaLaunchKernelEx(&cfg, kern, KArgs(args)...);
}

extern "C" void kernel_launch(void* const* d_in, const int* in_sizes, int n_in, void* d_out, int out_size) {
  const __nv_bfloat16* x = (const __nv_bfloat16*)d_in[0];
  const __nv_bfloat16* wqkv = (const __nv_bfloat16*)d_in[1];
  const __nv_bfloat16* wo = (const __nv_bfloat16*)d_in[2];
  const __nv_bfloat16* wgate = (const __nv_bfloat16*)d_in[4];
  const __nv_bfloat16* wup = (const __nv_bfloat16*)d_in[5];
  const __nv_bfloat16* wdown = (const __nv_bfloat16*)d_in[6];
  __nv_bfloat16* out = (__nv_bfloat16*)d_out;
  void *p_o, *p_h, *p_act;
  cudaGetSymbolAddress(&p_o, g_o); cudaGetSymbolAddress(&p_h, g_h); cudaGetSymbolAddress(&p_act, g_act);

#define A_CN 1
#define A_CM 2
#define C_CN 2
#define C_CM 2
#define D_CN 2
#define D_CM 2
#define E_CN 2
#define E_CM 2
  auto kA = gemm_kernel<256, 128, 1, DM, 4, EPI_QKV, 1, A_CN, A_CM>;
  auto kC = gemm_kernel<128, 64, 1, DM, 4, EPI_WO, 2, C_CN, C_CM>;
  auto kD = gemm_kernel<128, 192, 2, DM, 3, EPI_GLU, 1, D_CN, D_CM>;
  auto kE = gemm_kernel<128, 64, 1, DFF, 4, EPI_DOWN, 2, E_CN, E_CM>;
  constexpr int smA = GemmCfg<256, 128, 1, 4>::SMEM, smC = GemmCfg<128, 64, 1, 4>::SMEM, smD = GemmCfg<128, 192, 2, 3>::SMEM;
  cudaFuncSetAttribute(kA, cudaFuncAttributeMaxDynamicSharedMemorySize, smA);
  cudaFuncSetAttribute(kC, cudaFuncAttributeMaxDynamicSharedMemorySize, smC);
  cudaFuncSetAttribute(kD, cudaFuncAttributeMaxDynamicSharedMemorySize, smD);
  cudaFuncSetAttribute(kE, cudaFuncAttributeMaxDynamicSharedMemorySize, smC);
  cudaFuncSetAttribute(attn_kernel, cudaFuncAttributeMaxDynamicSharedMemorySize, ATT_SMEM);

  const CUtensorMap tm_x = make_map(x, S_LEN, DM, 256 / A_CN), tm_wqkv = make_map(wqkv, DM, 3 * DM, 2 % A_CM ? 64 / A_CM : 64);
  const CUtensorMap tm_o = make_map(p_o, S_LEN, DM, 128 / C_CN), tm_wo = make_map(wo, DM, DM, 64 / C_CM);
  const CUtensorMap tm_h = make_map(p_h, S_LEN, DM, 128 / D_CN), tm_wg = make_map(wgate, DM, DFF, 6 % D_CM ? 64 / D_CM : 64), tm_wu = make_map(wup, DM, DFF, 6 % D_CM ? 64 / D_CM : 64);
  const CUtensorMap tm_act = make_map(p_act, S_LEN, DFF, 128 / E_CN), tm_wd = make_map(wdown, DFF, DM, 64 / E_CM);

  launch(pre_kernel, dim3(PRE_COL_BLOCKS + PRE_ROW_BLOCKS), dim3(256), 0, false, dim3(1, 1), x, wqkv, wgate, wup);
  launch(kA, dim3(15, 8), dim3(288), smA, true, dim3(A_CN, A_CM), tm_x, tm_wqkv, tm_wqkv, (const __nv_bfloat16*)nullptr, (__nv_bfloat16*)nullptr);
  launch(attn_kernel, dim3(128), dim3(512), ATT_SMEM, true, dim3(1, 1), 0x800000);
  launch(kC, dim3(10, 16), dim3(288), smC, true, dim3(C_CN, C_CM), tm_o, tm_wo, tm_wo, x, (__nv_bfloat16*)p_h);
  launch(kD, dim3(8, 16), dim3(384), smD, true, dim3(D_CN, D_CM), tm_h, tm_wg, tm_wu, (const __nv_bfloat16*)nullptr, (__nv_bfloat16*)p_act);
  launch(kE, dim3(10, 16), dim3(288), smC, true, dim3(E_CN, E_CM), tm_act, tm_wd, tm_wd, (const __nv_bfloat16*)p_h, out);
}
```

```cpp
#include <cuda_runtime.h>
#include <cuda_bf16.h>
#include <cuda.h>
#include <stdint.h>

constexpr int S_LEN = 2048, DM = 640, NH = 32, DH = 20, DFF = 1536;

__device__ __align__(1024) __nv_bfloat16 g_q[S_LEN * DM];
__device__ __align__(1024) __nv_bfloat16 g_k[NH * S_LEN * 24];
__device__ __align__(1024) __nv_bfloat16 g_v[NH * S_LEN * 24];
__device__ __align__(1024) __nv_bfloat16 g_o[S_LEN * DM];
__device__ __align__(1024) __nv_bfloat16 g_h[S_LEN * DM];
__device__ __align__(1024) __nv_bfloat16 g_act[S_LEN * DFF];
__device__ float g_kn[8 * NH * 2];
__device__ float2 g_stat1[S_LEN];
__device__ float g_cs_qkv[3 * DM];
__device__ float g_cs_g[DFF];
__device__ float g_cs_u[DFF];
__device__ float2 g_part2[S_LEN * 10];

#define TS_BEGIN(k)
#define TS_END(k)
#define TS_MID(k, i)
__device__ __forceinline__ uint32_t smem_u32(const void* p) { return (uint32_t)__cvta_generic_to_shared(p); }
__device__ __forceinline__ void mbar_init(uint32_t bar, uint32_t cnt) { asm volatile("mbarrier.init.shared::cta.b64 [%0], %1;" :: "r"(bar), "r"(cnt)); }
__device__ __forceinline__ void mbar_expect_tx(uint32_t bar, uint32_t bytes) { asm volatile("mbarrier.arrive.expect_tx.shared::cta.b64 _, [%0], %1;" :: "r"(bar), "r"(bytes) : "memory"); }
__device__ __forceinline__ void mbar_arrive(uint32_t bar) { asm volatile("mbarrier.arrive.shared::cta.b64 _, [%0];" :: "r"(bar) : "memory"); }
__device__ __forceinline__ void mbar_wait(uint32_t bar, uint32_t parity) {
  uint32_t done;
  uint32_t spins = 0;
  do {
    asm volatile("{\n.reg .pred P1;\nmbarrier.try_wait.parity.shared::cta.b64 P1, [%1], %2;\nselp.u32 %0, 1, 0, P1;\n}" : "=r"(done) : "r"(bar), "r"(parity) : "memory");
  } while (!done && ++spins < (1u << 24));
}
__device__ __forceinline__ void bulk_g2s(uint32_t dst, const void* src, uint32_t bytes, uint32_t bar) {
  asm volatile("cp.async.bulk.shared::cluster.global.mbarrier::complete_tx::bytes [%0], [%1], %2, [%3];" :: "r"(dst), "l"(src), "r"(bytes), "r"(bar) : "memory");
}
__device__ __forceinline__ void tma_2d(uint32_t dst, const CUtensorMap* tm, int c0, int c1, uint32_t bar) {
  asm volatile("cp.async.bulk.tensor.2d.shared::cluster.global.mbarrier::complete_tx::bytes [%0], [%1, {%3, %4}], [%2];"
               :: "r"(dst), "l"(tm), "r"(bar), "r"(c0), "r"(c1) : "memory");
}
__device__ __forceinline__ void tma_2d_mc(uint32_t dst, const CUtensorMap* tm, int c0, int c1, uint32_t bar, uint16_t mask) {
  asm volatile("cp.async.bulk.tensor.2d.shared::cluster.global.mbarrier::complete_tx::bytes.multicast::cluster [%0], [%1, {%3, %4}], [%2], %5;"
               :: "r"(dst), "l"(tm), "r"(bar), "r"(c0), "r"(c1), "h"(mask) : "memory");
}
__device__ __forceinline__ void mbar_arrive_remote(uint32_t bar, uint32_t rank) {
  asm volatile("{\n.reg .b32 ra;\nmapa.shared::cluster.u32 ra, %0, %1;\nmbarrier.arrive.release.cluster.shared::cluster.b64 _, [ra];\n}" :: "r"(bar), "r"(rank) : "memory");
}
__device__ __forceinline__ void cluster_arrive() { asm volatile("barrier.cluster.arrive.release.aligned;" ::: "memory"); }
__device__ __forceinline__ void cluster_wait() { asm volatile("barrier.cluster.wait.acquire.aligned;" ::: "memory"); }
__device__ __forceinline__ void wgmma_fence() { asm volatile("wgmma.fence.sync.aligned;" ::: "memory"); }
__device__ __forceinline__ void wgmma_commit() { asm volatile("wgmma.commit_group.sync.aligned;" ::: "memory"); }
template <int N> __device__ __forceinline__ void wgmma_wait() { asm volatile("wgmma.wait_group.sync.aligned %0;" :: "n"(N) : "memory"); }
__device__ __forceinline__ void pdl_wait() { asm volatile("griddepcontrol.wait;" ::: "memory"); }
__device__ __forceinline__ void pdl_launch() { asm volatile("griddepcontrol.launch_dependents;" ::: "memory"); }
__device__ __forceinline__ void named_bar(int id, int n) { asm volatile("bar.sync %0, %1;" :: "r"(id), "r"(n) : "memory"); }
__device__ __forceinline__ uint64_t make_desc(uint32_t addr, uint32_t lbo, uint32_t sbo, uint32_t swz) {
  return (uint64_t)((addr & 0x3FFFF) >> 4) | ((uint64_t)(lbo >> 4) << 16) | ((uint64_t)(sbo >> 4) << 32) | ((uint64_t)swz << 62);
}
__device__ __forceinline__ uint32_t pack_bf16(float lo, float hi) { uint32_t r; asm("cvt.rn.bf16x2.f32 %0, %1, %2;" : "=r"(r) : "f"(hi), "f"(lo)); return r; }
__device__ __forceinline__ float bf_lo(uint32_t u) { return __uint_as_float(u << 16); }
__device__ __forceinline__ float bf_hi(uint32_t u) { return __uint_as_float(u & 0xffff0000u); }
__device__ __forceinline__ float bf_round(float x) { return __bfloat162float(__float2bfloat16_rn(x)); }
__device__ __forceinline__ float ex2_mufu(float x) { float y; asm("ex2.approx.ftz.f32 %0, %1;" : "=f"(y) : "f"(x)); return y; }

__device__ __forceinline__ void wgmma_ss_n64(float (&d)[32], uint64_t da, uint64_t db, int scale_d) {
  asm volatile("{\n.reg .pred p;\nsetp.ne.b32 p, %34, 0;\n"
    "wgmma.mma_async.sync.aligned.m64n64k16.f32.bf16.bf16 {%0,%1,%2,%3,%4,%5,%6,%7,%8,%9,%10,%11,%12,%13,%14,%15,%16,%17,%18,%19,%20,%21,%22,%23,%24,%25,%26,%27,%28,%29,%30,%31}, %32, %33, p, 1, 1, 0, 1;\n}\n"
    : "+f"(d[0]),"+f"(d[1]),"+f"(d[2]),"+f"(d[3]),"+f"(d[4]),"+f"(d[5]),"+f"(d[6]),"+f"(d[7]),"+f"(d[8]),"+f"(d[9]),"+f"(d[10]),"+f"(d[11]),"+f"(d[12]),"+f"(d[13]),"+f"(d[14]),"+f"(d[15]),"+f"(d[16]),"+f"(d[17]),"+f"(d[18]),"+f"(d[19]),"+f"(d[20]),"+f"(d[21]),"+f"(d[22]),"+f"(d[23]),"+f"(d[24]),"+f"(d[25]),"+f"(d[26]),"+f"(d[27]),"+f"(d[28]),"+f"(d[29]),"+f"(d[30]),"+f"(d[31])
    : "l"(da), "l"(db), "r"(scale_d));
}
__device__ __forceinline__ void wgmma_ss_n128(float (&d)[64], uint64_t da, uint64_t db, int scale_d) {
  asm volatile("{\n.reg .pred p;\nsetp.ne.b32 p, %66, 0;\n"
    "wgmma.mma_async.sync.aligned.m64n128k16.f32.bf16.bf16 {%0,%1,%2,%3,%4,%5,%6,%7,%8,%9,%10,%11,%12,%13,%14,%15,%16,%17,%18,%19,%20,%21,%22,%23,%24,%25,%26,%27,%28,%29,%30,%31,%32,%33,%34,%35,%36,%37,%38,%39,%40,%41,%42,%43,%44,%45,%46,%47,%48,%49,%50,%51,%52,%53,%54,%55,%56,%57,%58,%59,%60,%61,%62,%63}, %64, %65, p, 1, 1, 0, 1;\n}\n"
    : "+f"(d[0]),"+f"(d[1]),"+f"(d[2]),"+f"(d[3]),"+f"(d[4]),"+f"(d[5]),"+f"(d[6]),"+f"(d[7]),"+f"(d[8]),"+f"(d[9]),"+f"(d[10]),"+f"(d[11]),"+f"(d[12]),"+f"(d[13]),"+f"(d[14]),"+f"(d[15]),"+f"(d[16]),"+f"(d[17]),"+f"(d[18]),"+f"(d[19]),"+f"(d[20]),"+f"(d[21]),"+f"(d[22]),"+f"(d[23]),"+f"(d[24]),"+f"(d[25]),"+f"(d[26]),"+f"(d[27]),"+f"(d[28]),"+f"(d[29]),"+f"(d[30]),"+f"(d[31]),"+f"(d[32]),"+f"(d[33]),"+f"(d[34]),"+f"(d[35]),"+f"(d[36]),"+f"(d[37]),"+f"(d[38]),"+f"(d[39]),"+f"(d[40]),"+f"(d[41]),"+f"(d[42]),"+f"(d[43]),"+f"(d[44]),"+f"(d[45]),"+f"(d[46]),"+f"(d[47]),"+f"(d[48]),"+f"(d[49]),"+f"(d[50]),"+f"(d[51]),"+f"(d[52]),"+f"(d[53]),"+f"(d[54]),"+f"(d[55]),"+f"(d[56]),"+f"(d[57]),"+f"(d[58]),"+f"(d[59]),"+f"(d[60]),"+f"(d[61]),"+f"(d[62]),"+f"(d[63])
    : "l"(da), "l"(db), "r"(scale_d));
}
__device__ __forceinline__ void wgmma_ss_n160(float (&d)[80], uint64_t da, uint64_t db, int scale_d) {
  asm volatile("{\n.reg .pred p;\nsetp.ne.b32 p, %82, 0;\n"
    "wgmma.mma_async.sync.aligned.m64n160k16.f32.bf16.bf16 {%0,%1,%2,%3,%4,%5,%6,%7,%8,%9,%10,%11,%12,%13,%14,%15,%16,%17,%18,%19,%20,%21,%22,%23,%24,%25,%26,%27,%28,%29,%30,%31,%32,%33,%34,%35,%36,%37,%38,%39,%40,%41,%42,%43,%44,%45,%46,%47,%48,%49,%50,%51,%52,%53,%54,%55,%56,%57,%58,%59,%60,%61,%62,%63,%64,%65,%66,%67,%68,%69,%70,%71,%72,%73,%74,%75,%76,%77,%78,%79}, %80, %81, p, 1, 1, 0, 1;\n}\n"
    : "+f"(d[0]),"+f"(d[1]),"+f"(d[2]),"+f"(d[3]),"+f"(d[4]),"+f"(d[5]),"+f"(d[6]),"+f"(d[7]),"+f"(d[8]),"+f"(d[9]),"+f"(d[10]),"+f"(d[11]),"+f"(d[12]),"+f"(d[13]),"+f"(d[14]),"+f"(d[15]),"+f"(d[16]),"+f"(d[17]),"+f"(d[18]),"+f"(d[19]),"+f"(d[20]),"+f"(d[21]),"+f"(d[22]),"+f"(d[23]),"+f"(d[24]),"+f"(d[25]),"+f"(d[26]),"+f"(d[27]),"+f"(d[28]),"+f"(d[29]),"+f"(d[30]),"+f"(d[31]),"+f"(d[32]),"+f"(d[33]),"+f"(d[34]),"+f"(d[35]),"+f"(d[36]),"+f"(d[37]),"+f"(d[38]),"+f"(d[39]),"+f"(d[40]),"+f"(d[41]),"+f"(d[42]),"+f"(d[43]),"+f"(d[44]),"+f"(d[45]),"+f"(d[46]),"+f"(d[47]),"+f"(d[48]),"+f"(d[49]),"+f"(d[50]),"+f"(d[51]),"+f"(d[52]),"+f"(d[53]),"+f"(d[54]),"+f"(d[55]),"+f"(d[56]),"+f"(d[57]),"+f"(d[58]),"+f"(d[59]),"+f"(d[60]),"+f"(d[61]),"+f"(d[62]),"+f"(d[63]),"+f"(d[64]),"+f"(d[65]),"+f"(d[66]),"+f"(d[67]),"+f"(d[68]),"+f"(d[69]),"+f"(d[70]),"+f"(d[71]),"+f"(d[72]),"+f"(d[73]),"+f"(d[74]),"+f"(d[75]),"+f"(d[76]),"+f"(d[77]),"+f"(d[78]),"+f"(d[79])
    : "l"(da), "l"(db), "r"(scale_d));
}
__device__ __forceinline__ void wgmma_ss_n192(float (&d)[96], uint64_t da, uint64_t db, int scale_d) {
  asm volatile("{\n.reg .pred p;\nsetp.ne.b32 p, %98, 0;\n"
    "wgmma.mma_async.sync.aligned.m64n192k16.f32.bf16.bf16 {%0,%1,%2,%3,%4,%5,%6,%7,%8,%9,%10,%11,%12,%13,%14,%15,%16,%17,%18,%19,%20,%21,%22,%23,%24,%25,%26,%27,%28,%29,%30,%31,%32,%33,%34,%35,%36,%37,%38,%39,%40,%41,%42,%43,%44,%45,%46,%47,%48,%49,%50,%51,%52,%53,%54,%55,%56,%57,%58,%59,%60,%61,%62,%63,%64,%65,%66,%67,%68,%69,%70,%71,%72,%73,%74,%75,%76,%77,%78,%79,%80,%81,%82,%83,%84,%85,%86,%87,%88,%89,%90,%91,%92,%93,%94,%95}, %96, %97, p, 1, 1, 0, 1;\n}\n"
    : "+f"(d[0]),"+f"(d[1]),"+f"(d[2]),"+f"(d[3]),"+f"(d[4]),"+f"(d[5]),"+f"(d[6]),"+f"(d[7]),"+f"(d[8]),"+f"(d[9]),"+f"(d[10]),"+f"(d[11]),"+f"(d[12]),"+f"(d[13]),"+f"(d[14]),"+f"(d[15]),"+f"(d[16]),"+f"(d[17]),"+f"(d[18]),"+f"(d[19]),"+f"(d[20]),"+f"(d[21]),"+f"(d[22]),"+f"(d[23]),"+f"(d[24]),"+f"(d[25]),"+f"(d[26]),"+f"(d[27]),"+f"(d[28]),"+f"(d[29]),"+f"(d[30]),"+f"(d[31]),"+f"(d[32]),"+f"(d[33]),"+f"(d[34]),"+f"(d[35]),"+f"(d[36]),"+f"(d[37]),"+f"(d[38]),"+f"(d[39]),"+f"(d[40]),"+f"(d[41]),"+f"(d[42]),"+f"(d[43]),"+f"(d[44]),"+f"(d[45]),"+f"(d[46]),"+f"(d[47]),"+f"(d[48]),"+f"(d[49]),"+f"(d[50]),"+f"(d[51]),"+f"(d[52]),"+f"(d[53]),"+f"(d[54]),"+f"(d[55]),"+f"(d[56]),"+f"(d[57]),"+f"(d[58]),"+f"(d[59]),"+f"(d[60]),"+f"(d[61]),"+f"(d[62]),"+f"(d[63]),"+f"(d[64]),"+f"(d[65]),"+f"(d[66]),"+f"(d[67]),"+f"(d[68]),"+f"(d[69]),"+f"(d[70]),"+f"(d[71]),"+f"(d[72]),"+f"(d[73]),"+f"(d[74]),"+f"(d[75]),"+f"(d[76]),"+f"(d[77]),"+f"(d[78]),"+f"(d[79]),"+f"(d[80]),"+f"(d[81]),"+f"(d[82]),"+f"(d[83]),"+f"(d[84]),"+f"(d[85]),"+f"(d[86]),"+f"(d[87]),"+f"(d[88]),"+f"(d[89]),"+f"(d[90]),"+f"(d[91]),"+f"(d[92]),"+f"(d[93]),"+f"(d[94]),"+f"(d[95])
    : "l"(da), "l"(db), "r"(scale_d));
}
__device__ __forceinline__ void wgmma_rs_n64(float (&d)[32], uint32_t a0, uint32_t a1, uint32_t a2, uint32_t a3, uint64_t db, int scale_d) {
  asm volatile("{\n.reg .pred p;\nsetp.ne.b32 p, %37, 0;\n"
    "wgmma.mma_async.sync.aligned.m64n64k16.f32.bf16.bf16 {%0,%1,%2,%3,%4,%5,%6,%7,%8,%9,%10,%11,%12,%13,%14,%15,%16,%17,%18,%19,%20,%21,%22,%23,%24,%25,%26,%27,%28,%29,%30,%31}, {%32,%33,%34,%35}, %36, p, 1, 1, 0;\n}\n"
    : "+f"(d[0]),"+f"(d[1]),"+f"(d[2]),"+f"(d[3]),"+f"(d[4]),"+f"(d[5]),"+f"(d[6]),"+f"(d[7]),"+f"(d[8]),"+f"(d[9]),"+f"(d[10]),"+f"(d[11]),"+f"(d[12]),"+f"(d[13]),"+f"(d[14]),"+f"(d[15]),"+f"(d[16]),"+f"(d[17]),"+f"(d[18]),"+f"(d[19]),"+f"(d[20]),"+f"(d[21]),"+f"(d[22]),"+f"(d[23]),"+f"(d[24]),"+f"(d[25]),"+f"(d[26]),"+f"(d[27]),"+f"(d[28]),"+f"(d[29]),"+f"(d[30]),"+f"(d[31])
    : "r"(a0), "r"(a1), "r"(a2), "r"(a3), "l"(db), "r"(scale_d));
}
__device__ __forceinline__ void wgmma_rs_n24_tb(float (&d)[12], uint32_t a0, uint32_t a1, uint32_t a2, uint32_t a3, uint64_t db, int scale_d) {
  asm volatile("{\n.reg .pred p;\nsetp.ne.b32 p, %17, 0;\n"
    "wgmma.mma_async.sync.aligned.m64n24k16.f32.bf16.bf16 {%0,%1,%2,%3,%4,%5,%6,%7,%8,%9,%10,%11}, {%12,%13,%14,%15}, %16, p, 1, 1, 1;\n}\n"
    : "+f"(d[0]),"+f"(d[1]),"+f"(d[2]),"+f"(d[3]),"+f"(d[4]),"+f"(d[5]),"+f"(d[6]),"+f"(d[7]),"+f"(d[8]),"+f"(d[9]),"+f"(d[10]),"+f"(d[11])
    : "r"(a0), "r"(a1), "r"(a2), "r"(a3), "l"(db), "r"(scale_d));
}

constexpr int PRE_ROW_BLOCKS = 64;
constexpr int PRE_COL_BLOCKS = (3 * DM + 2 * DFF) / 64;
__device__ __forceinline__ float2 ln_finish(float mean, float var) {
  float mb = bf_round(mean);
  float s = bf_round(sqrtf(bf_round(bf_round(var) + 1e-5f)));
  return make_float2(mb, 1.0f / s);
}
__global__ void __launch_bounds__(256) pre_kernel(const __nv_bfloat16* __restrict__ x, const __nv_bfloat16* __restrict__ wqkv,
                                                  const __nv_bfloat16* __restrict__ wg, const __nv_bfloat16* __restrict__ wu) {
  TS_BEGIN(0);
  pdl_launch();
  const int tid = threadIdx.x, lane = tid & 31, warp = tid >> 5;
  if (blockIdx.x < PRE_COL_BLOCKS) {
    __shared__ float red[32][65];
    int c0 = blockIdx.x * 64;
    const __nv_bfloat16* w; float* dst; int ld;
    if (c0 < 3 * DM) { w = wqkv; dst = g_cs_qkv; ld = 3 * DM; }
    else if (c0 < 3 * DM + DFF) { w = wg; dst = g_cs_g; ld = DFF; c0 -= 3 * DM; }
    else { w = wu; dst = g_cs_u; ld = DFF; c0 -= 3 * DM + DFF; }
    const int cg = tid & 7, r0 = tid >> 3;
    float acc[8];
#pragma unroll
    for (int i = 0; i < 8; i++) acc[i] = 0.f;
#pragma unroll 5
    for (int r = r0; r < DM; r += 32) {
      uint4 v = __ldg((const uint4*)(w + (size_t)r * ld + c0 + cg * 8));
      acc[0] += bf_lo(v.x); acc[1] += bf_hi(v.x); acc[2] += bf_lo(v.y); acc[3] += bf_hi(v.y);
      acc[4] += bf_lo(v.z); acc[5] += bf_hi(v.z); acc[6] += bf_lo(v.w); acc[7] += bf_hi(v.w);
    }
#pragma unroll
    for (int i = 0; i < 8; i++) red[r0][cg * 8 + i] = acc[i];
    __syncthreads();
    if (tid < 64) {
      float s = 0.f;
#pragma unroll
      for (int r = 0; r < 32; r++) s += red[r][tid];
      dst[c0 + tid] = s;
    }
  } else {
    const int rb = blockIdx.x - PRE_COL_BLOCKS;
#pragma unroll
    for (int i = 0; i < 4; i++) {
      const int row = rb * 32 + warp * 4 + i;
      const uint4* p = (const uint4*)(x + (size_t)row * DM);
      uint4 v0 = __ldg(p + lane), v1 = __ldg(p + 32 + lane), v2 = make_uint4(0, 0, 0, 0);
      if (lane < 16) v2 = __ldg(p + 64 + lane);
      float f[24];
      uint32_t u[12] = {v0.x, v0.y, v0.z, v0.w, v1.x, v1.y, v1.z, v1.w, v2.x, v2.y, v2.z, v2.w};
#pragma unroll
      for (int j = 0; j < 12; j++) { f[2 * j] = bf_lo(u[j]); f[2 * j + 1] = bf_hi(u[j]); }
      float s = 0.f;
#pragma unroll
      for (int j = 0; j < 24; j++) s += f[j];
#pragma unroll
      for (int o = 16; o; o >>= 1) s += __shfl_xor_sync(~0u, s, o);
      const float mean = s * (1.0f / DM);
      float q = 0.f;
#pragma unroll
      for (int j = 0; j < 16; j++) { float d = f[j] - mean; q += d * d; }
      if (lane < 16) {
#pragma unroll
        for (int j = 16; j < 24; j++) { float d = f[j] - mean; q += d * d; }
      }
#pragma unroll
      for (int o = 16; o; o >>= 1) q += __shfl_xor_sync(~0u, q, o);
      if (lane == 0) g_stat1[row] = ln_finish(mean, q * (1.0f / DM));
    }
  }
  TS_END(0);
}

enum { EPI_QKV = 0, EPI_WO = 1, EPI_GLU = 2, EPI_DOWN = 3 };
template <int N> struct WG;
template <> struct WG<64>  { static __device__ __forceinline__ void mma(float (&d)[32], uint64_t a, uint64_t b, int s) { wgmma_ss_n64(d, a, b, s); } };
template <> struct WG<128> { static __device__ __forceinline__ void mma(float (&d)[64], uint64_t a, uint64_t b, int s) { wgmma_ss_n128(d, a, b, s); } };
template <> struct WG<192> { static __device__ __forceinline__ void mma(float (&d)[96], uint64_t a, uint64_t b, int s) { wgmma_ss_n192(d, a, b, s); } };

template <int BM, int BN, int NB, int STAGES> struct GemmCfg {
  static constexpr int A_BYTES = BM * 128;
  static constexpr int B_BYTES = NB * (BN / 64) * 8192;
  static constexpr int STAGE_BYTES = A_BYTES + B_BYTES;
  static constexpr int SMEM = STAGES * STAGE_BYTES + 1024   + 256   + 4096  ;
};

constexpr float QSCALE = 0.22360679774997896f * 1.4426950408889634f;

template <int BM, int BN, int NB, int KDIM, int STAGES, int EPI, int MINB, int CN, int CM>
__global__ void __launch_bounds__(EPI == EPI_GLU ? 384 : 288, MINB) gemm_kernel(const __grid_constant__ CUtensorMap tmA, const __grid_constant__ CUtensorMap tmB0,
                                                         const __grid_constant__ CUtensorMap tmB1,
                                                         const __nv_bfloat16* __restrict__ resid, __nv_bfloat16* __restrict__ out) {
  using Cfg = GemmCfg<BM, BN, NB, STAGES>;
  constexpr int MB = BM / 128;
  constexpr int KT = KDIM / 64;
  extern __shared__ uint8_t smem_raw[];
  const uint32_t sbase = (smem_u32(smem_raw) + 1023u) & ~1023u;
  uint8_t* sptr = smem_raw + (sbase - smem_u32(smem_raw));
  const uint32_t sbar = sbase + STAGES * Cfg::STAGE_BYTES;
  const int tid = threadIdx.x, warp = tid >> 5, lane = tid & 31;
  const int n0 = blockIdx.x * BN, m0 = blockIdx.y * BM;
  TS_BEGIN(EPI == EPI_QKV ? 1 : EPI + 2);
  constexpr int NCL = CN + CM - 1;
  const int cx = blockIdx.x % CN, cy = blockIdx.y % CM;
  if (tid == 0) {
    for (int i = 0; i < STAGES; i++) { mbar_init(sbar + 8 * i, 1); mbar_init(sbar + 8 * (STAGES + i), 2 * NCL); }
    asm volatile("fence.mbarrier_init.release.cluster;" ::: "memory");
  }
  __syncthreads();
  if constexpr (CN * CM > 1) { cluster_arrive(); cluster_wait(); }
  pdl_launch();
  if (warp >= 8) {
    if constexpr (EPI == EPI_GLU) asm volatile("setmaxnreg.dec.sync.aligned.u32 40;");
    if (warp == 8 && lane == 0) {
      uint16_t maskA = 0, maskB = 0;
#pragma unroll
      for (int i = 0; i < CN; i++) maskA |= (uint16_t)(1u << (cy * CN + i));
#pragma unroll
      for (int j = 0; j < CM; j++) maskB |= (uint16_t)(1u << (j * CN + cx));
      auto load_a = [&](int kt, int s) {
        const uint32_t dst = sbase + s * Cfg::STAGE_BYTES + cx * (BM / CN) * 128;
        if constexpr (CN > 1) tma_2d_mc(dst, &tmA, kt * 64, m0 + cx * (BM / CN), sbar + 8 * s, maskA);
        else tma_2d(dst, &tmA, kt * 64, m0, sbar + 8 * s);
      };
      auto load_b = [&](int kt, int s) {
        const uint32_t sb = sbase + s * Cfg::STAGE_BYTES + Cfg::A_BYTES;
        constexpr int NBOX = NB * (BN / 64);
        if constexpr (CM > 1 && NBOX % CM != 0) {
#pragma unroll
          for (int j = 0; j < NBOX; j++)
            tma_2d_mc(sb + j * 8192 + cy * (64 / CM) * 128, (NB == 2 && j >= BN / 64) ? &tmB1 : &tmB0, n0 + (j % (BN / 64)) * 64, kt * 64 + cy * (64 / CM), sbar + 8 * s, maskB);
        } else {
#pragma unroll
          for (int j = 0; j < NBOX; j++) {
            const CUtensorMap* tm = (NB == 2 && j >= BN / 64) ? &tmB1 : &tmB0;
            if constexpr (CM > 1) { if (j % CM == cy) tma_2d_mc(sb + j * 8192, tm, n0 + (j % (BN / 64)) * 64, kt * 64, sbar + 8 * s, maskB); }
            else tma_2d(sb + j * 8192, tm, n0 + (j % (BN / 64)) * 64, kt * 64, sbar + 8 * s);
          }
        }
      };
      for (int s = 0; s < STAGES; s++) { mbar_expect_tx(sbar + 8 * s, Cfg::STAGE_BYTES); load_b(s, s); }
      if (EPI != EPI_QKV) pdl_wait();
      for (int s = 0; s < STAGES; s++) load_a(s, s);
      for (int kt = STAGES; kt < KT; kt++) {
        const int s = kt % STAGES;
        mbar_wait(sbar + 8 * (STAGES + s), ((kt / STAGES) - 1) & 1);
        mbar_expect_tx(sbar + 8 * s, Cfg::STAGE_BYTES);
        load_a(kt, s);
        load_b(kt, s);
      }
    }
    if constexpr (EPI == EPI_GLU) {
      if (warp > 8) {
        float2* s_st = (float2*)(sptr + STAGES * Cfg::STAGE_BYTES + 256);
        float* s_cs = (float*)(sptr + STAGES * Cfg::STAGE_BYTES + 256 + 1024);
        pdl_wait();
        for (int r = tid - 288; r < BM; r += 96) {
          const float2* pp = &g_part2[(m0 + r) * 8];
          float s = 0.f;
#pragma unroll
          for (int i = 0; i < 8; i++) s += pp[i].x;
          const float mean = s * (1.0f / DM);
          float q = 0.f;
#pragma unroll
          for (int i = 0; i < 8; i++) { const float2 p = pp[i]; const float d = p.x * (1.0f / 80.f) - mean; q += p.y + 80.f * d * d; }
          s_st[r] = ln_finish(mean, q * (1.0f / DM));
        }
        for (int c = tid - 288; c < BN; c += 96) { s_cs[c] = g_cs_g[n0 + c]; s_cs[BN + c] = g_cs_u[n0 + c]; }
        __threadfence_block();
        asm volatile("bar.arrive 2, 352;" ::: "memory");
      }
    }
    if constexpr (CN * CM > 1) { __syncwarp(); cluster_arrive(); cluster_wait(); }
    return;
  }
  if constexpr (EPI == EPI_GLU) asm volatile("setmaxnreg.inc.sync.aligned.u32 232;");
  const int wg = warp >> 2, g = lane >> 2, t = lane & 3;
  float acc[MB][NB][BN / 2];
#pragma unroll
  for (int mb = 0; mb < MB; mb++)
#pragma unroll
    for (int nb = 0; nb < NB; nb++)
#pragma unroll
      for (int i = 0; i < BN / 2; i++) acc[mb][nb][i] = 0.f;
  for (int kt = 0; kt < KT; kt++) {
    const int s = kt % STAGES;
    mbar_wait(sbar + 8 * s, (kt / STAGES) & 1);
    if (kt == 0) TS_MID(EPI == EPI_QKV ? 1 : EPI + 2, 0);
    const uint32_t sa = sbase + s * Cfg::STAGE_BYTES + wg * (MB * 64 * 128);
    const uint32_t sb = sbase + s * Cfg::STAGE_BYTES + Cfg::A_BYTES;
    wgmma_fence();
#pragma unroll
    for (int ks = 0; ks < 4; ks++) {
#pragma unroll
      for (int mb = 0; mb < MB; mb++) {
        const uint64_t da = make_desc(sa + mb * 8192 + ks * 32, 16, 1024, 1);
#pragma unroll
        for (int nb = 0; nb < NB; nb++) {
          const uint64_t db = make_desc(sb + nb * (BN / 64) * 8192 + ks * 2048, 8192, 1024, 1);
          WG<BN>::mma(acc[mb][nb], da, db, 1);
        }
      }
    }
    wgmma_commit();
    wgmma_wait<1>();
    if (kt > 0 && kt - 1 + STAGES < KT && (tid & 127) < NCL) {
      const uint32_t eb = sbar + 8 * (STAGES + (kt - 1) % STAGES);
      if constexpr (CN * CM > 1) {
        const int i = tid & 127;
        const uint32_t rank = i < CN ? cy * CN + i : ((i - CN + (i - CN >= cy ? 1 : 0)) * CN + cx);
        mbar_arrive_remote(eb, rank);
      } else mbar_arrive(eb);
    }
  }
  wgmma_wait<0>();
#pragma unroll
  for (int mb = 0; mb < MB; mb++)
#pragma unroll
    for (int nb = 0; nb < NB; nb++)
#pragma unroll
      for (int i = 0; i < BN / 2; i++) asm volatile("" : "+f"(acc[mb][nb][i]) :: "memory");
  if constexpr (CN * CM > 1) cluster_arrive();
  TS_MID(EPI == EPI_QKV ? 1 : EPI + 2, 1);
  pdl_wait();
  TS_MID(EPI == EPI_QKV ? 1 : EPI + 2, 2);
  named_bar(1, 256);
  constexpr int LDS = BN * 2 + 16;
  const int ctid = tid;

  if constexpr (EPI == EPI_QKV) {
    const int sec = n0 / DM;
#pragma unroll
    for (int mb = 0; mb < MB; mb++) {
      const int r0 = wg * (MB * 64) + mb * 64 + (warp & 3) * 16 + g;
      const float2 st0 = g_stat1[m0 + r0], st1 = g_stat1[m0 + r0 + 8];
      const float sc0 = sec == 0 ? st0.y * QSCALE : st0.y, sc1 = sec == 0 ? st1.y * QSCALE : st1.y;
#pragma unroll
      for (int j = 0; j < BN / 8; j++) {
        const float2 cs = *(const float2*)&g_cs_qkv[n0 + j * 8 + 2 * t];
        const float* a = &acc[mb][0][4 * j];
        *(uint32_t*)(sptr + r0 * LDS + j * 16 + t * 4) = pack_bf16((a[0] - st0.x * cs.x) * sc0, (a[1] - st0.x * cs.y) * sc0);
        *(uint32_t*)(sptr + (r0 + 8) * LDS + j * 16 + t * 4) = pack_bf16((a[2] - st1.x * cs.x) * sc1, (a[3] - st1.x * cs.y) * sc1);
      }
    }
    named_bar(1, 256);
    if (sec == 0) {
#pragma unroll
      for (int i = 0; i < BM * (BN / 8) / 256; i++) {
        const int idx = i * 256 + ctid, r = idx / (BN / 8), c = idx % (BN / 8);
        *(uint4*)(g_q + (size_t)(m0 + r) * DM + n0 + c * 8) = *(const uint4*)(sptr + r * LDS + c * 16);
      }
    } else {
      __nv_bfloat16* dst = sec == 1 ? g_k : g_v;
      const int cbase = n0 - sec * DM;
#pragma unroll 4
      for (int i = 0; i < BM * (BN / 4) / 256; i++) {
        const int idx = i * 256 + ctid;
        const int half = idx & 1, r8 = (idx >> 1) & 7, rest = idx >> 4;
        const int pq = rest % (BN / 8), rg = rest / (BN / 8);
        const int r = rg * 8 + r8, cq = pq * 2 + half;
        const int col = cbase + cq * 4, h = col / DH, qd = (col % DH) >> 2;
        const uint2 v = *(const uint2*)(sptr + r * LDS + cq * 8);
        const int j = m0 + r;
        uint8_t* p = (uint8_t*)dst + ((size_t)h * S_LEN * 24 + (j >> 3) * 192 + (qd >> 1) * 64 + (j & 7) * 8 + (qd & 1) * 4) * 2;
        if (qd == 4) *(uint4*)p = make_uint4(v.x, v.y, 0x00003f80u, 0u);
        else *(uint2*)p = v;
      }
      if (sec == 1) {
        __shared__ unsigned int s_kn[8];
        if (ctid < 8) s_kn[ctid] = 0u;
        named_bar(1, 256);
        const int hfirst = cbase / DH, hlast = (cbase + BN - 1) / DH;
        for (int hh = hfirst; hh <= hlast; hh++) {
          const int c_lo = max(hh * DH, cbase) - cbase, c_hi = min(hh * DH + DH, cbase + BN) - cbase;
          float mx = 0.f;
          for (int r = ctid; r < BM; r += 256) {
            float s = 0.f;
            for (int c = c_lo; c < c_hi; c += 4) {
              const uint2 v = *(const uint2*)(sptr + r * LDS + c * 2);
              s += bf_lo(v.x) * bf_lo(v.x) + bf_hi(v.x) * bf_hi(v.x) + bf_lo(v.y) * bf_lo(v.y) + bf_hi(v.y) * bf_hi(v.y);
            }
            mx = (s > mx || s != s) ? s : mx;
          }
          unsigned int mb_ = __float_as_uint(mx) & 0x7fffffffu;
          mb_ = __reduce_max_sync(~0u, mb_);
          if (lane == 0) atomicMax(&s_kn[hh - hfirst], mb_);
        }
        named_bar(1, 256);
        if (ctid <= hlast - hfirst) {
          const int hh = hfirst + ctid;
          const bool starts_here = hh * DH >= cbase, ends_here = hh * DH + DH <= cbase + BN;
          const float v = __uint_as_float(s_kn[ctid]);
          float* o = &g_kn[(blockIdx.y * NH + hh) * 2];
          if (starts_here) { o[0] = v; if (ends_here) o[1] = 0.f; }
          else o[1] = v;
        }
      }
    }
  } else if constexpr (EPI == EPI_WO || EPI == EPI_DOWN) {
    const int r0 = wg * 64 + (warp & 3) * 16 + g;
#pragma unroll
    for (int j = 0; j < BN / 8; j++) {
      const float* a = &acc[0][0][4 * j];
      *(uint32_t*)(sptr + r0 * LDS + j * 16 + t * 4) = pack_bf16(a[0], a[1]);
      *(uint32_t*)(sptr + (r0 + 8) * LDS + j * 16 + t * 4) = pack_bf16(a[2], a[3]);
    }
    named_bar(1, 256);
#pragma unroll
    for (int i = 0; i < BM * (BN / 8) / 256; i++) {
      const int idx = i * 256 + ctid, r = idx / (BN / 8), c = idx % (BN / 8);
      const uint4 a = *(const uint4*)(sptr + r * LDS + c * 16);
      const size_t go = (size_t)(m0 + r) * DM + n0 + c * 8;
      const uint4 b = *(const uint4*)(resid + go);
      uint4 o;
      o.x = pack_bf16(bf_lo(a.x) + bf_lo(b.x), bf_hi(a.x) + bf_hi(b.x));
      o.y = pack_bf16(bf_lo(a.y) + bf_lo(b.y), bf_hi(a.y) + bf_hi(b.y));
      o.z = pack_bf16(bf_lo(a.z) + bf_lo(b.z), bf_hi(a.z) + bf_hi(b.z));
      o.w = pack_bf16(bf_lo(a.w) + bf_lo(b.w), bf_hi(a.w) + bf_hi(b.w));
      *(uint4*)(out + go) = o;
      if constexpr (EPI == EPI_WO) {
        static_assert(BN == 64, "stats assume 8 lanes per row");
        const float f[8] = {bf_lo(o.x), bf_hi(o.x), bf_lo(o.y), bf_hi(o.y), bf_lo(o.z), bf_hi(o.z), bf_lo(o.w), bf_hi(o.w)};
        float s = 0.f;
#pragma unroll
        for (int k = 0; k < 8; k++) s += f[k];
        s += __shfl_xor_sync(~0u, s, 1); s += __shfl_xor_sync(~0u, s, 2); s += __shfl_xor_sync(~0u, s, 4);
        const float mu = s * (1.0f / 64.f);
        float q = 0.f;
#pragma unroll
        for (int k = 0; k < 8; k++) { const float d = f[k] - mu; q += d * d; }
        q += __shfl_xor_sync(~0u, q, 1); q += __shfl_xor_sync(~0u, q, 2); q += __shfl_xor_sync(~0u, q, 4);
        if (c == 0) g_part2[(m0 + r) * 10 + blockIdx.x] = make_float2(s, q);
      }
    }
  } else {
    const int r0 = wg * 64 + (warp & 3) * 16 + g;
    const float2* s_st = (const float2*)(sptr + STAGES * Cfg::STAGE_BYTES + 256);
    const float* s_cs = (const float*)(sptr + STAGES * Cfg::STAGE_BYTES + 256 + 1024);
    named_bar(2, 352);
    float2 st[2] = {s_st[r0], s_st[r0 + 8]};
#pragma unroll
    for (int j = 0; j < BN / 8; j++) {
      const float2 cg = *(const float2*)&s_cs[j * 8 + 2 * t], cu = *(const float2*)&s_cs[BN + j * 8 + 2 * t];
      const float* a = &acc[0][0][4 * j];
      const float* b = &acc[0][1][4 * j];
      float v[4];
#pragma unroll
      for (int e = 0; e < 4; e++) {
        const float2 s_ = st[e >> 1];
        const float gt = bf_round((a[e] - s_.x * ((e & 1) ? cg.y : cg.x)) * s_.y);
        const float up = bf_round((b[e] - s_.x * ((e & 1) ? cu.y : cu.x)) * s_.y);
        v[e] = (gt > 0.f ? gt : 0.f) * up;
      }
      *(uint32_t*)(sptr + r0 * LDS + j * 16 + t * 4) = pack_bf16(v[0], v[1]);
      *(uint32_t*)(sptr + (r0 + 8) * LDS + j * 16 + t * 4) = pack_bf16(v[2], v[3]);
    }
    named_bar(1, 256);
#pragma unroll
    for (int i = 0; i < BM * (BN / 8) / 256; i++) {
      const int idx = i * 256 + ctid, r = idx / (BN / 8), c = idx % (BN / 8);
      *(uint4*)(out + (size_t)(m0 + r) * DFF + n0 + c * 8) = *(const uint4*)(sptr + r * LDS + c * 16);
    }
  }
  if constexpr (CN * CM > 1) cluster_wait();
  TS_END(EPI == EPI_QKV ? 1 : EPI + 2);
}

constexpr int SK_STAGES = 5;
constexpr int SK_STAGE_BYTES = 16384 + 5 * 4096;
constexpr int SK_RED_OFF = SK_STAGES * SK_STAGE_BYTES;
constexpr int SK_BAR_OFF = SK_RED_OFF + 40960;
constexpr int SK_SMEM = SK_BAR_OFF + 256 + 1024;
template <int KDIM, bool STATS>
__global__ void __launch_bounds__(288, 1) gemm_sk_kernel(const __grid_constant__ CUtensorMap tmA, const __grid_constant__ CUtensorMap tmB,
                                                         const __nv_bfloat16* __restrict__ resid, __nv_bfloat16* __restrict__ out) {
  constexpr int KT = KDIM / 128;
  extern __shared__ uint8_t smem_raw[];
  const uint32_t sbase = (smem_u32(smem_raw) + 1023u) & ~1023u;
  uint8_t* sptr = smem_raw + (sbase - smem_u32(smem_raw));
  const uint32_t sbar = sbase + SK_BAR_OFF;
  const int tid = threadIdx.x, warp = tid >> 5, lane = tid & 31;
  const int kh = blockIdx.x & 1, n0 = (blockIdx.x >> 1) * 160, m0 = blockIdx.y * 128;
  const int k0 = kh * (KDIM / 2);
  TS_BEGIN(STATS ? 3 : 5);
  if (tid == 0) {
    for (int i = 0; i < SK_STAGES; i++) { mbar_init(sbar + 8 * i, 1); mbar_init(sbar + 8 * (SK_STAGES + i), 2); }
    asm volatile("fence.mbarrier_init.release.cluster;" ::: "memory");
  }
  __syncthreads();
  pdl_launch();
  if (warp == 8) {
    if (lane == 0) {
      auto load_b = [&](int kt, int s) {
#pragma unroll
        for (int j = 0; j < 5; j++) tma_2d(sbase + s * SK_STAGE_BYTES + 16384 + j * 4096, &tmB, n0 + j * 32, k0 + kt * 64, sbar + 8 * s);
      };
      for (int s = 0; s < SK_STAGES; s++) { mbar_expect_tx(sbar + 8 * s, SK_STAGE_BYTES); load_b(s, s); }
      pdl_wait();
      for (int s = 0; s < SK_STAGES; s++) tma_2d(sbase + s * SK_STAGE_BYTES, &tmA, k0 + s * 64, m0, sbar + 8 * s);
      for (int kt = SK_STAGES; kt < KT; kt++) {
        const int s = kt % SK_STAGES;
        mbar_wait(sbar + 8 * (SK_STAGES + s), ((kt / SK_STAGES) - 1) & 1);
        mbar_expect_tx(sbar + 8 * s, SK_STAGE_BYTES);
        tma_2d(sbase + s * SK_STAGE_BYTES, &tmA, k0 + kt * 64, m0, sbar + 8 * s);
        load_b(kt, s);
      }
    }
    __syncwarp();
    cluster_arrive(); cluster_wait();
    return;
  }
  const int wg = warp >> 2, g = lane >> 2, t = lane & 3;
  float acc[80];
#pragma unroll
  for (int i = 0; i < 80; i++) acc[i] = 0.f;
  for (int kt = 0; kt < KT; kt++) {
    const int s = kt % SK_STAGES;
    mbar_wait(sbar + 8 * s, (kt / SK_STAGES) & 1);
    if (kt == 0) TS_MID(STATS ? 3 : 5, 0);
    const uint32_t sa = sbase + s * SK_STAGE_BYTES + wg * 8192;
    const uint32_t sb = sbase + s * SK_STAGE_BYTES + 16384;
    wgmma_fence();
#pragma unroll
    for (int ks = 0; ks < 4; ks++)
      wgmma_ss_n160(acc, make_desc(sa + ks * 32, 16, 1024, 1), make_desc(sb + ks * 1024, 4096, 512, 2), 1);
    wgmma_commit();
    wgmma_wait<1>();
    if (kt > 0 && kt - 1 + SK_STAGES < KT && (tid & 127) == 0) mbar_arrive(sbar + 8 * (SK_STAGES + (kt - 1) % SK_STAGES));
  }
  wgmma_wait<0>();
#pragma unroll
  for (int i = 0; i < 80; i++) asm volatile("" : "+f"(acc[i]) :: "memory");
  TS_MID(STATS ? 3 : 5, 1);
  pdl_wait();
  const int c0 = n0 + kh * 80;
  uint4 rv[5];
#pragma unroll
  for (int i = 0; i < 5; i++) {
    const int idx = i * 256 + tid, r = idx / 10, c = idx % 10;
    rv[i] = *(const uint4*)(resid + (size_t)(m0 + r) * DM + c0 + c * 8);
  }
  {
    uint32_t peer;
    asm volatile("mapa.shared::cluster.u32 %0, %1, %2;" : "=r"(peer) : "r"(sbase + SK_RED_OFF + tid * 16), "r"(kh ^ 1));
#pragma unroll
    for (int i = 0; i < 10; i++) {
      const float* a = kh ? &acc[4 * i] : &acc[40 + 4 * i];
      asm volatile("st.shared::cluster.v4.f32 [%0], {%1, %2, %3, %4};" :: "r"(peer + i * 4096), "f"(a[0]), "f"(a[1]), "f"(a[2]), "f"(a[3]) : "memory");
    }
  }
  cluster_arrive(); cluster_wait();
  constexpr int LDS = 176;
  const int r0 = wg * 64 + (warp & 3) * 16 + g;
#pragma unroll
  for (int i = 0; i < 10; i++) {
    const float4 p = *(const float4*)(sptr + SK_RED_OFF + i * 4096 + tid * 16);
    const float* a = kh ? &acc[40 + 4 * i] : &acc[4 * i];
    *(uint32_t*)(sptr + r0 * LDS + i * 16 + t * 4) = pack_bf16(a[0] + p.x, a[1] + p.y);
    *(uint32_t*)(sptr + (r0 + 8) * LDS + i * 16 + t * 4) = pack_bf16(a[2] + p.z, a[3] + p.w);
  }
  named_bar(1, 256);
#pragma unroll
  for (int i = 0; i < 5; i++) {
    const int idx = i * 256 + tid, r = idx / 10, c = idx % 10;
    const uint4 a = *(const uint4*)(sptr + r * LDS + c * 16);
    const uint4 b = rv[i];
    uint4 o;
    o.x = pack_bf16(bf_lo(a.x) + bf_lo(b.x), bf_hi(a.x) + bf_hi(b.x));
    o.y = pack_bf16(bf_lo(a.y) + bf_lo(b.y), bf_hi(a.y) + bf_hi(b.y));
    o.z = pack_bf16(bf_lo(a.z) + bf_lo(b.z), bf_hi(a.z) + bf_hi(b.z));
    o.w = pack_bf16(bf_lo(a.w) + bf_lo(b.w), bf_hi(a.w) + bf_hi(b.w));
    *(uint4*)(out + (size_t)(m0 + r) * DM + c0 + c * 8) = o;
    if constexpr (STATS) *(uint4*)(sptr + r * LDS + c * 16) = o;
  }
  if constexpr (STATS) {
    named_bar(1, 256);
    const int r = tid >> 1, hf = tid & 1;
    float f[40];
#pragma unroll
    for (int i = 0; i < 5; i++) {
      const uint4 v = *(const uint4*)(sptr + r * LDS + hf * 80 + i * 16);
      f[8 * i] = bf_lo(v.x); f[8 * i + 1] = bf_hi(v.x); f[8 * i + 2] = bf_lo(v.y); f[8 * i + 3] = bf_hi(v.y);
      f[8 * i + 4] = bf_lo(v.z); f[8 * i + 5] = bf_hi(v.z); f[8 * i + 6] = bf_lo(v.w); f[8 * i + 7] = bf_hi(v.w);
    }
    float s = 0.f;
#pragma unroll
    for (int i = 0; i < 40; i++) s += f[i];
    s += __shfl_xor_sync(~0u, s, 1);
    const float mu = s * (1.0f / 80.f);
    float q = 0.f;
#pragma unroll
    for (int i = 0; i < 40; i++) { const float d = f[i] - mu; q += d * d; }
    q += __shfl_xor_sync(~0u, q, 1);
    if (hf == 0) g_part2[(m0 + r) * 8 + blockIdx.x] = make_float2(s, q);
  }
  TS_END(STATS ? 3 : 5);
}

#define POLY_NUM 5
__device__ __forceinline__ float ex2_poly(float x, int shl23) {
  const float MAGIC = 12582912.f;
  const float tt = x + MAGIC;
  const float f = x - (tt - MAGIC);
  float p = fmaf(0.0013276472454890609f, f, 0.009675540961325169f);
  p = fmaf(p, f, 0.05550713092088699f);
  p = fmaf(p, f, 0.24022120237350464f);
  p = fmaf(p, f, 0.6931469440460205f);
  p = fmaf(p, f, 1.0000001192092896f);
  return __int_as_float(__float_as_int(tt) * shl23 + __float_as_int(p));
}
constexpr int KV_BYTES = S_LEN * 48;
constexpr int ATT_SMEM = 2 * KV_BYTES + 256;

__global__ void __launch_bounds__(512, 1) attn_kernel(int shl23) {
  extern __shared__ __align__(1024) uint8_t smem[];
  const int h = blockIdx.x >> 2, qb = blockIdx.x & 3;
  const uint32_t sK = smem_u32(smem), sV = sK + KV_BYTES, sBar = sV + KV_BYTES;
  const int tid = threadIdx.x;
  TS_BEGIN(2);
  if (tid == 0) {
    for (int i = 0; i < 8; i++) mbar_init(sBar + 8 * i, 1);
    asm volatile("fence.mbarrier_init.release.cluster;" ::: "memory");
  }
  pdl_launch();
  pdl_wait();
  if (tid == 0) {
    const uint8_t* gk = (const uint8_t*)(g_k + (size_t)h * S_LEN * 24);
    const uint8_t* gv = (const uint8_t*)(g_v + (size_t)h * S_LEN * 24);
    for (int i = 0; i < 8; i++) {
      mbar_expect_tx(sBar + 8 * i, 2 * 12288);
      bulk_g2s(sK + i * 12288, gk + i * 12288, 12288, sBar + 8 * i);
      bulk_g2s(sV + i * 12288, gv + i * 12288, 12288, sBar + 8 * i);
    }
  }
  __syncthreads();
  const int wg = tid >> 7, warp = (tid >> 5) & 3, lane = tid & 31, g = lane >> 2, t = lane & 3;
  float ka = 0.f, kb = 0.f;
#pragma unroll
  for (int i = 0; i < 8; i++) {
    const float2 v = *(const float2*)&g_kn[(i * NH + h) * 2];
    ka = (v.x > ka || v.x != v.x) ? v.x : ka;
    kb = (v.y > kb || v.y != v.y) ? v.y : kb;
  }
  const float kn = sqrtf(ka + kb);
  for (int it = 0; it < 2; it++) {
    const int q0 = qb * 512 + (it * 4 + wg) * 64 + warp * 16;
    uint32_t qa[4], qc[4];
    const uint32_t* qr0 = (const uint32_t*)(g_q + (size_t)(q0 + g) * DM + h * DH);
    const uint32_t* qr1 = (const uint32_t*)(g_q + (size_t)(q0 + g + 8) * DM + h * DH);
    qa[0] = qr0[t]; qa[1] = qr1[t]; qa[2] = qr0[t + 4]; qa[3] = qr1[t + 4];
    qc[0] = (t < 2) ? qr0[t + 8] : 0u; qc[1] = (t < 2) ? qr1[t + 8] : 0u; qc[2] = 0; qc[3] = 0;
    auto sq = [](uint32_t u) { const float a = bf_lo(u), b = bf_hi(u); return a * a + b * b; };
    float n0 = sq(qa[0]) + sq(qa[2]) + sq(qc[0]);
    float n1 = sq(qa[1]) + sq(qa[3]) + sq(qc[1]);
    n0 += __shfl_xor_sync(~0u, n0, 1); n0 += __shfl_xor_sync(~0u, n0, 2);
    n1 += __shfl_xor_sync(~0u, n1, 1); n1 += __shfl_xor_sync(~0u, n1, 2);
    const float m0 = ceilf(sqrtf(n0) * kn * 1.001f) + 1.f, m1 = ceilf(sqrtf(n1) * kn * 1.001f) + 1.f;
    const bool unsafe = !(m0 <= 62.f && m1 <= 62.f);
    uint32_t any_unsafe;
    asm volatile("{\n.reg .pred p, q;\nsetp.ne.u32 p, %1, 0;\nbarrier.cta.red.or.pred q, %2, 128, p;\nselp.u32 %0, 1, 0, q;\n}"
                 : "=r"(any_unsafe) : "r"((uint32_t)unsafe), "r"(1 + wg) : "memory");
    float O[12];
    float S[32];
    if (!__any_sync(~0u, any_unsafe)) {
      if (t == 2) { qc[0] = pack_bf16(-m0, 0.f); qc[1] = pack_bf16(-m1, 0.f); }
      for (int j = 0; j < 32; j++) {
        if (it == 0 && (j & 3) == 0) mbar_wait(sBar + 8 * (j >> 2), 0);
        const uint64_t dk = make_desc(sK + j * 8 * 384, 128, 384, 0);
        wgmma_fence();
        wgmma_rs_n64(S, qa[0], qa[1], qa[2], qa[3], dk, 0);
        wgmma_rs_n64(S, qc[0], qc[1], qc[2], qc[3], dk + (256 >> 4), 1);
        wgmma_commit();
        wgmma_wait<0>();
        uint32_t P[16];
#pragma unroll
        for (int i = 0; i < 16; i++) {
          const bool usepoly = ((i + 1) * POLY_NUM / 16) != (i * POLY_NUM / 16);
          float a, b;
          if (usepoly) { a = ex2_poly(S[2 * i], shl23); b = ex2_poly(S[2 * i + 1], shl23); }
          else { a = ex2_mufu(S[2 * i]); b = ex2_mufu(S[2 * i + 1]); }
          P[i] = pack_bf16(a, b);
        }
        wgmma_fence();
        const uint64_t dv = make_desc(sV + j * 8 * 384, 384, 128, 0);
#pragma unroll
        for (int ks = 0; ks < 4; ks++)
          wgmma_rs_n24_tb(O, P[4 * ks], P[4 * ks + 1], P[4 * ks + 2], P[4 * ks + 3], dv + ((ks * 768) >> 4), (j | ks) != 0);
        wgmma_commit();
      }
    } else {
      float mx0 = -INFINITY, mx1 = -INFINITY;
      for (int j = 0; j < 32; j++) {
        if (it == 0 && (j & 3) == 0) mbar_wait(sBar + 8 * (j >> 2), 0);
        const uint64_t dk = make_desc(sK + j * 8 * 384, 128, 384, 0);
        wgmma_fence();
        wgmma_rs_n64(S, qa[0], qa[1], qa[2], qa[3], dk, 0);
        wgmma_rs_n64(S, qc[0], qc[1], qc[2], qc[3], dk + (256 >> 4), 1);
        wgmma_commit();
        wgmma_wait<0>();
#pragma unroll
        for (int i = 0; i < 8; i++) {
          mx0 = fmaxf(mx0, fmaxf(S[4 * i], S[4 * i + 1]));
          mx1 = fmaxf(mx1, fmaxf(S[4 * i + 2], S[4 * i + 3]));
        }
      }
      mx0 = fmaxf(mx0, __shfl_xor_sync(~0u, mx0, 1)); mx0 = fmaxf(mx0, __shfl_xor_sync(~0u, mx0, 2));
      mx1 = fmaxf(mx1, __shfl_xor_sync(~0u, mx1, 1)); mx1 = fmaxf(mx1, __shfl_xor_sync(~0u, mx1, 2));
      for (int j = 0; j < 32; j++) {
        const uint64_t dk = make_desc(sK + j * 8 * 384, 128, 384, 0);
        wgmma_fence();
        wgmma_rs_n64(S, qa[0], qa[1], qa[2], qa[3], dk, 0);
        wgmma_rs_n64(S, qc[0], qc[1], qc[2], qc[3], dk + (256 >> 4), 1);
        wgmma_commit();
        wgmma_wait<0>();
        uint32_t P[16];
#pragma unroll
        for (int i = 0; i < 8; i++) {
          P[2 * i] = pack_bf16(ex2_mufu(S[4 * i] - mx0), ex2_mufu(S[4 * i + 1] - mx0));
          P[2 * i + 1] = pack_bf16(ex2_mufu(S[4 * i + 2] - mx1), ex2_mufu(S[4 * i + 3] - mx1));
        }
        wgmma_fence();
        const uint64_t dv = make_desc(sV + j * 8 * 384, 384, 128, 0);
#pragma unroll
        for (int ks = 0; ks < 4; ks++)
          wgmma_rs_n24_tb(O, P[4 * ks], P[4 * ks + 1], P[4 * ks + 2], P[4 * ks + 3], dv + ((ks * 768) >> 4), (j | ks) != 0);
        wgmma_commit();
      }
    }
    wgmma_wait<0>();
#pragma unroll
    for (int i = 0; i < 12; i++) asm volatile("" : "+f"(O[i]) :: "memory");
    const float l0 = __shfl_sync(~0u, O[8], (lane & ~3) | 2), l1 = __shfl_sync(~0u, O[10], (lane & ~3) | 2);
    const float r0 = 1.f / l0, r1 = 1.f / l1;
    uint32_t* o0 = (uint32_t*)(g_o + (size_t)(q0 + g) * DM + h * DH);
    uint32_t* o1 = (uint32_t*)(g_o + (size_t)(q0 + g + 8) * DM + h * DH);
    o0[t] = pack_bf16(O[0] * r0, O[1] * r0); o1[t] = pack_bf16(O[2] * r1, O[3] * r1);
    o0[t + 4] = pack_bf16(O[4] * r0, O[5] * r0); o1[t + 4] = pack_bf16(O[6] * r1, O[7] * r1);
    if (t < 2) { o0[t + 8] = pack_bf16(O[8] * r0, O[9] * r0); o1[t + 8] = pack_bf16(O[10] * r1, O[11] * r1); }
  }
  TS_END(2);
}

typedef CUresult (*EncodeFn)(CUtensorMap*, CUtensorMapDataType, cuuint32_t, void*, const cuuint64_t*, const cuuint64_t*, const cuuint32_t*,
                             const cuuint32_t*, CUtensorMapInterleave, CUtensorMapSwizzle, CUtensorMapL2promotion, CUtensorMapFloatOOBfill);
static EncodeFn get_encode() {
  static EncodeFn fn = nullptr;
  if (!fn) {
    void* p = nullptr; cudaDriverEntryPointQueryResult st;
    cudaGetDriverEntryPoint("cuTensorMapEncodeTiled", &p, cudaEnableDefault, &st);
    fn = (EncodeFn)p;
  }
  return fn;
}
static CUtensorMap make_map(const void* ptr, int rows, int cols, int box_rows, int box_cols = 64) {
  CUtensorMap m;
  cuuint64_t dims[2] = {(cuuint64_t)cols, (cuuint64_t)rows};
  cuuint64_t strides[1] = {(cuuint64_t)cols * 2};
  cuuint32_t box[2] = {(cuuint32_t)box_cols, (cuuint32_t)box_rows};
  cuuint32_t es[2] = {1, 1};
  get_encode()(&m, CU_TENSOR_MAP_DATA_TYPE_BFLOAT16, 2, const_cast<void*>(ptr), dims, strides, box, es, CU_TENSOR_MAP_INTERLEAVE_NONE,
               box_cols == 64 ? CU_TENSOR_MAP_SWIZZLE_128B : CU_TENSOR_MAP_SWIZZLE_64B, CU_TENSOR_MAP_L2_PROMOTION_L2_128B, CU_TENSOR_MAP_FLOAT_OOB_FILL_NONE);
  return m;
}
template <typename... KArgs, typename... Args>
static void launch(void (*kern)(KArgs...), dim3 grid, dim3 block, size_t smem, bool pdl, dim3 cluster, Args... args) {
  cudaLaunchConfig_t cfg = {};
  cfg.gridDim = grid; cfg.blockDim = block; cfg.dynamicSmemBytes = smem; cfg.stream = cudaStreamPerThread;
  cudaLaunchAttribute at[2];
  int na = 0;
  if (pdl) { at[na].id = cudaLaunchAttributeProgrammaticStreamSerialization; at[na].val.programmaticStreamSerializationAllowed = 1; na++; }
  if (cluster.x * cluster.y > 1) { at[na].id = cudaLaunchAttributeClusterDimension; at[na].val.clusterDim.x = cluster.x; at[na].val.clusterDim.y = cluster.y; at[na].val.clusterDim.z = 1; na++; }
  cfg.attrs = at; cfg.numAttrs = na;
  cudaLaunchKernelEx(&cfg, kern, KArgs(args)...);
}

extern "C" void kernel_launch(void* const* d_in, const int* in_sizes, int n_in, void* d_out, int out_size) {
  const __nv_bfloat16* x = (const __nv_bfloat16*)d_in[0];
  const __nv_bfloat16* wqkv = (const __nv_bfloat16*)d_in[1];
  const __nv_bfloat16* wo = (const __nv_bfloat16*)d_in[2];
  const __nv_bfloat16* wgate = (const __nv_bfloat16*)d_in[4];
  const __nv_bfloat16* wup = (const __nv_bfloat16*)d_in[5];
  const __nv_bfloat16* wdown = (const __nv_bfloat16*)d_in[6];
  __nv_bfloat16* out = (__nv_bfloat16*)d_out;
  void *p_o, *p_h, *p_act;
  cudaGetSymbolAddress(&p_o, g_o); cudaGetSymbolAddress(&p_h, g_h); cudaGetSymbolAddress(&p_act, g_act);

#define A_CN 1
#define A_CM 1
#define D_CN 1
#define D_CM 1
  auto kA = gemm_kernel<256, 128, 1, DM, 4, EPI_QKV, 1, A_CN, A_CM>;
  auto kC = gemm_sk_kernel<DM, true>;
  auto kD = gemm_kernel<128, 192, 2, DM, 3, EPI_GLU, 1, D_CN, D_CM>;
  auto kE = gemm_sk_kernel<DFF, false>;
  constexpr int smA = GemmCfg<256, 128, 1, 4>::SMEM, smC = SK_SMEM, smD = GemmCfg<128, 192, 2, 3>::SMEM;
  cudaFuncSetAttribute(kA, cudaFuncAttributeMaxDynamicSharedMemorySize, smA);
  cudaFuncSetAttribute(kC, cudaFuncAttributeMaxDynamicSharedMemorySize, smC);
  cudaFuncSetAttribute(kD, cudaFuncAttributeMaxDynamicSharedMemorySize, smD);
  cudaFuncSetAttribute(kE, cudaFuncAttributeMaxDynamicSharedMemorySize, smC);
  cudaFuncSetAttribute(attn_kernel, cudaFuncAttributeMaxDynamicSharedMemorySize, ATT_SMEM);

  const CUtensorMap tm_x = make_map(x, S_LEN, DM, 256 / A_CN), tm_wqkv = make_map(wqkv, DM, 3 * DM, 2 % A_CM ? 64 / A_CM : 64);
  const CUtensorMap tm_o = make_map(p_o, S_LEN, DM, 128), tm_wo = make_map(wo, DM, DM, 64, 32);
  const CUtensorMap tm_h = make_map(p_h, S_LEN, DM, 128 / D_CN), tm_wg = make_map(wgate, DM, DFF, 6 % D_CM ? 64 / D_CM : 64), tm_wu = make_map(wup, DM, DFF, 6 % D_CM ? 64 / D_CM : 64);
  const CUtensorMap tm_act = make_map(p_act, S_LEN, DFF, 128), tm_wd = make_map(wdown, DFF, DM, 64, 32);

  launch(pre_kernel, dim3(PRE_COL_BLOCKS + PRE_ROW_BLOCKS), dim3(256), 0, false, dim3(1, 1), x, wqkv, wgate, wup);
  launch(kA, dim3(15, 8), dim3(288), smA, true, dim3(A_CN, A_CM), tm_x, tm_wqkv, tm_wqkv, (const __nv_bfloat16*)nullptr, (__nv_bfloat16*)nullptr);
  launch(attn_kernel, dim3(128), dim3(512), ATT_SMEM, true, dim3(1, 1), 0x800000);
  launch(kC, dim3(8, 16), dim3(288), smC, true, dim3(2, 1), tm_o, tm_wo, x, (__nv_bfloat16*)p_h);
  launch(kD, dim3(8, 16), dim3(384), smD, true, dim3(D_CN, D_CM), tm_h, tm_wg, tm_wu, (const __nv_bfloat16*)nullptr, (__nv_bfloat16*)p_act);
  launch(kE, dim3(8, 16), dim3(288), smC, true, dim3(2, 1), tm_act, tm_wd, (const __nv_bfloat16*)p_h, out);
}
```

```cpp
#include <cuda_runtime.h>
#include <cuda_bf16.h>
#include <cuda.h>
#include <stdint.h>

constexpr int S_LEN = 2048, DM = 640, NH = 32, DH = 20, DFF = 1536;

__device__ __align__(1024) __nv_bfloat16 g_q[S_LEN * DM];
__device__ __align__(1024) __nv_bfloat16 g_k[NH * S_LEN * 24];
__device__ __align__(1024) __nv_bfloat16 g_v[NH * S_LEN * 24];
__device__ __align__(1024) __nv_bfloat16 g_o[S_LEN * DM];
__device__ __align__(1024) __nv_bfloat16 g_h[S_LEN * DM];
__device__ __align__(1024) __nv_bfloat16 g_act[S_LEN * DFF];
__device__ float g_kn[8 * NH * 2];
__device__ float2 g_stat1[S_LEN];
__device__ float g_cs_qkv[3 * DM];
__device__ float g_cs_g[DFF];
__device__ float g_cs_u[DFF];
__device__ float2 g_part2[S_LEN * 10];

#define TS_BEGIN(k)
#define TS_END(k)
#define TS_MID(k, i)
__device__ __forceinline__ uint32_t smem_u32(const void* p) { return (uint32_t)__cvta_generic_to_shared(p); }
__device__ __forceinline__ void mbar_init(uint32_t bar, uint32_t cnt) { asm volatile("mbarrier.init.shared::cta.b64 [%0], %1;" :: "r"(bar), "r"(cnt)); }
__device__ __forceinline__ void mbar_expect_tx(uint32_t bar, uint32_t bytes) { asm volatile("mbarrier.arrive.expect_tx.shared::cta.b64 _, [%0], %1;" :: "r"(bar), "r"(bytes) : "memory"); }
__device__ __forceinline__ void mbar_arrive(uint32_t bar) { asm volatile("mbarrier.arrive.shared::cta.b64 _, [%0];" :: "r"(bar) : "memory"); }
__device__ __forceinline__ void mbar_wait(uint32_t bar, uint32_t parity) {
  uint32_t done;
  uint32_t spins = 0;
  do {
    asm volatile("{\n.reg .pred P1;\nmbarrier.try_wait.parity.shared::cta.b64 P1, [%1], %2;\nselp.u32 %0, 1, 0, P1;\n}" : "=r"(done) : "r"(bar), "r"(parity) : "memory");
  } while (!done && ++spins < (1u << 24));
}
__device__ __forceinline__ void bulk_g2s(uint32_t dst, const void* src, uint32_t bytes, uint32_t bar) {
  asm volatile("cp.async.bulk.shared::cluster.global.mbarrier::complete_tx::bytes [%0], [%1], %2, [%3];" :: "r"(dst), "l"(src), "r"(bytes), "r"(bar) : "memory");
}
__device__ __forceinline__ void tma_2d(uint32_t dst, const CUtensorMap* tm, int c0, int c1, uint32_t bar) {
  asm volatile("cp.async.bulk.tensor.2d.shared::cluster.global.mbarrier::complete_tx::bytes [%0], [%1, {%3, %4}], [%2];"
               :: "r"(dst), "l"(tm), "r"(bar), "r"(c0), "r"(c1) : "memory");
}
__device__ __forceinline__ void tma_2d_mc(uint32_t dst, const CUtensorMap* tm, int c0, int c1, uint32_t bar, uint16_t mask) {
  asm volatile("cp.async.bulk.tensor.2d.shared::cluster.global.mbarrier::complete_tx::bytes.multicast::cluster [%0], [%1, {%3, %4}], [%2], %5;"
               :: "r"(dst), "l"(tm), "r"(bar), "r"(c0), "r"(c1), "h"(mask) : "memory");
}
__device__ __forceinline__ void mbar_arrive_remote(uint32_t bar, uint32_t rank) {
  asm volatile("{\n.reg .b32 ra;\nmapa.shared::cluster.u32 ra, %0, %1;\nmbarrier.arrive.release.cluster.shared::cluster.b64 _, [ra];\n}" :: "r"(bar), "r"(rank) : "memory");
}
__device__ __forceinline__ void cluster_arrive() { asm volatile("barrier.cluster.arrive.release.aligned;" ::: "memory"); }
__device__ __forceinline__ void cluster_wait() { asm volatile("barrier.cluster.wait.acquire.aligned;" ::: "memory"); }
__device__ __forceinline__ void wgmma_fence() { asm volatile("wgmma.fence.sync.aligned;" ::: "memory"); }
__device__ __forceinline__ void wgmma_commit() { asm volatile("wgmma.commit_group.sync.aligned;" ::: "memory"); }
template <int N> __device__ __forceinline__ void wgmma_wait() { asm volatile("wgmma.wait_group.sync.aligned %0;" :: "n"(N) : "memory"); }
__device__ __forceinline__ void pdl_wait() { asm volatile("griddepcontrol.wait;" ::: "memory"); }
__device__ __forceinline__ void pdl_launch() { asm volatile("griddepcontrol.launch_dependents;" ::: "memory"); }
__device__ __forceinline__ void named_bar(int id, int n) { asm volatile("bar.sync %0, %1;" :: "r"(id), "r"(n) : "memory"); }
__device__ __forceinline__ uint64_t make_desc(uint32_t addr, uint32_t lbo, uint32_t sbo, uint32_t swz) {
  return (uint64_t)((addr & 0x3FFFF) >> 4) | ((uint64_t)(lbo >> 4) << 16) | ((uint64_t)(sbo >> 4) << 32) | ((uint64_t)swz << 62);
}
__device__ __forceinline__ uint32_t pack_bf16(float lo, float hi) { uint32_t r; asm("cvt.rn.bf16x2.f32 %0, %1, %2;" : "=r"(r) : "f"(hi), "f"(lo)); return r; }
__device__ __forceinline__ float bf_lo(uint32_t u) { return __uint_as_float(u << 16); }
__device__ __forceinline__ float bf_hi(uint32_t u) { return __uint_as_float(u & 0xffff0000u); }
__device__ __forceinline__ float bf_round(float x) { return __bfloat162float(__float2bfloat16_rn(x)); }
__device__ __forceinline__ float ex2_mufu(float x) { float y; asm("ex2.approx.ftz.f32 %0, %1;" : "=f"(y) : "f"(x)); return y; }

__device__ __forceinline__ void wgmma_ss_n80(float (&d)[40], uint64_t da, uint64_t db, int scale_d) {
  asm volatile("{\n.reg .pred p;\nsetp.ne.b32 p, %42, 0;\n"
    "wgmma.mma_async.sync.aligned.m64n80k16.f32.bf16.bf16 {%0,%1,%2,%3,%4,%5,%6,%7,%8,%9,%10,%11,%12,%13,%14,%15,%16,%17,%18,%19,%20,%21,%22,%23,%24,%25,%26,%27,%28,%29,%30,%31,%32,%33,%34,%35,%36,%37,%38,%39}, %40, %41, p, 1, 1, 0, 1;\n}\n"
    : "+f"(d[0]),"+f"(d[1]),"+f"(d[2]),"+f"(d[3]),"+f"(d[4]),"+f"(d[5]),"+f"(d[6]),"+f"(d[7]),"+f"(d[8]),"+f"(d[9]),"+f"(d[10]),"+f"(d[11]),"+f"(d[12]),"+f"(d[13]),"+f"(d[14]),"+f"(d[15]),"+f"(d[16]),"+f"(d[17]),"+f"(d[18]),"+f"(d[19]),"+f"(d[20]),"+f"(d[21]),"+f"(d[22]),"+f"(d[23]),"+f"(d[24]),"+f"(d[25]),"+f"(d[26]),"+f"(d[27]),"+f"(d[28]),"+f"(d[29]),"+f"(d[30]),"+f"(d[31]),"+f"(d[32]),"+f"(d[33]),"+f"(d[34]),"+f"(d[35]),"+f"(d[36]),"+f"(d[37]),"+f"(d[38]),"+f"(d[39])
    : "l"(da), "l"(db), "r"(scale_d));
}
__device__ __forceinline__ void wgmma_ss_n128(float (&d)[64], uint64_t da, uint64_t db, int scale_d) {
  asm volatile("{\n.reg .pred p;\nsetp.ne.b32 p, %66, 0;\n"
    "wgmma.mma_async.sync.aligned.m64n128k16.f32.bf16.bf16 {%0,%1,%2,%3,%4,%5,%6,%7,%8,%9,%10,%11,%12,%13,%14,%15,%16,%17,%18,%19,%20,%21,%22,%23,%24,%25,%26,%27,%28,%29,%30,%31,%32,%33,%34,%35,%36,%37,%38,%39,%40,%41,%42,%43,%44,%45,%46,%47,%48,%49,%50,%51,%52,%53,%54,%55,%56,%57,%58,%59,%60,%61,%62,%63}, %64, %65, p, 1, 1, 0, 1;\n}\n"
    : "+f"(d[0]),"+f"(d[1]),"+f"(d[2]),"+f"(d[3]),"+f"(d[4]),"+f"(d[5]),"+f"(d[6]),"+f"(d[7]),"+f"(d[8]),"+f"(d[9]),"+f"(d[10]),"+f"(d[11]),"+f"(d[12]),"+f"(d[13]),"+f"(d[14]),"+f"(d[15]),"+f"(d[16]),"+f"(d[17]),"+f"(d[18]),"+f"(d[19]),"+f"(d[20]),"+f"(d[21]),"+f"(d[22]),"+f"(d[23]),"+f"(d[24]),"+f"(d[25]),"+f"(d[26]),"+f"(d[27]),"+f"(d[28]),"+f"(d[29]),"+f"(d[30]),"+f"(d[31]),"+f"(d[32]),"+f"(d[33]),"+f"(d[34]),"+f"(d[35]),"+f"(d[36]),"+f"(d[37]),"+f"(d[38]),"+f"(d[39]),"+f"(d[40]),"+f"(d[41]),"+f"(d[42]),"+f"(d[43]),"+f"(d[44]),"+f"(d[45]),"+f"(d[46]),"+f"(d[47]),"+f"(d[48]),"+f"(d[49]),"+f"(d[50]),"+f"(d[51]),"+f"(d[52]),"+f"(d[53]),"+f"(d[54]),"+f"(d[55]),"+f"(d[56]),"+f"(d[57]),"+f"(d[58]),"+f"(d[59]),"+f"(d[60]),"+f"(d[61]),"+f"(d[62]),"+f"(d[63])
    : "l"(da), "l"(db), "r"(scale_d));
}
__device__ __forceinline__ void wgmma_ss_n192(float (&d)[96], uint64_t da, uint64_t db, int scale_d) {
  asm volatile("{\n.reg .pred p;\nsetp.ne.b32 p, %98, 0;\n"
    "wgmma.mma_async.sync.aligned.m64n192k16.f32.bf16.bf16 {%0,%1,%2,%3,%4,%5,%6,%7,%8,%9,%10,%11,%12,%13,%14,%15,%16,%17,%18,%19,%20,%21,%22,%23,%24,%25,%26,%27,%28,%29,%30,%31,%32,%33,%34,%35,%36,%37,%38,%39,%40,%41,%42,%43,%44,%45,%46,%47,%48,%49,%50,%51,%52,%53,%54,%55,%56,%57,%58,%59,%60,%61,%62,%63,%64,%65,%66,%67,%68,%69,%70,%71,%72,%73,%74,%75,%76,%77,%78,%79,%80,%81,%82,%83,%84,%85,%86,%87,%88,%89,%90,%91,%92,%93,%94,%95}, %96, %97, p, 1, 1, 0, 1;\n}\n"
    : "+f"(d[0]),"+f"(d[1]),"+f"(d[2]),"+f"(d[3]),"+f"(d[4]),"+f"(d[5]),"+f"(d[6]),"+f"(d[7]),"+f"(d[8]),"+f"(d[9]),"+f"(d[10]),"+f"(d[11]),"+f"(d[12]),"+f"(d[13]),"+f"(d[14]),"+f"(d[15]),"+f"(d[16]),"+f"(d[17]),"+f"(d[18]),"+f"(d[19]),"+f"(d[20]),"+f"(d[21]),"+f"(d[22]),"+f"(d[23]),"+f"(d[24]),"+f"(d[25]),"+f"(d[26]),"+f"(d[27]),"+f"(d[28]),"+f"(d[29]),"+f"(d[30]),"+f"(d[31]),"+f"(d[32]),"+f"(d[33]),"+f"(d[34]),"+f"(d[35]),"+f"(d[36]),"+f"(d[37]),"+f"(d[38]),"+f"(d[39]),"+f"(d[40]),"+f"(d[41]),"+f"(d[42]),"+f"(d[43]),"+f"(d[44]),"+f"(d[45]),"+f"(d[46]),"+f"(d[47]),"+f"(d[48]),"+f"(d[49]),"+f"(d[50]),"+f"(d[51]),"+f"(d[52]),"+f"(d[53]),"+f"(d[54]),"+f"(d[55]),"+f"(d[56]),"+f"(d[57]),"+f"(d[58]),"+f"(d[59]),"+f"(d[60]),"+f"(d[61]),"+f"(d[62]),"+f"(d[63]),"+f"(d[64]),"+f"(d[65]),"+f"(d[66]),"+f"(d[67]),"+f"(d[68]),"+f"(d[69]),"+f"(d[70]),"+f"(d[71]),"+f"(d[72]),"+f"(d[73]),"+f"(d[74]),"+f"(d[75]),"+f"(d[76]),"+f"(d[77]),"+f"(d[78]),"+f"(d[79]),"+f"(d[80]),"+f"(d[81]),"+f"(d[82]),"+f"(d[83]),"+f"(d[84]),"+f"(d[85]),"+f"(d[86]),"+f"(d[87]),"+f"(d[88]),"+f"(d[89]),"+f"(d[90]),"+f"(d[91]),"+f"(d[92]),"+f"(d[93]),"+f"(d[94]),"+f"(d[95])
    : "l"(da), "l"(db), "r"(scale_d));
}
__device__ __forceinline__ void wgmma_rs_n64(float (&d)[32], uint32_t a0, uint32_t a1, uint32_t a2, uint32_t a3, uint64_t db, int scale_d) {
  asm volatile("{\n.reg .pred p;\nsetp.ne.b32 p, %37, 0;\n"
    "wgmma.mma_async.sync.aligned.m64n64k16.f32.bf16.bf16 {%0,%1,%2,%3,%4,%5,%6,%7,%8,%9,%10,%11,%12,%13,%14,%15,%16,%17,%18,%19,%20,%21,%22,%23,%24,%25,%26,%27,%28,%29,%30,%31}, {%32,%33,%34,%35}, %36, p, 1, 1, 0;\n}\n"
    : "+f"(d[0]),"+f"(d[1]),"+f"(d[2]),"+f"(d[3]),"+f"(d[4]),"+f"(d[5]),"+f"(d[6]),"+f"(d[7]),"+f"(d[8]),"+f"(d[9]),"+f"(d[10]),"+f"(d[11]),"+f"(d[12]),"+f"(d[13]),"+f"(d[14]),"+f"(d[15]),"+f"(d[16]),"+f"(d[17]),"+f"(d[18]),"+f"(d[19]),"+f"(d[20]),"+f"(d[21]),"+f"(d[22]),"+f"(d[23]),"+f"(d[24]),"+f"(d[25]),"+f"(d[26]),"+f"(d[27]),"+f"(d[28]),"+f"(d[29]),"+f"(d[30]),"+f"(d[31])
    : "r"(a0), "r"(a1), "r"(a2), "r"(a3), "l"(db), "r"(scale_d));
}
__device__ __forceinline__ void wgmma_rs_n24_tb(float (&d)[12], uint32_t a0, uint32_t a1, uint32_t a2, uint32_t a3, uint64_t db, int scale_d) {
  asm volatile("{\n.reg .pred p;\nsetp.ne.b32 p, %17, 0;\n"
    "wgmma.mma_async.sync.aligned.m64n24k16.f32.bf16.bf16 {%0,%1,%2,%3,%4,%5,%6,%7,%8,%9,%10,%11}, {%12,%13,%14,%15}, %16, p, 1, 1, 1;\n}\n"
    : "+f"(d[0]),"+f"(d[1]),"+f"(d[2]),"+f"(d[3]),"+f"(d[4]),"+f"(d[5]),"+f"(d[6]),"+f"(d[7]),"+f"(d[8]),"+f"(d[9]),"+f"(d[10]),"+f"(d[11])
    : "r"(a0), "r"(a1), "r"(a2), "r"(a3), "l"(db), "r"(scale_d));
}

constexpr int PRE_ROW_BLOCKS = 64;
constexpr int PRE_COL_BLOCKS = (3 * DM + 2 * DFF) / 64;
__device__ __forceinline__ float2 ln_finish(float mean, float var) {
  float mb = bf_round(mean);
  float s = bf_round(sqrtf(bf_round(bf_round(var) + 1e-5f)));
  return make_float2(mb, 1.0f / s);
}
__global__ void __launch_bounds__(256) pre_kernel(const __nv_bfloat16* __restrict__ x, const __nv_bfloat16* __restrict__ wqkv,
                                                  const __nv_bfloat16* __restrict__ wg, const __nv_bfloat16* __restrict__ wu) {
  TS_BEGIN(0);
  pdl_launch();
  const int tid = threadIdx.x, lane = tid & 31, warp = tid >> 5;
  if (blockIdx.x < PRE_COL_BLOCKS) {
    __shared__ float red[32][65];
    int c0 = blockIdx.x * 64;
    const __nv_bfloat16* w; float* dst; int ld;
    if (c0 < 3 * DM) { w = wqkv; dst = g_cs_qkv; ld = 3 * DM; }
    else if (c0 < 3 * DM + DFF) { w = wg; dst = g_cs_g; ld = DFF; c0 -= 3 * DM; }
    else { w = wu; dst = g_cs_u; ld = DFF; c0 -= 3 * DM + DFF; }
    const int cg = tid & 7, r0 = tid >> 3;
    float acc[8];
#pragma unroll
    for (int i = 0; i < 8; i++) acc[i] = 0.f;
#pragma unroll 5
    for (int r = r0; r < DM; r += 32) {
      uint4 v = __ldg((const uint4*)(w + (size_t)r * ld + c0 + cg * 8));
      acc[0] += bf_lo(v.x); acc[1] += bf_hi(v.x); acc[2] += bf_lo(v.y); acc[3] += bf_hi(v.y);
      acc[4] += bf_lo(v.z); acc[5] += bf_hi(v.z); acc[6] += bf_lo(v.w); acc[7] += bf_hi(v.w);
    }
#pragma unroll
    for (int i = 0; i < 8; i++) red[r0][cg * 8 + i] = acc[i];
    __syncthreads();
    if (tid < 64) {
      float s = 0.f;
#pragma unroll
      for (int r = 0; r < 32; r++) s += red[r][tid];
      dst[c0 + tid] = s;
    }
  } else {
    const int rb = blockIdx.x - PRE_COL_BLOCKS;
#pragma unroll
    for (int i = 0; i < 4; i++) {
      const int row = rb * 32 + warp * 4 + i;
      const uint4* p = (const uint4*)(x + (size_t)row * DM);
      uint4 v0 = __ldg(p + lane), v1 = __ldg(p + 32 + lane), v2 = make_uint4(0, 0, 0, 0);
      if (lane < 16) v2 = __ldg(p + 64 + lane);
      float f[24];
      uint32_t u[12] = {v0.x, v0.y, v0.z, v0.w, v1.x, v1.y, v1.z, v1.w, v2.x, v2.y, v2.z, v2.w};
#pragma unroll
      for (int j = 0; j < 12; j++) { f[2 * j] = bf_lo(u[j]); f[2 * j + 1] = bf_hi(u[j]); }
      float s = 0.f;
#pragma unroll
      for (int j = 0; j < 24; j++) s += f[j];
#pragma unroll
      for (int o = 16; o; o >>= 1) s += __shfl_xor_sync(~0u, s, o);
      const float mean = s * (1.0f / DM);
      float q = 0.f;
#pragma unroll
      for (int j = 0; j < 16; j++) { float d = f[j] - mean; q += d * d; }
      if (lane < 16) {
#pragma unroll
        for (int j = 16; j < 24; j++) { float d = f[j] - mean; q += d * d; }
      }
#pragma unroll
      for (int o = 16; o; o >>= 1) q += __shfl_xor_sync(~0u, q, o);
      if (lane == 0) g_stat1[row] = ln_finish(mean, q * (1.0f / DM));
    }
  }
  TS_END(0);
}

enum { EPI_QKV = 0, EPI_WO = 1, EPI_GLU = 2, EPI_DOWN = 3 };
template <int N> struct WG;
template <> struct WG<128> { static __device__ __forceinline__ void mma(float (&d)[64], uint64_t a, uint64_t b, int s) { wgmma_ss_n128(d, a, b, s); } };
template <> struct WG<192> { static __device__ __forceinline__ void mma(float (&d)[96], uint64_t a, uint64_t b, int s) { wgmma_ss_n192(d, a, b, s); } };

template <int BM, int BN, int NB, int STAGES> struct GemmCfg {
  static constexpr int A_BYTES = BM * 128;
  static constexpr int B_BYTES = NB * (BN / 64) * 8192;
  static constexpr int STAGE_BYTES = A_BYTES + B_BYTES;
  static constexpr int SMEM = STAGES * STAGE_BYTES + 1024   + 256   + 4096  ;
};

constexpr float QSCALE = 0.22360679774997896f * 1.4426950408889634f;

template <int BM, int BN, int NB, int KDIM, int STAGES, int EPI, int MINB, int CN, int CM>
__global__ void __launch_bounds__(EPI == EPI_GLU ? 384 : 288, MINB) gemm_kernel(const __grid_constant__ CUtensorMap tmA, const __grid_constant__ CUtensorMap tmB0,
                                                         const __grid_constant__ CUtensorMap tmB1,
                                                         const __nv_bfloat16* __restrict__ resid, __nv_bfloat16* __restrict__ out) {
  using Cfg = GemmCfg<BM, BN, NB, STAGES>;
  constexpr int MB = BM / 128;
  constexpr int KT = KDIM / 64;
  extern __shared__ uint8_t smem_raw[];
  const uint32_t sbase = (smem_u32(smem_raw) + 1023u) & ~1023u;
  uint8_t* sptr = smem_raw + (sbase - smem_u32(smem_raw));
  const uint32_t sbar = sbase + STAGES * Cfg::STAGE_BYTES;
  const int tid = threadIdx.x, warp = tid >> 5, lane = tid & 31;
  const int n0 = blockIdx.x * BN, m0 = blockIdx.y * BM;
  TS_BEGIN(EPI == EPI_QKV ? 1 : EPI + 2);
  constexpr int NCL = CN + CM - 1;
  const int cx = blockIdx.x % CN, cy = blockIdx.y % CM;
  if (tid == 0) {
    for (int i = 0; i < STAGES; i++) { mbar_init(sbar + 8 * i, 1); mbar_init(sbar + 8 * (STAGES + i), 2 * NCL); }
    asm volatile("fence.mbarrier_init.release.cluster;" ::: "memory");
  }
  __syncthreads();
  if constexpr (CN * CM > 1) { cluster_arrive(); cluster_wait(); }
  pdl_launch();
  if (warp >= 8) {
    if constexpr (EPI == EPI_GLU) asm volatile("setmaxnreg.dec.sync.aligned.u32 40;");
    if (warp == 8 && lane == 0) {
      uint16_t maskA = 0, maskB = 0;
#pragma unroll
      for (int i = 0; i < CN; i++) maskA |= (uint16_t)(1u << (cy * CN + i));
#pragma unroll
      for (int j = 0; j < CM; j++) maskB |= (uint16_t)(1u << (j * CN + cx));
      auto load_a = [&](int kt, int s) {
        const uint32_t dst = sbase + s * Cfg::STAGE_BYTES + cx * (BM / CN) * 128;
        if constexpr (CN > 1) tma_2d_mc(dst, &tmA, kt * 64, m0 + cx * (BM / CN), sbar + 8 * s, maskA);
        else tma_2d(dst, &tmA, kt * 64, m0, sbar + 8 * s);
      };
      auto load_b = [&](int kt, int s) {
        const uint32_t sb = sbase + s * Cfg::STAGE_BYTES + Cfg::A_BYTES;
        constexpr int NBOX = NB * (BN / 64);
        if constexpr (CM > 1 && NBOX % CM != 0) {
#pragma unroll
          for (int j = 0; j < NBOX; j++)
            tma_2d_mc(sb + j * 8192 + cy * (64 / CM) * 128, (NB == 2 && j >= BN / 64) ? &tmB1 : &tmB0, n0 + (j % (BN / 64)) * 64, kt * 64 + cy * (64 / CM), sbar + 8 * s, maskB);
        } else {
#pragma unroll
          for (int j = 0; j < NBOX; j++) {
            const CUtensorMap* tm = (NB == 2 && j >= BN / 64) ? &tmB1 : &tmB0;
            if constexpr (CM > 1) { if (j % CM == cy) tma_2d_mc(sb + j * 8192, tm, n0 + (j % (BN / 64)) * 64, kt * 64, sbar + 8 * s, maskB); }
            else tma_2d(sb + j * 8192, tm, n0 + (j % (BN / 64)) * 64, kt * 64, sbar + 8 * s);
          }
        }
      };
      for (int s = 0; s < STAGES; s++) { mbar_expect_tx(sbar + 8 * s, Cfg::STAGE_BYTES); load_b(s, s); }
      if (EPI != EPI_QKV) pdl_wait();
      for (int s = 0; s < STAGES; s++) load_a(s, s);
      for (int kt = STAGES; kt < KT; kt++) {
        const int s = kt % STAGES;
        mbar_wait(sbar + 8 * (STAGES + s), ((kt / STAGES) - 1) & 1);
        mbar_expect_tx(sbar + 8 * s, Cfg::STAGE_BYTES);
        load_a(kt, s);
        load_b(kt, s);
      }
    }
    if constexpr (EPI == EPI_GLU) {
      if (warp > 8) {
        float2* s_st = (float2*)(sptr + STAGES * Cfg::STAGE_BYTES + 256);
        float* s_cs = (float*)(sptr + STAGES * Cfg::STAGE_BYTES + 256 + 1024);
        pdl_wait();
        for (int r = tid - 288; r < BM; r += 96) {
          const float2* pp = &g_part2[(m0 + r) * 8];
          float s = 0.f;
#pragma unroll
          for (int i = 0; i < 8; i++) s += pp[i].x;
          const float mean = s * (1.0f / DM);
          float q = 0.f;
#pragma unroll
          for (int i = 0; i < 8; i++) { const float2 p = pp[i]; const float d = p.x * (1.0f / 80.f) - mean; q += p.y + 80.f * d * d; }
          s_st[r] = ln_finish(mean, q * (1.0f / DM));
        }
        for (int c = tid - 288; c < BN; c += 96) { s_cs[c] = g_cs_g[n0 + c]; s_cs[BN + c] = g_cs_u[n0 + c]; }
        __threadfence_block();
        asm volatile("bar.arrive 2, 352;" ::: "memory");
      }
    }
    if constexpr (CN * CM > 1) { __syncwarp(); cluster_arrive(); cluster_wait(); }
    return;
  }
  if constexpr (EPI == EPI_GLU) asm volatile("setmaxnreg.inc.sync.aligned.u32 232;");
  const int wg = warp >> 2, g = lane >> 2, t = lane & 3;
  float acc[MB][NB][BN / 2];
#pragma unroll
  for (int mb = 0; mb < MB; mb++)
#pragma unroll
    for (int nb = 0; nb < NB; nb++)
#pragma unroll
      for (int i = 0; i < BN / 2; i++) acc[mb][nb][i] = 0.f;
  for (int kt = 0; kt < KT; kt++) {
    const int s = kt % STAGES;
    mbar_wait(sbar + 8 * s, (kt / STAGES) & 1);
    if (kt == 0) TS_MID(EPI == EPI_QKV ? 1 : EPI + 2, 0);
    const uint32_t sa = sbase + s * Cfg::STAGE_BYTES + wg * (MB * 64 * 128);
    const uint32_t sb = sbase + s * Cfg::STAGE_BYTES + Cfg::A_BYTES;
    wgmma_fence();
#pragma unroll
    for (int ks = 0; ks < 4; ks++) {
#pragma unroll
      for (int mb = 0; mb < MB; mb++) {
        const uint64_t da = make_desc(sa + mb * 8192 + ks * 32, 16, 1024, 1);
#pragma unroll
        for (int nb = 0; nb < NB; nb++) {
          const uint64_t db = make_desc(sb + nb * (BN / 64) * 8192 + ks * 2048, 8192, 1024, 1);
          WG<BN>::mma(acc[mb][nb], da, db, 1);
        }
      }
    }
    wgmma_commit();
    wgmma_wait<1>();
    if (kt > 0 && kt - 1 + STAGES < KT && (tid & 127) < NCL) {
      const uint32_t eb = sbar + 8 * (STAGES + (kt - 1) % STAGES);
      if constexpr (CN * CM > 1) {
        const int i = tid & 127;
        const uint32_t rank = i < CN ? cy * CN + i : ((i - CN + (i - CN >= cy ? 1 : 0)) * CN + cx);
        mbar_arrive_remote(eb, rank);
      } else mbar_arrive(eb);
    }
  }
  wgmma_wait<0>();
#pragma unroll
  for (int mb = 0; mb < MB; mb++)
#pragma unroll
    for (int nb = 0; nb < NB; nb++)
#pragma unroll
      for (int i = 0; i < BN / 2; i++) asm volatile("" : "+f"(acc[mb][nb][i]) :: "memory");
  if constexpr (CN * CM > 1) cluster_arrive();
  TS_MID(EPI == EPI_QKV ? 1 : EPI + 2, 1);
  pdl_wait();
  TS_MID(EPI == EPI_QKV ? 1 : EPI + 2, 2);
  named_bar(1, 256);
  constexpr int LDS = BN * 2 + 16;
  const int ctid = tid;

  if constexpr (EPI == EPI_QKV) {
    const int sec = n0 / DM;
#pragma unroll
    for (int mb = 0; mb < MB; mb++) {
      const int r0 = wg * (MB * 64) + mb * 64 + (warp & 3) * 16 + g;
      const float2 st0 = g_stat1[m0 + r0], st1 = g_stat1[m0 + r0 + 8];
      const float sc0 = sec == 0 ? st0.y * QSCALE : st0.y, sc1 = sec == 0 ? st1.y * QSCALE : st1.y;
#pragma unroll
      for (int j = 0; j < BN / 8; j++) {
        const float2 cs = *(const float2*)&g_cs_qkv[n0 + j * 8 + 2 * t];
        const float* a = &acc[mb][0][4 * j];
        *(uint32_t*)(sptr + r0 * LDS + j * 16 + t * 4) = pack_bf16((a[0] - st0.x * cs.x) * sc0, (a[1] - st0.x * cs.y) * sc0);
        *(uint32_t*)(sptr + (r0 + 8) * LDS + j * 16 + t * 4) = pack_bf16((a[2] - st1.x * cs.x) * sc1, (a[3] - st1.x * cs.y) * sc1);
      }
    }
    named_bar(1, 256);
    if (sec == 0) {
#pragma unroll
      for (int i = 0; i < BM * (BN / 8) / 256; i++) {
        const int idx = i * 256 + ctid, r = idx / (BN / 8), c = idx % (BN / 8);
        *(uint4*)(g_q + (size_t)(m0 + r) * DM + n0 + c * 8) = *(const uint4*)(sptr + r * LDS + c * 16);
      }
    } else {
      __nv_bfloat16* dst = sec == 1 ? g_k : g_v;
      const int cbase = n0 - sec * DM;
#pragma unroll 4
      for (int i = 0; i < BM * (BN / 4) / 256; i++) {
        const int idx = i * 256 + ctid;
        const int half = idx & 1, r8 = (idx >> 1) & 7, rest = idx >> 4;
        const int pq = rest % (BN / 8), rg = rest / (BN / 8);
        const int r = rg * 8 + r8, cq = pq * 2 + half;
        const int col = cbase + cq * 4, h = col / DH, qd = (col % DH) >> 2;
        const uint2 v = *(const uint2*)(sptr + r * LDS + cq * 8);
        const int j = m0 + r;
        uint8_t* p = (uint8_t*)dst + ((size_t)h * S_LEN * 24 + (j >> 3) * 192 + (qd >> 1) * 64 + (j & 7) * 8 + (qd & 1) * 4) * 2;
        if (qd == 4) *(uint4*)p = make_uint4(v.x, v.y, 0x00003f80u, 0u);
        else *(uint2*)p = v;
      }
      if (sec == 1) {
        __shared__ unsigned int s_kn[8];
        if (ctid < 8) s_kn[ctid] = 0u;
        named_bar(1, 256);
        const int hfirst = cbase / DH, hlast = (cbase + BN - 1) / DH;
        for (int hh = hfirst; hh <= hlast; hh++) {
          const int c_lo = max(hh * DH, cbase) - cbase, c_hi = min(hh * DH + DH, cbase + BN) - cbase;
          float mx = 0.f;
          for (int r = ctid; r < BM; r += 256) {
            float s = 0.f;
            for (int c = c_lo; c < c_hi; c += 4) {
              const uint2 v = *(const uint2*)(sptr + r * LDS + c * 2);
              s += bf_lo(v.x) * bf_lo(v.x) + bf_hi(v.x) * bf_hi(v.x) + bf_lo(v.y) * bf_lo(v.y) + bf_hi(v.y) * bf_hi(v.y);
            }
            mx = (s > mx || s != s) ? s : mx;
          }
          unsigned int mb_ = __float_as_uint(mx) & 0x7fffffffu;
          mb_ = __reduce_max_sync(~0u, mb_);
          if (lane == 0) atomicMax(&s_kn[hh - hfirst], mb_);
        }
        named_bar(1, 256);
        if (ctid <= hlast - hfirst) {
          const int hh = hfirst + ctid;
          const bool starts_here = hh * DH >= cbase, ends_here = hh * DH + DH <= cbase + BN;
          const float v = __uint_as_float(s_kn[ctid]);
          float* o = &g_kn[(blockIdx.y * NH + hh) * 2];
          if (starts_here) { o[0] = v; if (ends_here) o[1] = 0.f; }
          else o[1] = v;
        }
      }
    }
  } else if constexpr (EPI == EPI_WO || EPI == EPI_DOWN) {
    const int r0 = wg * 64 + (warp & 3) * 16 + g;
#pragma unroll
    for (int j = 0; j < BN / 8; j++) {
      const float* a = &acc[0][0][4 * j];
      *(uint32_t*)(sptr + r0 * LDS + j * 16 + t * 4) = pack_bf16(a[0], a[1]);
      *(uint32_t*)(sptr + (r0 + 8) * LDS + j * 16 + t * 4) = pack_bf16(a[2], a[3]);
    }
    named_bar(1, 256);
#pragma unroll
    for (int i = 0; i < BM * (BN / 8) / 256; i++) {
      const int idx = i * 256 + ctid, r = idx / (BN / 8), c = idx % (BN / 8);
      const uint4 a = *(const uint4*)(sptr + r * LDS + c * 16);
      const size_t go = (size_t)(m0 + r) * DM + n0 + c * 8;
      const uint4 b = *(const uint4*)(resid + go);
      uint4 o;
      o.x = pack_bf16(bf_lo(a.x) + bf_lo(b.x), bf_hi(a.x) + bf_hi(b.x));
      o.y = pack_bf16(bf_lo(a.y) + bf_lo(b.y), bf_hi(a.y) + bf_hi(b.y));
      o.z = pack_bf16(bf_lo(a.z) + bf_lo(b.z), bf_hi(a.z) + bf_hi(b.z));
      o.w = pack_bf16(bf_lo(a.w) + bf_lo(b.w), bf_hi(a.w) + bf_hi(b.w));
      *(uint4*)(out + go) = o;
      if constexpr (EPI == EPI_WO) {
        static_assert(BN == 64, "stats assume 8 lanes per row");
        const float f[8] = {bf_lo(o.x), bf_hi(o.x), bf_lo(o.y), bf_hi(o.y), bf_lo(o.z), bf_hi(o.z), bf_lo(o.w), bf_hi(o.w)};
        float s = 0.f;
#pragma unroll
        for (int k = 0; k < 8; k++) s += f[k];
        s += __shfl_xor_sync(~0u, s, 1); s += __shfl_xor_sync(~0u, s, 2); s += __shfl_xor_sync(~0u, s, 4);
        const float mu = s * (1.0f / 64.f);
        float q = 0.f;
#pragma unroll
        for (int k = 0; k < 8; k++) { const float d = f[k] - mu; q += d * d; }
        q += __shfl_xor_sync(~0u, q, 1); q += __shfl_xor_sync(~0u, q, 2); q += __shfl_xor_sync(~0u, q, 4);
        if (c == 0) g_part2[(m0 + r) * 10 + blockIdx.x] = make_float2(s, q);
      }
    }
  } else {
    const int r0 = wg * 64 + (warp & 3) * 16 + g;
    const float2* s_st = (const float2*)(sptr + STAGES * Cfg::STAGE_BYTES + 256);
    const float* s_cs = (const float*)(sptr + STAGES * Cfg::STAGE_BYTES + 256 + 1024);
    named_bar(2, 352);
    float2 st[2] = {s_st[r0], s_st[r0 + 8]};
#pragma unroll
    for (int j = 0; j < BN / 8; j++) {
      const float2 cg = *(const float2*)&s_cs[j * 8 + 2 * t], cu = *(const float2*)&s_cs[BN + j * 8 + 2 * t];
      const float* a = &acc[0][0][4 * j];
      const float* b = &acc[0][1][4 * j];
#pragma unroll
      for (int e = 0; e < 2; e++) {
        const float2 s_ = st[e];
        const uint32_t gp = pack_bf16(fmaf(-s_.x, cg.x, a[2 * e]) * s_.y, fmaf(-s_.x, cg.y, a[2 * e + 1]) * s_.y);
        const uint32_t up = pack_bf16(fmaf(-s_.x, cu.x, b[2 * e]) * s_.y, fmaf(-s_.x, cu.y, b[2 * e + 1]) * s_.y);
        uint32_t r;
        asm("{\n.reg .b32 z;\nmax.bf16x2 z, %1, %3;\nmul.rn.bf16x2 %0, z, %2;\n}" : "=r"(r) : "r"(gp), "r"(up), "r"(0u));
        *(uint32_t*)(sptr + (r0 + 8 * e) * LDS + j * 16 + t * 4) = r;
      }
    }
    named_bar(1, 256);
#pragma unroll
    for (int i = 0; i < BM * (BN / 8) / 256; i++) {
      const int idx = i * 256 + ctid, r = idx / (BN / 8), c = idx % (BN / 8);
      *(uint4*)(out + (size_t)(m0 + r) * DFF + n0 + c * 8) = *(const uint4*)(sptr + r * LDS + c * 16);
    }
  }
  if constexpr (CN * CM > 1) cluster_wait();
  TS_END(EPI == EPI_QKV ? 1 : EPI + 2);
}

constexpr int R_STAGES = 8;
constexpr int R_STAGE_BYTES = 16384 + 5 * 2048;
constexpr int R_BAR_OFF = R_STAGES * R_STAGE_BYTES;
constexpr int R_SMEM = R_BAR_OFF + 256 + 1024;
template <int KDIM, bool STATS>
__global__ void __launch_bounds__(288, 1) gemm_res_kernel(const __grid_constant__ CUtensorMap tmA, const __grid_constant__ CUtensorMap tmB,
                                                          const __nv_bfloat16* __restrict__ resid, __nv_bfloat16* __restrict__ out) {
  constexpr int KT = KDIM / 64;
  extern __shared__ uint8_t smem_raw[];
  const uint32_t sbase = (smem_u32(smem_raw) + 1023u) & ~1023u;
  uint8_t* sptr = smem_raw + (sbase - smem_u32(smem_raw));
  const uint32_t sbar = sbase + R_BAR_OFF;
  const int tid = threadIdx.x, warp = tid >> 5, lane = tid & 31;
  const int n0 = blockIdx.x * 80, m0 = blockIdx.y * 128;
  TS_BEGIN(STATS ? 3 : 5);
  if (tid == 0) {
    for (int i = 0; i < R_STAGES; i++) { mbar_init(sbar + 8 * i, 1); mbar_init(sbar + 8 * (R_STAGES + i), 2); }
    asm volatile("fence.mbarrier_init.release.cluster;" ::: "memory");
  }
  __syncthreads();
  pdl_launch();
  if (warp == 8) {
    if (lane == 0) {
      auto load_b = [&](int kt, int s) {
#pragma unroll
        for (int j = 0; j < 5; j++) tma_2d(sbase + s * R_STAGE_BYTES + 16384 + j * 2048, &tmB, n0 + j * 16, kt * 64, sbar + 8 * s);
      };
      for (int s = 0; s < R_STAGES; s++) { mbar_expect_tx(sbar + 8 * s, R_STAGE_BYTES); load_b(s, s); }
      pdl_wait();
      for (int s = 0; s < R_STAGES; s++) tma_2d(sbase + s * R_STAGE_BYTES, &tmA, s * 64, m0, sbar + 8 * s);
      for (int kt = R_STAGES; kt < KT; kt++) {
        const int s = kt % R_STAGES;
        mbar_wait(sbar + 8 * (R_STAGES + s), ((kt / R_STAGES) - 1) & 1);
        mbar_expect_tx(sbar + 8 * s, R_STAGE_BYTES);
        tma_2d(sbase + s * R_STAGE_BYTES, &tmA, kt * 64, m0, sbar + 8 * s);
        load_b(kt, s);
      }
    }
    return;
  }
  const int wg = warp >> 2, g = lane >> 2, t = lane & 3;
  pdl_wait();
  uint4 rv[5];
#pragma unroll
  for (int i = 0; i < 5; i++) {
    const int idx = i * 256 + tid, r = idx / 10, c = idx % 10;
    rv[i] = *(const uint4*)(resid + (size_t)(m0 + r) * DM + n0 + c * 8);
  }
  float acc[40];
#pragma unroll
  for (int i = 0; i < 40; i++) acc[i] = 0.f;
  for (int kt = 0; kt < KT; kt++) {
    const int s = kt % R_STAGES;
    mbar_wait(sbar + 8 * s, (kt / R_STAGES) & 1);
    if (kt == 0) TS_MID(STATS ? 3 : 5, 0);
    const uint32_t sa = sbase + s * R_STAGE_BYTES + wg * 8192;
    const uint32_t sb = sbase + s * R_STAGE_BYTES + 16384;
    wgmma_fence();
#pragma unroll
    for (int ks = 0; ks < 4; ks++)
      wgmma_ss_n80(acc, make_desc(sa + ks * 32, 16, 1024, 1), make_desc(sb + ks * 512, 2048, 256, 3), 1);
    wgmma_commit();
    wgmma_wait<1>();
    if (kt > 0 && kt - 1 + R_STAGES < KT && (tid & 127) == 0) mbar_arrive(sbar + 8 * (R_STAGES + (kt - 1) % R_STAGES));
  }
  wgmma_wait<0>();
#pragma unroll
  for (int i = 0; i < 40; i++) asm volatile("" : "+f"(acc[i]) :: "memory");
  TS_MID(STATS ? 3 : 5, 1);
  named_bar(1, 256);
  constexpr int LDS = 176;
  const int r0 = wg * 64 + (warp & 3) * 16 + g;
#pragma unroll
  for (int i = 0; i < 10; i++) {
    *(uint32_t*)(sptr + r0 * LDS + i * 16 + t * 4) = pack_bf16(acc[4 * i], acc[4 * i + 1]);
    *(uint32_t*)(sptr + (r0 + 8) * LDS + i * 16 + t * 4) = pack_bf16(acc[4 * i + 2], acc[4 * i + 3]);
  }
  named_bar(1, 256);
#pragma unroll
  for (int i = 0; i < 5; i++) {
    const int idx = i * 256 + tid, r = idx / 10, c = idx % 10;
    const uint4 a = *(const uint4*)(sptr + r * LDS + c * 16);
    const uint4 b = rv[i];
    uint4 o;
    o.x = pack_bf16(bf_lo(a.x) + bf_lo(b.x), bf_hi(a.x) + bf_hi(b.x));
    o.y = pack_bf16(bf_lo(a.y) + bf_lo(b.y), bf_hi(a.y) + bf_hi(b.y));
    o.z = pack_bf16(bf_lo(a.z) + bf_lo(b.z), bf_hi(a.z) + bf_hi(b.z));
    o.w = pack_bf16(bf_lo(a.w) + bf_lo(b.w), bf_hi(a.w) + bf_hi(b.w));
    *(uint4*)(out + (size_t)(m0 + r) * DM + n0 + c * 8) = o;
    if constexpr (STATS) *(uint4*)(sptr + r * LDS + c * 16) = o;
  }
  TS_MID(STATS ? 3 : 5, 3);
  if constexpr (STATS) {
    named_bar(1, 256);
    const int r = tid >> 1, hf = tid & 1;
    float f[40];
#pragma unroll
    for (int i = 0; i < 5; i++) {
      const uint4 v = *(const uint4*)(sptr + r * LDS + hf * 80 + i * 16);
      f[8 * i] = bf_lo(v.x); f[8 * i + 1] = bf_hi(v.x); f[8 * i + 2] = bf_lo(v.y); f[8 * i + 3] = bf_hi(v.y);
      f[8 * i + 4] = bf_lo(v.z); f[8 * i + 5] = bf_hi(v.z); f[8 * i + 6] = bf_lo(v.w); f[8 * i + 7] = bf_hi(v.w);
    }
    float s = 0.f;
#pragma unroll
    for (int i = 0; i < 40; i++) s += f[i];
    s += __shfl_xor_sync(~0u, s, 1);
    const float mu = s * (1.0f / 80.f);
    float q = 0.f;
#pragma unroll
    for (int i = 0; i < 40; i++) { const float d = f[i] - mu; q += d * d; }
    q += __shfl_xor_sync(~0u, q, 1);
    if (hf == 0) g_part2[(m0 + r) * 8 + blockIdx.x] = make_float2(s, q);
  }
  TS_END(STATS ? 3 : 5);
}

#define POLY_NUM 5
__device__ __forceinline__ float ex2_poly(float x, int shl23) {
  const float MAGIC = 12582912.f;
  const float tt = x + MAGIC;
  const float f = x - (tt - MAGIC);
  float p = fmaf(0.0013276472454890609f, f, 0.009675540961325169f);
  p = fmaf(p, f, 0.05550713092088699f);
  p = fmaf(p, f, 0.24022120237350464f);
  p = fmaf(p, f, 0.6931469440460205f);
  p = fmaf(p, f, 1.0000001192092896f);
  return __int_as_float(__float_as_int(tt) * shl23 + __float_as_int(p));
}
constexpr int KV_BYTES = S_LEN * 48;
constexpr int ATT_SMEM = 2 * KV_BYTES + 256;

__global__ void __launch_bounds__(512, 1) attn_kernel(int shl23) {
  extern __shared__ __align__(1024) uint8_t smem[];
  const int h = blockIdx.x >> 2, qb = blockIdx.x & 3;
  const uint32_t sK = smem_u32(smem), sV = sK + KV_BYTES, sBar = sV + KV_BYTES;
  const int tid = threadIdx.x;
  TS_BEGIN(2);
  if (tid == 0) {
    for (int i = 0; i < 8; i++) mbar_init(sBar + 8 * i, 1);
    asm volatile("fence.mbarrier_init.release.cluster;" ::: "memory");
  }
  pdl_launch();
  pdl_wait();
  if (tid == 0) {
    const uint8_t* gk = (const uint8_t*)(g_k + (size_t)h * S_LEN * 24);
    const uint8_t* gv = (const uint8_t*)(g_v + (size_t)h * S_LEN * 24);
    for (int i = 0; i < 8; i++) {
      mbar_expect_tx(sBar + 8 * i, 2 * 12288);
      bulk_g2s(sK + i * 12288, gk + i * 12288, 12288, sBar + 8 * i);
      bulk_g2s(sV + i * 12288, gv + i * 12288, 12288, sBar + 8 * i);
    }
  }
  __syncthreads();
  const int wg = tid >> 7, warp = (tid >> 5) & 3, lane = tid & 31, g = lane >> 2, t = lane & 3;
  float ka = 0.f, kb = 0.f;
#pragma unroll
  for (int i = 0; i < 8; i++) {
    const float2 v = *(const float2*)&g_kn[(i * NH + h) * 2];
    ka = (v.x > ka || v.x != v.x) ? v.x : ka;
    kb = (v.y > kb || v.y != v.y) ? v.y : kb;
  }
  const float kn = sqrtf(ka + kb);
  for (int it = 0; it < 2; it++) {
    const int q0 = qb * 512 + (it * 4 + wg) * 64 + warp * 16;
    uint32_t qa[4], qc[4];
    const uint32_t* qr0 = (const uint32_t*)(g_q + (size_t)(q0 + g) * DM + h * DH);
    const uint32_t* qr1 = (const uint32_t*)(g_q + (size_t)(q0 + g + 8) * DM + h * DH);
    qa[0] = qr0[t]; qa[1] = qr1[t]; qa[2] = qr0[t + 4]; qa[3] = qr1[t + 4];
    qc[0] = (t < 2) ? qr0[t + 8] : 0u; qc[1] = (t < 2) ? qr1[t + 8] : 0u; qc[2] = 0; qc[3] = 0;
    auto sq = [](uint32_t u) { const float a = bf_lo(u), b = bf_hi(u); return a * a + b * b; };
    float n0 = sq(qa[0]) + sq(qa[2]) + sq(qc[0]);
    float n1 = sq(qa[1]) + sq(qa[3]) + sq(qc[1]);
    n0 += __shfl_xor_sync(~0u, n0, 1); n0 += __shfl_xor_sync(~0u, n0, 2);
    n1 += __shfl_xor_sync(~0u, n1, 1); n1 += __shfl_xor_sync(~0u, n1, 2);
    const float m0 = ceilf(sqrtf(n0) * kn * 1.001f) + 1.f, m1 = ceilf(sqrtf(n1) * kn * 1.001f) + 1.f;
    const bool unsafe = !(m0 <= 62.f && m1 <= 62.f);
    uint32_t any_unsafe;
    asm volatile("{\n.reg .pred p, q;\nsetp.ne.u32 p, %1, 0;\nbarrier.cta.red.or.pred q, %2, 128, p;\nselp.u32 %0, 1, 0, q;\n}"
                 : "=r"(any_unsafe) : "r"((uint32_t)unsafe), "r"(1 + wg) : "memory");
    float O[12];
    float S[32];
    if (!__any_sync(~0u, any_unsafe)) {
      if (t == 2) { qc[0] = pack_bf16(-m0, 0.f); qc[1] = pack_bf16(-m1, 0.f); }
      for (int j = 0; j < 32; j++) {
        if (it == 0 && (j & 3) == 0) mbar_wait(sBar + 8 * (j >> 2), 0);
        const uint64_t dk = make_desc(sK + j * 8 * 384, 128, 384, 0);
        wgmma_fence();
        wgmma_rs_n64(S, qa[0], qa[1], qa[2], qa[3], dk, 0);
        wgmma_rs_n64(S, qc[0], qc[1], qc[2], qc[3], dk + (256 >> 4), 1);
        wgmma_commit();
        wgmma_wait<0>();
        uint32_t P[16];
#pragma unroll
        for (int i = 0; i < 16; i++) {
          const bool usepoly = ((i + 1) * POLY_NUM / 16) != (i * POLY_NUM / 16);
          float a, b;
          if (usepoly) { a = ex2_poly(S[2 * i], shl23); b = ex2_poly(S[2 * i + 1], shl23); }
          else { a = ex2_mufu(S[2 * i]); b = ex2_mufu(S[2 * i + 1]); }
          P[i] = pack_bf16(a, b);
        }
        wgmma_fence();
        const uint64_t dv = make_desc(sV + j * 8 * 384, 384, 128, 0);
#pragma unroll
        for (int ks = 0; ks < 4; ks++)
          wgmma_rs_n24_tb(O, P[4 * ks], P[4 * ks + 1], P[4 * ks + 2], P[4 * ks + 3], dv + ((ks * 768) >> 4), (j | ks) != 0);
        wgmma_commit();
      }
    } else {
      float mx0 = -INFINITY, mx1 = -INFINITY;
      for (int j = 0; j < 32; j++) {
        if (it == 0 && (j & 3) == 0) mbar_wait(sBar + 8 * (j >> 2), 0);
        const uint64_t dk = make_desc(sK + j * 8 * 384, 128, 384, 0);
        wgmma_fence();
        wgmma_rs_n64(S, qa[0], qa[1], qa[2], qa[3], dk, 0);
        wgmma_rs_n64(S, qc[0], qc[1], qc[2], qc[3], dk + (256 >> 4), 1);
        wgmma_commit();
        wgmma_wait<0>();
#pragma unroll
        for (int i = 0; i < 8; i++) {
          mx0 = fmaxf(mx0, fmaxf(S[4 * i], S[4 * i + 1]));
          mx1 = fmaxf(mx1, fmaxf(S[4 * i + 2], S[4 * i + 3]));
        }
      }
      mx0 = fmaxf(mx0, __shfl_xor_sync(~0u, mx0, 1)); mx0 = fmaxf(mx0, __shfl_xor_sync(~0u, mx0, 2));
      mx1 = fmaxf(mx1, __shfl_xor_sync(~0u, mx1, 1)); mx1 = fmaxf(mx1, __shfl_xor_sync(~0u, mx1, 2));
      for (int j = 0; j < 32; j++) {
        const uint64_t dk = make_desc(sK + j * 8 * 384, 128, 384, 0);
        wgmma_fence();
        wgmma_rs_n64(S, qa[0], qa[1], qa[2], qa[3], dk, 0);
        wgmma_rs_n64(S, qc[0], qc[1], qc[2], qc[3], dk + (256 >> 4), 1);
        wgmma_commit();
        wgmma_wait<0>();
        uint32_t P[16];
#pragma unroll
        for (int i = 0; i < 8; i++) {
          P[2 * i] = pack_bf16(ex2_mufu(S[4 * i] - mx0), ex2_mufu(S[4 * i + 1] - mx0));
          P[2 * i + 1] = pack_bf16(ex2_mufu(S[4 * i + 2] - mx1), ex2_mufu(S[4 * i + 3] - mx1));
        }
        wgmma_fence();
        const uint64_t dv = make_desc(sV + j * 8 * 384, 384, 128, 0);
#pragma unroll
        for (int ks = 0; ks < 4; ks++)
          wgmma_rs_n24_tb(O, P[4 * ks], P[4 * ks + 1], P[4 * ks + 2], P[4 * ks + 3], dv + ((ks * 768) >> 4), (j | ks) != 0);
        wgmma_commit();
      }
    }
    wgmma_wait<0>();
#pragma unroll
    for (int i = 0; i < 12; i++) asm volatile("" : "+f"(O[i]) :: "memory");
    const float l0 = __shfl_sync(~0u, O[8], (lane & ~3) | 2), l1 = __shfl_sync(~0u, O[10], (lane & ~3) | 2);
    const float r0 = 1.f / l0, r1 = 1.f / l1;
    uint32_t* o0 = (uint32_t*)(g_o + (size_t)(q0 + g) * DM + h * DH);
    uint32_t* o1 = (uint32_t*)(g_o + (size_t)(q0 + g + 8) * DM + h * DH);
    o0[t] = pack_bf16(O[0] * r0, O[1] * r0); o1[t] = pack_bf16(O[2] * r1, O[3] * r1);
    o0[t + 4] = pack_bf16(O[4] * r0, O[5] * r0); o1[t + 4] = pack_bf16(O[6] * r1, O[7] * r1);
    if (t < 2) { o0[t + 8] = pack_bf16(O[8] * r0, O[9] * r0); o1[t + 8] = pack_bf16(O[10] * r1, O[11] * r1); }
  }
  TS_END(2);
}

typedef CUresult (*EncodeFn)(CUtensorMap*, CUtensorMapDataType, cuuint32_t, void*, const cuuint64_t*, const cuuint64_t*, const cuuint32_t*,
                             const cuuint32_t*, CUtensorMapInterleave, CUtensorMapSwizzle, CUtensorMapL2promotion, CUtensorMapFloatOOBfill);
static EncodeFn get_encode() {
  static EncodeFn fn = nullptr;
  if (!fn) {
    void* p = nullptr; cudaDriverEntryPointQueryResult st;
    cudaGetDriverEntryPoint("cuTensorMapEncodeTiled", &p, cudaEnableDefault, &st);
    fn = (EncodeFn)p;
  }
  return fn;
}
static CUtensorMap make_map(const void* ptr, int rows, int cols, int box_rows, int box_cols = 64) {
  CUtensorMap m;
  cuuint64_t dims[2] = {(cuuint64_t)cols, (cuuint64_t)rows};
  cuuint64_t strides[1] = {(cuuint64_t)cols * 2};
  cuuint32_t box[2] = {(cuuint32_t)box_cols, (cuuint32_t)box_rows};
  cuuint32_t es[2] = {1, 1};
  get_encode()(&m, CU_TENSOR_MAP_DATA_TYPE_BFLOAT16, 2, const_cast<void*>(ptr), dims, strides, box, es, CU_TENSOR_MAP_INTERLEAVE_NONE,
               box_cols == 64 ? CU_TENSOR_MAP_SWIZZLE_128B : (box_cols == 32 ? CU_TENSOR_MAP_SWIZZLE_64B : CU_TENSOR_MAP_SWIZZLE_32B), CU_TENSOR_MAP_L2_PROMOTION_L2_128B, CU_TENSOR_MAP_FLOAT_OOB_FILL_NONE);
  return m;
}
template <typename... KArgs, typename... Args>
static void launch(void (*kern)(KArgs...), dim3 grid, dim3 block, size_t smem, bool pdl, dim3 cluster, Args... args) {
  cudaLaunchConfig_t cfg = {};
  cfg.gridDim = grid; cfg.blockDim = block; cfg.dynamicSmemBytes = smem; cfg.stream = cudaStreamPerThread;
  cudaLaunchAttribute at[2];
  int na = 0;
  if (pdl) { at[na].id = cudaLaunchAttributeProgrammaticStreamSerialization; at[na].val.programmaticStreamSerializationAllowed = 1; na++; }
  if (cluster.x * cluster.y > 1) { at[na].id = cudaLaunchAttributeClusterDimension; at[na].val.clusterDim.x = cluster.x; at[na].val.clusterDim.y = cluster.y; at[na].val.clusterDim.z = 1; na++; }
  cfg.attrs = at; cfg.numAttrs = na;
  cudaLaunchKernelEx(&cfg, kern, KArgs(args)...);
}

extern "C" void kernel_launch(void* const* d_in, const int* in_sizes, int n_in, void* d_out, int out_size) {
  const __nv_bfloat16* x = (const __nv_bfloat16*)d_in[0];
  const __nv_bfloat16* wqkv = (const __nv_bfloat16*)d_in[1];
  const __nv_bfloat16* wo = (const __nv_bfloat16*)d_in[2];
  const __nv_bfloat16* wgate = (const __nv_bfloat16*)d_in[4];
  const __nv_bfloat16* wup = (const __nv_bfloat16*)d_in[5];
  const __nv_bfloat16* wdown = (const __nv_bfloat16*)d_in[6];
  __nv_bfloat16* out = (__nv_bfloat16*)d_out;
  void *p_o, *p_h, *p_act;
  cudaGetSymbolAddress(&p_o, g_o); cudaGetSymbolAddress(&p_h, g_h); cudaGetSymbolAddress(&p_act, g_act);

#define A_CN 1
#define A_CM 1
#define D_CN 1
#define D_CM 1
  auto kA = gemm_kernel<256, 128, 1, DM, 4, EPI_QKV, 1, A_CN, A_CM>;
  auto kC = gemm_res_kernel<DM, true>;
  auto kD = gemm_kernel<128, 192, 2, DM, 3, EPI_GLU, 1, D_CN, D_CM>;
  auto kE = gemm_res_kernel<DFF, false>;
  constexpr int smA = GemmCfg<256, 128, 1, 4>::SMEM, smC = R_SMEM, smD = GemmCfg<128, 192, 2, 3>::SMEM;
  cudaFuncSetAttribute(kA, cudaFuncAttributeMaxDynamicSharedMemorySize, smA);
  cudaFuncSetAttribute(kC, cudaFuncAttributeMaxDynamicSharedMemorySize, smC);
  cudaFuncSetAttribute(kD, cudaFuncAttributeMaxDynamicSharedMemorySize, smD);
  cudaFuncSetAttribute(kE, cudaFuncAttributeMaxDynamicSharedMemorySize, smC);
  cudaFuncSetAttribute(attn_kernel, cudaFuncAttributeMaxDynamicSharedMemorySize, ATT_SMEM);

  const CUtensorMap tm_x = make_map(x, S_LEN, DM, 256 / A_CN), tm_wqkv = make_map(wqkv, DM, 3 * DM, 2 % A_CM ? 64 / A_CM : 64);
  const CUtensorMap tm_o = make_map(p_o, S_LEN, DM, 128), tm_wo = make_map(wo, DM, DM, 64, 16);
  const CUtensorMap tm_h = make_map(p_h, S_LEN, DM, 128 / D_CN), tm_wg = make_map(wgate, DM, DFF, 6 % D_CM ? 64 / D_CM : 64), tm_wu = make_map(wup, DM, DFF, 6 % D_CM ? 64 / D_CM : 64);
  const CUtensorMap tm_act = make_map(p_act, S_LEN, DFF, 128), tm_wd = make_map(wdown, DFF, DM, 64, 16);

  launch(pre_kernel, dim3(PRE_COL_BLOCKS + PRE_ROW_BLOCKS), dim3(256), 0, false, dim3(1, 1), x, wqkv, wgate, wup);
  launch(kA, dim3(15, 8), dim3(288), smA, true, dim3(A_CN, A_CM), tm_x, tm_wqkv, tm_wqkv, (const __nv_bfloat16*)nullptr, (__nv_bfloat16*)nullptr);
  launch(attn_kernel, dim3(128), dim3(512), ATT_SMEM, true, dim3(1, 1), 0x800000);
  launch(kC, dim3(8, 16), dim3(288), smC, true, dim3(1, 1), tm_o, tm_wo, x, (__nv_bfloat16*)p_h);
  launch(kD, dim3(8, 16), dim3(384), smD, true, dim3(D_CN, D_CM), tm_h, tm_wg, tm_wu, (const __nv_bfloat16*)nullptr, (__nv_bfloat16*)p_act);
  launch(kE, dim3(8, 16), dim3(288), smC, true, dim3(1, 1), tm_act, tm_wd, (const __nv_bfloat16*)p_h, out);
}
```

```cpp
#include <cuda_runtime.h>
#include <cuda_bf16.h>
#include <cuda.h>
#include <stdint.h>

constexpr int S_LEN = 2048, DM = 640, NH = 32, DH = 20, DFF = 1536;

__device__ __align__(1024) __nv_bfloat16 g_q[S_LEN * DM];
__device__ __align__(1024) __nv_bfloat16 g_k[NH * S_LEN * 24];
__device__ __align__(1024) __nv_bfloat16 g_v[NH * S_LEN * 24];
__device__ __align__(1024) __nv_bfloat16 g_o[S_LEN * DM];
__device__ __align__(1024) __nv_bfloat16 g_h[S_LEN * DM];
__device__ __align__(1024) __nv_bfloat16 g_act[S_LEN * DFF];
__device__ float g_kn[8 * NH * 2];
__device__ float2 g_stat1[S_LEN];
__device__ float g_cs_qkv[3 * DM];
__device__ float g_cs_g[DFF];
__device__ float g_cs_u[DFF];
__device__ float2 g_part2[S_LEN * 10];

#define TS_BEGIN(k)
#define TS_END(k)
#define TS_MID(k, i)
__device__ __forceinline__ uint32_t smem_u32(const void* p) { return (uint32_t)__cvta_generic_to_shared(p); }
__device__ __forceinline__ void mbar_init(uint32_t bar, uint32_t cnt) { asm volatile("mbarrier.init.shared::cta.b64 [%0], %1;" :: "r"(bar), "r"(cnt)); }
__device__ __forceinline__ void mbar_expect_tx(uint32_t bar, uint32_t bytes) { asm volatile("mbarrier.arrive.expect_tx.shared::cta.b64 _, [%0], %1;" :: "r"(bar), "r"(bytes) : "memory"); }
__device__ __forceinline__ void mbar_arrive(uint32_t bar) { asm volatile("mbarrier.arrive.shared::cta.b64 _, [%0];" :: "r"(bar) : "memory"); }
__device__ __forceinline__ void mbar_wait(uint32_t bar, uint32_t parity) {
  uint32_t done;
  uint32_t spins = 0;
  do {
    asm volatile("{\n.reg .pred P1;\nmbarrier.try_wait.parity.shared::cta.b64 P1, [%1], %2;\nselp.u32 %0, 1, 0, P1;\n}" : "=r"(done) : "r"(bar), "r"(parity) : "memory");
  } while (!done && ++spins < (1u << 24));
}
__device__ __forceinline__ void bulk_g2s(uint32_t dst, const void* src, uint32_t bytes, uint32_t bar) {
  asm volatile("cp.async.bulk.shared::cluster.global.mbarrier::complete_tx::bytes [%0], [%1], %2, [%3];" :: "r"(dst), "l"(src), "r"(bytes), "r"(bar) : "memory");
}
__device__ __forceinline__ void tma_2d(uint32_t dst, const CUtensorMap* tm, int c0, int c1, uint32_t bar) {
  asm volatile("cp.async.bulk.tensor.2d.shared::cluster.global.mbarrier::complete_tx::bytes [%0], [%1, {%3, %4}], [%2];"
               :: "r"(dst), "l"(tm), "r"(bar), "r"(c0), "r"(c1) : "memory");
}
__device__ __forceinline__ void tma_2d_mc(uint32_t dst, const CUtensorMap* tm, int c0, int c1, uint32_t bar, uint16_t mask) {
  asm volatile("cp.async.bulk.tensor.2d.shared::cluster.global.mbarrier::complete_tx::bytes.multicast::cluster [%0], [%1, {%3, %4}], [%2], %5;"
               :: "r"(dst), "l"(tm), "r"(bar), "r"(c0), "r"(c1), "h"(mask) : "memory");
}
__device__ __forceinline__ void mbar_arrive_remote(uint32_t bar, uint32_t rank) {
  asm volatile("{\n.reg .b32 ra;\nmapa.shared::cluster.u32 ra, %0, %1;\nmbarrier.arrive.release.cluster.shared::cluster.b64 _, [ra];\n}" :: "r"(bar), "r"(rank) : "memory");
}
__device__ __forceinline__ void cluster_arrive() { asm volatile("barrier.cluster.arrive.release.aligned;" ::: "memory"); }
__device__ __forceinline__ void cluster_wait() { asm volatile("barrier.cluster.wait.acquire.aligned;" ::: "memory"); }
__device__ __forceinline__ void wgmma_fence() { asm volatile("wgmma.fence.sync.aligned;" ::: "memory"); }
__device__ __forceinline__ void wgmma_commit() { asm volatile("wgmma.commit_group.sync.aligned;" ::: "memory"); }
template <int N> __device__ __forceinline__ void wgmma_wait() { asm volatile("wgmma.wait_group.sync.aligned %0;" :: "n"(N) : "memory"); }
__device__ __forceinline__ void pdl_wait() { asm volatile("griddepcontrol.wait;" ::: "memory"); }
__device__ __forceinline__ void pdl_launch() { asm volatile("griddepcontrol.launch_dependents;" ::: "memory"); }
__device__ __forceinline__ void named_bar(int id, int n) { asm volatile("bar.sync %0, %1;" :: "r"(id), "r"(n) : "memory"); }
__device__ __forceinline__ uint64_t make_desc(uint32_t addr, uint32_t lbo, uint32_t sbo, uint32_t swz) {
  return (uint64_t)((addr & 0x3FFFF) >> 4) | ((uint64_t)(lbo >> 4) << 16) | ((uint64_t)(sbo >> 4) << 32) | ((uint64_t)swz << 62);
}
__device__ __forceinline__ uint32_t pack_bf16(float lo, float hi) { uint32_t r; asm("cvt.rn.bf16x2.f32 %0, %1, %2;" : "=r"(r) : "f"(hi), "f"(lo)); return r; }
__device__ __forceinline__ float bf_lo(uint32_t u) { return __uint_as_float(u << 16); }
__device__ __forceinline__ float bf_hi(uint32_t u) { return __uint_as_float(u & 0xffff0000u); }
__device__ __forceinline__ float bf_round(float x) { return __bfloat162float(__float2bfloat16_rn(x)); }
__device__ __forceinline__ float ex2_mufu(float x) { float y; asm("ex2.approx.ftz.f32 %0, %1;" : "=f"(y) : "f"(x)); return y; }

__device__ __forceinline__ void wgmma_ss_n80(float (&d)[40], uint64_t da, uint64_t db, int scale_d) {
  asm volatile("{\n.reg .pred p;\nsetp.ne.b32 p, %42, 0;\n"
    "wgmma.mma_async.sync.aligned.m64n80k16.f32.bf16.bf16 {%0,%1,%2,%3,%4,%5,%6,%7,%8,%9,%10,%11,%12,%13,%14,%15,%16,%17,%18,%19,%20,%21,%22,%23,%24,%25,%26,%27,%28,%29,%30,%31,%32,%33,%34,%35,%36,%37,%38,%39}, %40, %41, p, 1, 1, 0, 1;\n}\n"
    : "+f"(d[0]),"+f"(d[1]),"+f"(d[2]),"+f"(d[3]),"+f"(d[4]),"+f"(d[5]),"+f"(d[6]),"+f"(d[7]),"+f"(d[8]),"+f"(d[9]),"+f"(d[10]),"+f"(d[11]),"+f"(d[12]),"+f"(d[13]),"+f"(d[14]),"+f"(d[15]),"+f"(d[16]),"+f"(d[17]),"+f"(d[18]),"+f"(d[19]),"+f"(d[20]),"+f"(d[21]),"+f"(d[22]),"+f"(d[23]),"+f"(d[24]),"+f"(d[25]),"+f"(d[26]),"+f"(d[27]),"+f"(d[28]),"+f"(d[29]),"+f"(d[30]),"+f"(d[31]),"+f"(d[32]),"+f"(d[33]),"+f"(d[34]),"+f"(d[35]),"+f"(d[36]),"+f"(d[37]),"+f"(d[38]),"+f"(d[39])
    : "l"(da), "l"(db), "r"(scale_d));
}
__device__ __forceinline__ void wgmma_ss_n128(float (&d)[64], uint64_t da, uint64_t db, int scale_d) {
  asm volatile("{\n.reg .pred p;\nsetp.ne.b32 p, %66, 0;\n"
    "wgmma.mma_async.sync.aligned.m64n128k16.f32.bf16.bf16 {%0,%1,%2,%3,%4,%5,%6,%7,%8,%9,%10,%11,%12,%13,%14,%15,%16,%17,%18,%19,%20,%21,%22,%23,%24,%25,%26,%27,%28,%29,%30,%31,%32,%33,%34,%35,%36,%37,%38,%39,%40,%41,%42,%43,%44,%45,%46,%47,%48,%49,%50,%51,%52,%53,%54,%55,%56,%57,%58,%59,%60,%61,%62,%63}, %64, %65, p, 1, 1, 0, 1;\n}\n"
    : "+f"(d[0]),"+f"(d[1]),"+f"(d[2]),"+f"(d[3]),"+f"(d[4]),"+f"(d[5]),"+f"(d[6]),"+f"(d[7]),"+f"(d[8]),"+f"(d[9]),"+f"(d[10]),"+f"(d[11]),"+f"(d[12]),"+f"(d[13]),"+f"(d[14]),"+f"(d[15]),"+f"(d[16]),"+f"(d[17]),"+f"(d[18]),"+f"(d[19]),"+f"(d[20]),"+f"(d[21]),"+f"(d[22]),"+f"(d[23]),"+f"(d[24]),"+f"(d[25]),"+f"(d[26]),"+f"(d[27]),"+f"(d[28]),"+f"(d[29]),"+f"(d[30]),"+f"(d[31]),"+f"(d[32]),"+f"(d[33]),"+f"(d[34]),"+f"(d[35]),"+f"(d[36]),"+f"(d[37]),"+f"(d[38]),"+f"(d[39]),"+f"(d[40]),"+f"(d[41]),"+f"(d[42]),"+f"(d[43]),"+f"(d[44]),"+f"(d[45]),"+f"(d[46]),"+f"(d[47]),"+f"(d[48]),"+f"(d[49]),"+f"(d[50]),"+f"(d[51]),"+f"(d[52]),"+f"(d[53]),"+f"(d[54]),"+f"(d[55]),"+f"(d[56]),"+f"(d[57]),"+f"(d[58]),"+f"(d[59]),"+f"(d[60]),"+f"(d[61]),"+f"(d[62]),"+f"(d[63])
    : "l"(da), "l"(db), "r"(scale_d));
}
__device__ __forceinline__ void wgmma_ss_n192(float (&d)[96], uint64_t da, uint64_t db, int scale_d) {
  asm volatile("{\n.reg .pred p;\nsetp.ne.b32 p, %98, 0;\n"
    "wgmma.mma_async.sync.aligned.m64n192k16.f32.bf16.bf16 {%0,%1,%2,%3,%4,%5,%6,%7,%8,%9,%10,%11,%12,%13,%14,%15,%16,%17,%18,%19,%20,%21,%22,%23,%24,%25,%26,%27,%28,%29,%30,%31,%32,%33,%34,%35,%36,%37,%38,%39,%40,%41,%42,%43,%44,%45,%46,%47,%48,%49,%50,%51,%52,%53,%54,%55,%56,%57,%58,%59,%60,%61,%62,%63,%64,%65,%66,%67,%68,%69,%70,%71,%72,%73,%74,%75,%76,%77,%78,%79,%80,%81,%82,%83,%84,%85,%86,%87,%88,%89,%90,%91,%92,%93,%94,%95}, %96, %97, p, 1, 1, 0, 1;\n}\n"
    : "+f"(d[0]),"+f"(d[1]),"+f"(d[2]),"+f"(d[3]),"+f"(d[4]),"+f"(d[5]),"+f"(d[6]),"+f"(d[7]),"+f"(d[8]),"+f"(d[9]),"+f"(d[10]),"+f"(d[11]),"+f"(d[12]),"+f"(d[13]),"+f"(d[14]),"+f"(d[15]),"+f"(d[16]),"+f"(d[17]),"+f"(d[18]),"+f"(d[19]),"+f"(d[20]),"+f"(d[21]),"+f"(d[22]),"+f"(d[23]),"+f"(d[24]),"+f"(d[25]),"+f"(d[26]),"+f"(d[27]),"+f"(d[28]),"+f"(d[29]),"+f"(d[30]),"+f"(d[31]),"+f"(d[32]),"+f"(d[33]),"+f"(d[34]),"+f"(d[35]),"+f"(d[36]),"+f"(d[37]),"+f"(d[38]),"+f"(d[39]),"+f"(d[40]),"+f"(d[41]),"+f"(d[42]),"+f"(d[43]),"+f"(d[44]),"+f"(d[45]),"+f"(d[46]),"+f"(d[47]),"+f"(d[48]),"+f"(d[49]),"+f"(d[50]),"+f"(d[51]),"+f"(d[52]),"+f"(d[53]),"+f"(d[54]),"+f"(d[55]),"+f"(d[56]),"+f"(d[57]),"+f"(d[58]),"+f"(d[59]),"+f"(d[60]),"+f"(d[61]),"+f"(d[62]),"+f"(d[63]),"+f"(d[64]),"+f"(d[65]),"+f"(d[66]),"+f"(d[67]),"+f"(d[68]),"+f"(d[69]),"+f"(d[70]),"+f"(d[71]),"+f"(d[72]),"+f"(d[73]),"+f"(d[74]),"+f"(d[75]),"+f"(d[76]),"+f"(d[77]),"+f"(d[78]),"+f"(d[79]),"+f"(d[80]),"+f"(d[81]),"+f"(d[82]),"+f"(d[83]),"+f"(d[84]),"+f"(d[85]),"+f"(d[86]),"+f"(d[87]),"+f"(d[88]),"+f"(d[89]),"+f"(d[90]),"+f"(d[91]),"+f"(d[92]),"+f"(d[93]),"+f"(d[94]),"+f"(d[95])
    : "l"(da), "l"(db), "r"(scale_d));
}
__device__ __forceinline__ void wgmma_rs_n64(float (&d)[32], uint32_t a0, uint32_t a1, uint32_t a2, uint32_t a3, uint64_t db, int scale_d) {
  asm volatile("{\n.reg .pred p;\nsetp.ne.b32 p, %37, 0;\n"
    "wgmma.mma_async.sync.aligned.m64n64k16.f32.bf16.bf16 {%0,%1,%2,%3,%4,%5,%6,%7,%8,%9,%10,%11,%12,%13,%14,%15,%16,%17,%18,%19,%20,%21,%22,%23,%24,%25,%26,%27,%28,%29,%30,%31}, {%32,%33,%34,%35}, %36, p, 1, 1, 0;\n}\n"
    : "+f"(d[0]),"+f"(d[1]),"+f"(d[2]),"+f"(d[3]),"+f"(d[4]),"+f"(d[5]),"+f"(d[6]),"+f"(d[7]),"+f"(d[8]),"+f"(d[9]),"+f"(d[10]),"+f"(d[11]),"+f"(d[12]),"+f"(d[13]),"+f"(d[14]),"+f"(d[15]),"+f"(d[16]),"+f"(d[17]),"+f"(d[18]),"+f"(d[19]),"+f"(d[20]),"+f"(d[21]),"+f"(d[22]),"+f"(d[23]),"+f"(d[24]),"+f"(d[25]),"+f"(d[26]),"+f"(d[27]),"+f"(d[28]),"+f"(d[29]),"+f"(d[30]),"+f"(d[31])
    : "r"(a0), "r"(a1), "r"(a2), "r"(a3), "l"(db), "r"(scale_d));
}
__device__ __forceinline__ void wgmma_rs_n24_tb(float (&d)[12], uint32_t a0, uint32_t a1, uint32_t a2, uint32_t a3, uint64_t db, int scale_d) {
  asm volatile("{\n.reg .pred p;\nsetp.ne.b32 p, %17, 0;\n"
    "wgmma.mma_async.sync.aligned.m64n24k16.f32.bf16.bf16 {%0,%1,%2,%3,%4,%5,%6,%7,%8,%9,%10,%11}, {%12,%13,%14,%15}, %16, p, 1, 1, 1;\n}\n"
    : "+f"(d[0]),"+f"(d[1]),"+f"(d[2]),"+f"(d[3]),"+f"(d[4]),"+f"(d[5]),"+f"(d[6]),"+f"(d[7]),"+f"(d[8]),"+f"(d[9]),"+f"(d[10]),"+f"(d[11])
    : "r"(a0), "r"(a1), "r"(a2), "r"(a3), "l"(db), "r"(scale_d));
}

constexpr int PRE_ROW_BLOCKS = 64;
constexpr int PRE_COL_BLOCKS = 3 * DM / 64;
__device__ __forceinline__ float2 ln_finish(float mean, float var) {
  float mb = bf_round(mean);
  float s = bf_round(sqrtf(bf_round(bf_round(var) + 1e-5f)));
  return make_float2(mb, 1.0f / s);
}
__device__ __forceinline__ void colsum64(const __nv_bfloat16* __restrict__ w, int ld, int c0, float* __restrict__ dst, float (*red)[65], int tid, int bar_id) {
  const int cg = tid & 7, r0 = tid >> 3;
  float acc[8];
#pragma unroll
  for (int i = 0; i < 8; i++) acc[i] = 0.f;
#pragma unroll 10
  for (int r = r0; r < DM; r += 32) {
    uint4 v = __ldg((const uint4*)(w + (size_t)r * ld + c0 + cg * 8));
    acc[0] += bf_lo(v.x); acc[1] += bf_hi(v.x); acc[2] += bf_lo(v.y); acc[3] += bf_hi(v.y);
    acc[4] += bf_lo(v.z); acc[5] += bf_hi(v.z); acc[6] += bf_lo(v.w); acc[7] += bf_hi(v.w);
  }
#pragma unroll
  for (int i = 0; i < 8; i++) red[r0][cg * 8 + i] = acc[i];
  named_bar(bar_id, 256);
  if (tid < 64) {
    float s = 0.f;
#pragma unroll
    for (int r = 0; r < 32; r++) s += red[r][tid];
    dst[c0 + tid] = s;
  }
  named_bar(bar_id, 256);
}
__global__ void __launch_bounds__(256) pre_kernel(const __nv_bfloat16* __restrict__ x, const __nv_bfloat16* __restrict__ wqkv) {
  TS_BEGIN(0);
  pdl_launch();
  const int tid = threadIdx.x, lane = tid & 31, warp = tid >> 5;
  if (blockIdx.x < PRE_COL_BLOCKS) {
    __shared__ float red[32][65];
    colsum64(wqkv, 3 * DM, blockIdx.x * 64, g_cs_qkv, red, tid, 1);
  } else {
    const int rb = blockIdx.x - PRE_COL_BLOCKS;
#pragma unroll
    for (int i = 0; i < 4; i++) {
      const int row = rb * 32 + warp * 4 + i;
      const uint4* p = (const uint4*)(x + (size_t)row * DM);
      uint4 v0 = __ldg(p + lane), v1 = __ldg(p + 32 + lane), v2 = make_uint4(0, 0, 0, 0);
      if (lane < 16) v2 = __ldg(p + 64 + lane);
      float f[24];
      uint32_t u[12] = {v0.x, v0.y, v0.z, v0.w, v1.x, v1.y, v1.z, v1.w, v2.x, v2.y, v2.z, v2.w};
#pragma unroll
      for (int j = 0; j < 12; j++) { f[2 * j] = bf_lo(u[j]); f[2 * j + 1] = bf_hi(u[j]); }
      float s = 0.f;
#pragma unroll
      for (int j = 0; j < 24; j++) s += f[j];
#pragma unroll
      for (int o = 16; o; o >>= 1) s += __shfl_xor_sync(~0u, s, o);
      const float mean = s * (1.0f / DM);
      float q = 0.f;
#pragma unroll
      for (int j = 0; j < 16; j++) { float d = f[j] - mean; q += d * d; }
      if (lane < 16) {
#pragma unroll
        for (int j = 16; j < 24; j++) { float d = f[j] - mean; q += d * d; }
      }
#pragma unroll
      for (int o = 16; o; o >>= 1) q += __shfl_xor_sync(~0u, q, o);
      if (lane == 0) g_stat1[row] = ln_finish(mean, q * (1.0f / DM));
    }
  }
  TS_END(0);
}

enum { EPI_QKV = 0, EPI_WO = 1, EPI_GLU = 2, EPI_DOWN = 3 };
template <int N> struct WG;
template <> struct WG<128> { static __device__ __forceinline__ void mma(float (&d)[64], uint64_t a, uint64_t b, int s) { wgmma_ss_n128(d, a, b, s); } };
template <> struct WG<192> { static __device__ __forceinline__ void mma(float (&d)[96], uint64_t a, uint64_t b, int s) { wgmma_ss_n192(d, a, b, s); } };

template <int BM, int BN, int NB, int STAGES> struct GemmCfg {
  static constexpr int A_BYTES = BM * 128;
  static constexpr int B_BYTES = NB * (BN / 64) * 8192;
  static constexpr int STAGE_BYTES = A_BYTES + B_BYTES;
  static constexpr int SMEM = STAGES * STAGE_BYTES + 1024   + 256   + 4096  ;
};

constexpr float QSCALE = 0.22360679774997896f * 1.4426950408889634f;

template <int BM, int BN, int NB, int KDIM, int STAGES, int EPI, int MINB, int CN, int CM>
__global__ void __launch_bounds__(EPI == EPI_GLU ? 384 : 288, MINB) gemm_kernel(const __grid_constant__ CUtensorMap tmA, const __grid_constant__ CUtensorMap tmB0,
                                                         const __grid_constant__ CUtensorMap tmB1,
                                                         const __nv_bfloat16* __restrict__ resid, __nv_bfloat16* __restrict__ out) {
  using Cfg = GemmCfg<BM, BN, NB, STAGES>;
  constexpr int MB = BM / 128;
  constexpr int KT = KDIM / 64;
  extern __shared__ uint8_t smem_raw[];
  const uint32_t sbase = (smem_u32(smem_raw) + 1023u) & ~1023u;
  uint8_t* sptr = smem_raw + (sbase - smem_u32(smem_raw));
  const uint32_t sbar = sbase + STAGES * Cfg::STAGE_BYTES;
  const int tid = threadIdx.x, warp = tid >> 5, lane = tid & 31;
  const int n0 = blockIdx.x * BN, m0 = blockIdx.y * BM;
  TS_BEGIN(EPI == EPI_QKV ? 1 : EPI + 2);
  constexpr int NCL = CN + CM - 1;
  const int cx = blockIdx.x % CN, cy = blockIdx.y % CM;
  if (tid == 0) {
    for (int i = 0; i < STAGES; i++) { mbar_init(sbar + 8 * i, 1); mbar_init(sbar + 8 * (STAGES + i), 2 * NCL); }
    asm volatile("fence.mbarrier_init.release.cluster;" ::: "memory");
  }
  __syncthreads();
  if constexpr (CN * CM > 1) { cluster_arrive(); cluster_wait(); }
  pdl_launch();
  if (warp >= 8) {
    if constexpr (EPI == EPI_GLU) asm volatile("setmaxnreg.dec.sync.aligned.u32 40;");
    if (warp == 8 && lane == 0) {
      uint16_t maskA = 0, maskB = 0;
#pragma unroll
      for (int i = 0; i < CN; i++) maskA |= (uint16_t)(1u << (cy * CN + i));
#pragma unroll
      for (int j = 0; j < CM; j++) maskB |= (uint16_t)(1u << (j * CN + cx));
      auto load_a = [&](int kt, int s) {
        const uint32_t dst = sbase + s * Cfg::STAGE_BYTES + cx * (BM / CN) * 128;
        if constexpr (CN > 1) tma_2d_mc(dst, &tmA, kt * 64, m0 + cx * (BM / CN), sbar + 8 * s, maskA);
        else tma_2d(dst, &tmA, kt * 64, m0, sbar + 8 * s);
      };
      auto load_b = [&](int kt, int s) {
        const uint32_t sb = sbase + s * Cfg::STAGE_BYTES + Cfg::A_BYTES;
        constexpr int NBOX = NB * (BN / 64);
        if constexpr (CM > 1 && NBOX % CM != 0) {
#pragma unroll
          for (int j = 0; j < NBOX; j++)
            tma_2d_mc(sb + j * 8192 + cy * (64 / CM) * 128, (NB == 2 && j >= BN / 64) ? &tmB1 : &tmB0, n0 + (j % (BN / 64)) * 64, kt * 64 + cy * (64 / CM), sbar + 8 * s, maskB);
        } else {
#pragma unroll
          for (int j = 0; j < NBOX; j++) {
            const CUtensorMap* tm = (NB == 2 && j >= BN / 64) ? &tmB1 : &tmB0;
            if constexpr (CM > 1) { if (j % CM == cy) tma_2d_mc(sb + j * 8192, tm, n0 + (j % (BN / 64)) * 64, kt * 64, sbar + 8 * s, maskB); }
            else tma_2d(sb + j * 8192, tm, n0 + (j % (BN / 64)) * 64, kt * 64, sbar + 8 * s);
          }
        }
      };
      for (int s = 0; s < STAGES; s++) { mbar_expect_tx(sbar + 8 * s, Cfg::STAGE_BYTES); load_b(s, s); }
      if (EPI != EPI_QKV) pdl_wait();
      for (int s = 0; s < STAGES; s++) load_a(s, s);
      for (int kt = STAGES; kt < KT; kt++) {
        const int s = kt % STAGES;
        mbar_wait(sbar + 8 * (STAGES + s), ((kt / STAGES) - 1) & 1);
        mbar_expect_tx(sbar + 8 * s, Cfg::STAGE_BYTES);
        load_a(kt, s);
        load_b(kt, s);
      }
    }
    if constexpr (EPI == EPI_GLU) {
      if (warp > 8) {
        float2* s_st = (float2*)(sptr + STAGES * Cfg::STAGE_BYTES + 256);
        float* s_cs = (float*)(sptr + STAGES * Cfg::STAGE_BYTES + 256 + 1024);
        pdl_wait();
        for (int r = tid - 288; r < BM; r += 96) {
          const float2* pp = &g_part2[(m0 + r) * 8];
          float s = 0.f;
#pragma unroll
          for (int i = 0; i < 8; i++) s += pp[i].x;
          const float mean = s * (1.0f / DM);
          float q = 0.f;
#pragma unroll
          for (int i = 0; i < 8; i++) { const float2 p = pp[i]; const float d = p.x * (1.0f / 80.f) - mean; q += p.y + 80.f * d * d; }
          s_st[r] = ln_finish(mean, q * (1.0f / DM));
        }
        for (int c = tid - 288; c < BN; c += 96) { s_cs[c] = g_cs_g[n0 + c]; s_cs[BN + c] = g_cs_u[n0 + c]; }
        __threadfence_block();
        asm volatile("bar.arrive 2, 352;" ::: "memory");
      }
    }
    if constexpr (CN * CM > 1) { __syncwarp(); cluster_arrive(); cluster_wait(); }
    return;
  }
  if constexpr (EPI == EPI_GLU) asm volatile("setmaxnreg.inc.sync.aligned.u32 232;");
  const int wg = warp >> 2, g = lane >> 2, t = lane & 3;
  float acc[MB][NB][BN / 2];
#pragma unroll
  for (int mb = 0; mb < MB; mb++)
#pragma unroll
    for (int nb = 0; nb < NB; nb++)
#pragma unroll
      for (int i = 0; i < BN / 2; i++) acc[mb][nb][i] = 0.f;
  for (int kt = 0; kt < KT; kt++) {
    const int s = kt % STAGES;
    mbar_wait(sbar + 8 * s, (kt / STAGES) & 1);
    if (kt == 0) TS_MID(EPI == EPI_QKV ? 1 : EPI + 2, 0);
    const uint32_t sa = sbase + s * Cfg::STAGE_BYTES + wg * (MB * 64 * 128);
    const uint32_t sb = sbase + s * Cfg::STAGE_BYTES + Cfg::A_BYTES;
    wgmma_fence();
#pragma unroll
    for (int ks = 0; ks < 4; ks++) {
#pragma unroll
      for (int mb = 0; mb < MB; mb++) {
        const uint64_t da = make_desc(sa + mb * 8192 + ks * 32, 16, 1024, 1);
#pragma unroll
        for (int nb = 0; nb < NB; nb++) {
          const uint64_t db = make_desc(sb + nb * (BN / 64) * 8192 + ks * 2048, 8192, 1024, 1);
          WG<BN>::mma(acc[mb][nb], da, db, 1);
        }
      }
    }
    wgmma_commit();
    wgmma_wait<1>();
    if (kt > 0 && kt - 1 + STAGES < KT && (tid & 127) < NCL) {
      const uint32_t eb = sbar + 8 * (STAGES + (kt - 1) % STAGES);
      if constexpr (CN * CM > 1) {
        const int i = tid & 127;
        const uint32_t rank = i < CN ? cy * CN + i : ((i - CN + (i - CN >= cy ? 1 : 0)) * CN + cx);
        mbar_arrive_remote(eb, rank);
      } else mbar_arrive(eb);
    }
  }
  wgmma_wait<0>();
#pragma unroll
  for (int mb = 0; mb < MB; mb++)
#pragma unroll
    for (int nb = 0; nb < NB; nb++)
#pragma unroll
      for (int i = 0; i < BN / 2; i++) asm volatile("" : "+f"(acc[mb][nb][i]) :: "memory");
  if constexpr (CN * CM > 1) cluster_arrive();
  TS_MID(EPI == EPI_QKV ? 1 : EPI + 2, 1);
  pdl_wait();
  TS_MID(EPI == EPI_QKV ? 1 : EPI + 2, 2);
  named_bar(1, 256);
  constexpr int LDS = BN * 2 + 16;
  const int ctid = tid;

  if constexpr (EPI == EPI_QKV) {
    const int sec = n0 / DM;
#pragma unroll
    for (int mb = 0; mb < MB; mb++) {
      const int r0 = wg * (MB * 64) + mb * 64 + (warp & 3) * 16 + g;
      const float2 st0 = g_stat1[m0 + r0], st1 = g_stat1[m0 + r0 + 8];
      const float sc0 = sec == 0 ? st0.y * QSCALE : st0.y, sc1 = sec == 0 ? st1.y * QSCALE : st1.y;
#pragma unroll
      for (int j = 0; j < BN / 8; j++) {
        const float2 cs = *(const float2*)&g_cs_qkv[n0 + j * 8 + 2 * t];
        const float* a = &acc[mb][0][4 * j];
        *(uint32_t*)(sptr + r0 * LDS + j * 16 + t * 4) = pack_bf16((a[0] - st0.x * cs.x) * sc0, (a[1] - st0.x * cs.y) * sc0);
        *(uint32_t*)(sptr + (r0 + 8) * LDS + j * 16 + t * 4) = pack_bf16((a[2] - st1.x * cs.x) * sc1, (a[3] - st1.x * cs.y) * sc1);
      }
    }
    named_bar(1, 256);
    if (sec == 0) {
#pragma unroll
      for (int i = 0; i < BM * (BN / 8) / 256; i++) {
        const int idx = i * 256 + ctid, r = idx / (BN / 8), c = idx % (BN / 8);
        *(uint4*)(g_q + (size_t)(m0 + r) * DM + n0 + c * 8) = *(const uint4*)(sptr + r * LDS + c * 16);
      }
    } else {
      __nv_bfloat16* dst = sec == 1 ? g_k : g_v;
      const int cbase = n0 - sec * DM;
#pragma unroll 4
      for (int i = 0; i < BM * (BN / 4) / 256; i++) {
        const int idx = i * 256 + ctid;
        const int half = idx & 1, r8 = (idx >> 1) & 7, rest = idx >> 4;
        const int pq = rest % (BN / 8), rg = rest / (BN / 8);
        const int r = rg * 8 + r8, cq = pq * 2 + half;
        const int col = cbase + cq * 4, h = col / DH, qd = (col % DH) >> 2;
        const uint2 v = *(const uint2*)(sptr + r * LDS + cq * 8);
        const int j = m0 + r;
        uint8_t* p = (uint8_t*)dst + ((size_t)h * S_LEN * 24 + (j >> 3) * 192 + (qd >> 1) * 64 + (j & 7) * 8 + (qd & 1) * 4) * 2;
        if (qd == 4) *(uint4*)p = make_uint4(v.x, v.y, 0x00003f80u, 0u);
        else *(uint2*)p = v;
      }
      if (sec == 1) {
        __shared__ unsigned int s_kn[8];
        if (ctid < 8) s_kn[ctid] = 0u;
        named_bar(1, 256);
        const int hfirst = cbase / DH, hlast = (cbase + BN - 1) / DH;
        for (int hh = hfirst; hh <= hlast; hh++) {
          const int c_lo = max(hh * DH, cbase) - cbase, c_hi = min(hh * DH + DH, cbase + BN) - cbase;
          float mx = 0.f;
          for (int r = ctid; r < BM; r += 256) {
            float s = 0.f;
            for (int c = c_lo; c < c_hi; c += 4) {
              const uint2 v = *(const uint2*)(sptr + r * LDS + c * 2);
              s += bf_lo(v.x) * bf_lo(v.x) + bf_hi(v.x) * bf_hi(v.x) + bf_lo(v.y) * bf_lo(v.y) + bf_hi(v.y) * bf_hi(v.y);
            }
            mx = (s > mx || s != s) ? s : mx;
          }
          unsigned int mb_ = __float_as_uint(mx) & 0x7fffffffu;
          mb_ = __reduce_max_sync(~0u, mb_);
          if (lane == 0) atomicMax(&s_kn[hh - hfirst], mb_);
        }
        named_bar(1, 256);
        if (ctid <= hlast - hfirst) {
          const int hh = hfirst + ctid;
          const bool starts_here = hh * DH >= cbase, ends_here = hh * DH + DH <= cbase + BN;
          const float v = __uint_as_float(s_kn[ctid]);
          float* o = &g_kn[(blockIdx.y * NH + hh) * 2];
          if (starts_here) { o[0] = v; if (ends_here) o[1] = 0.f; }
          else o[1] = v;
        }
      }
    }
  } else if constexpr (EPI == EPI_WO || EPI == EPI_DOWN) {
    const int r0 = wg * 64 + (warp & 3) * 16 + g;
#pragma unroll
    for (int j = 0; j < BN / 8; j++) {
      const float* a = &acc[0][0][4 * j];
      *(uint32_t*)(sptr + r0 * LDS + j * 16 + t * 4) = pack_bf16(a[0], a[1]);
      *(uint32_t*)(sptr + (r0 + 8) * LDS + j * 16 + t * 4) = pack_bf16(a[2], a[3]);
    }
    named_bar(1, 256);
#pragma unroll
    for (int i = 0; i < BM * (BN / 8) / 256; i++) {
      const int idx = i * 256 + ctid, r = idx / (BN / 8), c = idx % (BN / 8);
      const uint4 a = *(const uint4*)(sptr + r * LDS + c * 16);
      const size_t go = (size_t)(m0 + r) * DM + n0 + c * 8;
      const uint4 b = *(const uint4*)(resid + go);
      uint4 o;
      o.x = pack_bf16(bf_lo(a.x) + bf_lo(b.x), bf_hi(a.x) + bf_hi(b.x));
      o.y = pack_bf16(bf_lo(a.y) + bf_lo(b.y), bf_hi(a.y) + bf_hi(b.y));
      o.z = pack_bf16(bf_lo(a.z) + bf_lo(b.z), bf_hi(a.z) + bf_hi(b.z));
      o.w = pack_bf16(bf_lo(a.w) + bf_lo(b.w), bf_hi(a.w) + bf_hi(b.w));
      *(uint4*)(out + go) = o;
      if constexpr (EPI == EPI_WO) {
        static_assert(BN == 64, "stats assume 8 lanes per row");
        const float f[8] = {bf_lo(o.x), bf_hi(o.x), bf_lo(o.y), bf_hi(o.y), bf_lo(o.z), bf_hi(o.z), bf_lo(o.w), bf_hi(o.w)};
        float s = 0.f;
#pragma unroll
        for (int k = 0; k < 8; k++) s += f[k];
        s += __shfl_xor_sync(~0u, s, 1); s += __shfl_xor_sync(~0u, s, 2); s += __shfl_xor_sync(~0u, s, 4);
        const float mu = s * (1.0f / 64.f);
        float q = 0.f;
#pragma unroll
        for (int k = 0; k < 8; k++) { const float d = f[k] - mu; q += d * d; }
        q += __shfl_xor_sync(~0u, q, 1); q += __shfl_xor_sync(~0u, q, 2); q += __shfl_xor_sync(~0u, q, 4);
        if (c == 0) g_part2[(m0 + r) * 10 + blockIdx.x] = make_float2(s, q);
      }
    }
  } else {
    const int r0 = wg * 64 + (warp & 3) * 16 + g;
    const float2* s_st = (const float2*)(sptr + STAGES * Cfg::STAGE_BYTES + 256);
    const float* s_cs = (const float*)(sptr + STAGES * Cfg::STAGE_BYTES + 256 + 1024);
    named_bar(2, 352);
    float2 st[2] = {s_st[r0], s_st[r0 + 8]};
#pragma unroll
    for (int j = 0; j < BN / 8; j++) {
      const float2 cg = *(const float2*)&s_cs[j * 8 + 2 * t], cu = *(const float2*)&s_cs[BN + j * 8 + 2 * t];
      const float* a = &acc[0][0][4 * j];
      const float* b = &acc[0][1][4 * j];
#pragma unroll
      for (int e = 0; e < 2; e++) {
        const float2 s_ = st[e];
        const uint32_t gp = pack_bf16(fmaf(-s_.x, cg.x, a[2 * e]) * s_.y, fmaf(-s_.x, cg.y, a[2 * e + 1]) * s_.y);
        const uint32_t up = pack_bf16(fmaf(-s_.x, cu.x, b[2 * e]) * s_.y, fmaf(-s_.x, cu.y, b[2 * e + 1]) * s_.y);
        uint32_t r;
        asm("{\n.reg .b32 z;\nmax.bf16x2 z, %1, %3;\nmul.rn.bf16x2 %0, z, %2;\n}" : "=r"(r) : "r"(gp), "r"(up), "r"(0u));
        *(uint32_t*)(sptr + (r0 + 8 * e) * LDS + j * 16 + t * 4) = r;
      }
    }
    named_bar(1, 256);
#pragma unroll
    for (int i = 0; i < BM * (BN / 8) / 256; i++) {
      const int idx = i * 256 + ctid, r = idx / (BN / 8), c = idx % (BN / 8);
      *(uint4*)(out + (size_t)(m0 + r) * DFF + n0 + c * 8) = *(const uint4*)(sptr + r * LDS + c * 16);
    }
  }
  if constexpr (CN * CM > 1) cluster_wait();
  TS_END(EPI == EPI_QKV ? 1 : EPI + 2);
}

constexpr int R_STAGES = 8;
constexpr int R_STAGE_BYTES = 16384 + 5 * 2048;
constexpr int R_BAR_OFF = R_STAGES * R_STAGE_BYTES;
constexpr int R_SMEM = R_BAR_OFF + 256 + 1024;
template <int KDIM, bool STATS>
__global__ void __launch_bounds__(288, 1) gemm_res_kernel(const __grid_constant__ CUtensorMap tmA, const __grid_constant__ CUtensorMap tmB,
                                                          const __nv_bfloat16* __restrict__ resid, __nv_bfloat16* __restrict__ out) {
  constexpr int KT = KDIM / 64;
  extern __shared__ uint8_t smem_raw[];
  const uint32_t sbase = (smem_u32(smem_raw) + 1023u) & ~1023u;
  uint8_t* sptr = smem_raw + (sbase - smem_u32(smem_raw));
  const uint32_t sbar = sbase + R_BAR_OFF;
  const int tid = threadIdx.x, warp = tid >> 5, lane = tid & 31;
  const int n0 = blockIdx.x * 80, m0 = blockIdx.y * 128;
  TS_BEGIN(STATS ? 3 : 5);
  if (tid == 0) {
    for (int i = 0; i < R_STAGES; i++) { mbar_init(sbar + 8 * i, 1); mbar_init(sbar + 8 * (R_STAGES + i), 2); }
    asm volatile("fence.mbarrier_init.release.cluster;" ::: "memory");
  }
  __syncthreads();
  pdl_launch();
  if (warp == 8) {
    if (lane == 0) {
      auto load_b = [&](int kt, int s) {
#pragma unroll
        for (int j = 0; j < 5; j++) tma_2d(sbase + s * R_STAGE_BYTES + 16384 + j * 2048, &tmB, n0 + j * 16, kt * 64, sbar + 8 * s);
      };
      for (int s = 0; s < R_STAGES; s++) { mbar_expect_tx(sbar + 8 * s, R_STAGE_BYTES); load_b(s, s); }
      pdl_wait();
      for (int s = 0; s < R_STAGES; s++) tma_2d(sbase + s * R_STAGE_BYTES, &tmA, s * 64, m0, sbar + 8 * s);
      for (int kt = R_STAGES; kt < KT; kt++) {
        const int s = kt % R_STAGES;
        mbar_wait(sbar + 8 * (R_STAGES + s), ((kt / R_STAGES) - 1) & 1);
        mbar_expect_tx(sbar + 8 * s, R_STAGE_BYTES);
        tma_2d(sbase + s * R_STAGE_BYTES, &tmA, kt * 64, m0, sbar + 8 * s);
        load_b(kt, s);
      }
    }
    return;
  }
  const int wg = warp >> 2, g = lane >> 2, t = lane & 3;
  pdl_wait();
  uint4 rv[5];
#pragma unroll
  for (int i = 0; i < 5; i++) {
    const int idx = i * 256 + tid, r = idx / 10, c = idx % 10;
    rv[i] = *(const uint4*)(resid + (size_t)(m0 + r) * DM + n0 + c * 8);
  }
  float acc[40];
#pragma unroll
  for (int i = 0; i < 40; i++) acc[i] = 0.f;
  for (int kt = 0; kt < KT; kt++) {
    const int s = kt % R_STAGES;
    mbar_wait(sbar + 8 * s, (kt / R_STAGES) & 1);
    if (kt == 0) TS_MID(STATS ? 3 : 5, 0);
    const uint32_t sa = sbase + s * R_STAGE_BYTES + wg * 8192;
    const uint32_t sb = sbase + s * R_STAGE_BYTES + 16384;
    wgmma_fence();
#pragma unroll
    for (int ks = 0; ks < 4; ks++)
      wgmma_ss_n80(acc, make_desc(sa + ks * 32, 16, 1024, 1), make_desc(sb + ks * 512, 2048, 256, 3), 1);
    wgmma_commit();
    wgmma_wait<1>();
    if (kt > 0 && kt - 1 + R_STAGES < KT && (tid & 127) == 0) mbar_arrive(sbar + 8 * (R_STAGES + (kt - 1) % R_STAGES));
  }
  wgmma_wait<0>();
#pragma unroll
  for (int i = 0; i < 40; i++) asm volatile("" : "+f"(acc[i]) :: "memory");
  TS_MID(STATS ? 3 : 5, 1);
  named_bar(1, 256);
  constexpr int LDS = 176;
  const int r0 = wg * 64 + (warp & 3) * 16 + g;
#pragma unroll
  for (int i = 0; i < 10; i++) {
    *(uint32_t*)(sptr + r0 * LDS + i * 16 + t * 4) = pack_bf16(acc[4 * i], acc[4 * i + 1]);
    *(uint32_t*)(sptr + (r0 + 8) * LDS + i * 16 + t * 4) = pack_bf16(acc[4 * i + 2], acc[4 * i + 3]);
  }
  named_bar(1, 256);
#pragma unroll
  for (int i = 0; i < 5; i++) {
    const int idx = i * 256 + tid, r = idx / 10, c = idx % 10;
    const uint4 a = *(const uint4*)(sptr + r * LDS + c * 16);
    const uint4 b = rv[i];
    uint4 o;
    o.x = pack_bf16(bf_lo(a.x) + bf_lo(b.x), bf_hi(a.x) + bf_hi(b.x));
    o.y = pack_bf16(bf_lo(a.y) + bf_lo(b.y), bf_hi(a.y) + bf_hi(b.y));
    o.z = pack_bf16(bf_lo(a.z) + bf_lo(b.z), bf_hi(a.z) + bf_hi(b.z));
    o.w = pack_bf16(bf_lo(a.w) + bf_lo(b.w), bf_hi(a.w) + bf_hi(b.w));
    *(uint4*)(out + (size_t)(m0 + r) * DM + n0 + c * 8) = o;
    if constexpr (STATS) *(uint4*)(sptr + r * LDS + c * 16) = o;
  }
  TS_MID(STATS ? 3 : 5, 3);
  if constexpr (STATS) {
    named_bar(1, 256);
    const int r = tid >> 1, hf = tid & 1;
    float f[40];
#pragma unroll
    for (int i = 0; i < 5; i++) {
      const uint4 v = *(const uint4*)(sptr + r * LDS + hf * 80 + i * 16);
      f[8 * i] = bf_lo(v.x); f[8 * i + 1] = bf_hi(v.x); f[8 * i + 2] = bf_lo(v.y); f[8 * i + 3] = bf_hi(v.y);
      f[8 * i + 4] = bf_lo(v.z); f[8 * i + 5] = bf_hi(v.z); f[8 * i + 6] = bf_lo(v.w); f[8 * i + 7] = bf_hi(v.w);
    }
    float s = 0.f;
#pragma unroll
    for (int i = 0; i < 40; i++) s += f[i];
    s += __shfl_xor_sync(~0u, s, 1);
    const float mu = s * (1.0f / 80.f);
    float q = 0.f;
#pragma unroll
    for (int i = 0; i < 40; i++) { const float d = f[i] - mu; q += d * d; }
    q += __shfl_xor_sync(~0u, q, 1);
    if (hf == 0) g_part2[(m0 + r) * 8 + blockIdx.x] = make_float2(s, q);
  }
  TS_END(STATS ? 3 : 5);
}

#define POLY_NUM 5
__device__ __forceinline__ float ex2_poly(float x, int shl23) {
  const float MAGIC = 12582912.f;
  const float tt = x + MAGIC;
  const float f = x - (tt - MAGIC);
  float p = fmaf(0.0013276472454890609f, f, 0.009675540961325169f);
  p = fmaf(p, f, 0.05550713092088699f);
  p = fmaf(p, f, 0.24022120237350464f);
  p = fmaf(p, f, 0.6931469440460205f);
  p = fmaf(p, f, 1.0000001192092896f);
  return __int_as_float(__float_as_int(tt) * shl23 + __float_as_int(p));
}
constexpr int KV_BYTES = S_LEN * 48;
constexpr int ATT_SMEM = 2 * KV_BYTES + 256;

__global__ void __launch_bounds__(512, 1) attn_kernel(int shl23, const __nv_bfloat16* __restrict__ wg_, const __nv_bfloat16* __restrict__ wu_,
                                                      const __nv_bfloat16* __restrict__ wo_, const __nv_bfloat16* __restrict__ wd_) {
  extern __shared__ __align__(1024) uint8_t smem[];
  if (blockIdx.x >= 128) {
    pdl_launch();
    const int e = blockIdx.x - 128, half = threadIdx.x >> 8;
    if (threadIdx.x == 0) {
      for (int i = 0; i < 13; i++) asm volatile("cp.async.bulk.prefetch.L2.global [%0], %1;" :: "l"((const uint8_t*)wo_ + (e * 13 + i) * 16384 * 0 + (size_t)(e * 13 + i >= 50 ? 0 : (e * 13 + i)) * 16384), "r"(16384));
      for (int i = 0; i < 30; i++) asm volatile("cp.async.bulk.prefetch.L2.global [%0], %1;" :: "l"((const uint8_t*)wd_ + (size_t)(e * 30 + i) * 16384), "r"(16384));
    }
    float (*red)[65] = (float (*)[65])(smem + half * 16384);
    for (int b = e * 12 + half; b < e * 12 + 12; b += 2) {
      if (b < 24) colsum64(wg_, DFF, b * 64, g_cs_g, red, threadIdx.x & 255, 1 + half);
      else colsum64(wu_, DFF, (b - 24) * 64, g_cs_u, red, threadIdx.x & 255, 1 + half);
    }
    return;
  }
  const int h = blockIdx.x >> 2, qb = blockIdx.x & 3;
  const uint32_t sK = smem_u32(smem), sV = sK + KV_BYTES, sBar = sV + KV_BYTES;
  const int tid = threadIdx.x;
  TS_BEGIN(2);
  if (tid == 0) {
    for (int i = 0; i < 8; i++) mbar_init(sBar + 8 * i, 1);
    asm volatile("fence.mbarrier_init.release.cluster;" ::: "memory");
  }
  pdl_launch();
  pdl_wait();
  if (tid == 0) {
    const uint8_t* gk = (const uint8_t*)(g_k + (size_t)h * S_LEN * 24);
    const uint8_t* gv = (const uint8_t*)(g_v + (size_t)h * S_LEN * 24);
    for (int i = 0; i < 8; i++) {
      mbar_expect_tx(sBar + 8 * i, 2 * 12288);
      bulk_g2s(sK + i * 12288, gk + i * 12288, 12288, sBar + 8 * i);
      bulk_g2s(sV + i * 12288, gv + i * 12288, 12288, sBar + 8 * i);
    }
  }
  __syncthreads();
  const int wg = tid >> 7, warp = (tid >> 5) & 3, lane = tid & 31, g = lane >> 2, t = lane & 3;
  float ka = 0.f, kb = 0.f;
#pragma unroll
  for (int i = 0; i < 8; i++) {
    const float2 v = *(const float2*)&g_kn[(i * NH + h) * 2];
    ka = (v.x > ka || v.x != v.x) ? v.x : ka;
    kb = (v.y > kb || v.y != v.y) ? v.y : kb;
  }
  const float kn = sqrtf(ka + kb);
  for (int it = 0; it < 2; it++) {
    const int q0 = qb * 512 + (it * 4 + wg) * 64 + warp * 16;
    uint32_t qa[4], qc[4];
    const uint32_t* qr0 = (const uint32_t*)(g_q + (size_t)(q0 + g) * DM + h * DH);
    const uint32_t* qr1 = (const uint32_t*)(g_q + (size_t)(q0 + g + 8) * DM + h * DH);
    qa[0] = qr0[t]; qa[1] = qr1[t]; qa[2] = qr0[t + 4]; qa[3] = qr1[t + 4];
    qc[0] = (t < 2) ? qr0[t + 8] : 0u; qc[1] = (t < 2) ? qr1[t + 8] : 0u; qc[2] = 0; qc[3] = 0;
    auto sq = [](uint32_t u) { const float a = bf_lo(u), b = bf_hi(u); return a * a + b * b; };
    float n0 = sq(qa[0]) + sq(qa[2]) + sq(qc[0]);
    float n1 = sq(qa[1]) + sq(qa[3]) + sq(qc[1]);
    n0 += __shfl_xor_sync(~0u, n0, 1); n0 += __shfl_xor_sync(~0u, n0, 2);
    n1 += __shfl_xor_sync(~0u, n1, 1); n1 += __shfl_xor_sync(~0u, n1, 2);
    const float m0 = ceilf(sqrtf(n0) * kn * 1.001f) + 1.f, m1 = ceilf(sqrtf(n1) * kn * 1.001f) + 1.f;
    const bool unsafe = !(m0 <= 62.f && m1 <= 62.f);
    uint32_t any_unsafe;
    asm volatile("{\n.reg .pred p, q;\nsetp.ne.u32 p, %1, 0;\nbarrier.cta.red.or.pred q, %2, 128, p;\nselp.u32 %0, 1, 0, q;\n}"
                 : "=r"(any_unsafe) : "r"((uint32_t)unsafe), "r"(1 + wg) : "memory");
    float O[12];
    float S[32];
    if (!__any_sync(~0u, any_unsafe)) {
      if (t == 2) { qc[0] = pack_bf16(-m0, 0.f); qc[1] = pack_bf16(-m1, 0.f); }
      for (int j = 0; j < 32; j++) {
        if (it == 0 && (j & 3) == 0) mbar_wait(sBar + 8 * (j >> 2), 0);
        const uint64_t dk = make_desc(sK + j * 8 * 384, 128, 384, 0);
        wgmma_fence();
        wgmma_rs_n64(S, qa[0], qa[1], qa[2], qa[3], dk, 0);
        wgmma_rs_n64(S, qc[0], qc[1], qc[2], qc[3], dk + (256 >> 4), 1);
        wgmma_commit();
        wgmma_wait<0>();
        uint32_t P[16];
#pragma unroll
        for (int i = 0; i < 16; i++) {
          const bool usepoly = ((i + 1) * POLY_NUM / 16) != (i * POLY_NUM / 16);
          float a, b;
          if (usepoly) { a = ex2_poly(S[2 * i], shl23); b = ex2_poly(S[2 * i + 1], shl23); }
          else { a = ex2_mufu(S[2 * i]); b = ex2_mufu(S[2 * i + 1]); }
          P[i] = pack_bf16(a, b);
        }
        wgmma_fence();
        const uint64_t dv = make_desc(sV + j * 8 * 384, 384, 128, 0);
#pragma unroll
        for (int ks = 0; ks < 4; ks++)
          wgmma_rs_n24_tb(O, P[4 * ks], P[4 * ks + 1], P[4 * ks + 2], P[4 * ks + 3], dv + ((ks * 768) >> 4), (j | ks) != 0);
        wgmma_commit();
      }
    } else {
      float mx0 = -INFINITY, mx1 = -INFINITY;
      for (int j = 0; j < 32; j++) {
        if (it == 0 && (j & 3) == 0) mbar_wait(sBar + 8 * (j >> 2), 0);
        const uint64_t dk = make_desc(sK + j * 8 * 384, 128, 384, 0);
        wgmma_fence();
        wgmma_rs_n64(S, qa[0], qa[1], qa[2], qa[3], dk, 0);
        wgmma_rs_n64(S, qc[0], qc[1], qc[2], qc[3], dk + (256 >> 4), 1);
        wgmma_commit();
        wgmma_wait<0>();
#pragma unroll
        for (int i = 0; i < 8; i++) {
          mx0 = fmaxf(mx0, fmaxf(S[4 * i], S[4 * i + 1]));
          mx1 = fmaxf(mx1, fmaxf(S[4 * i + 2], S[4 * i + 3]));
        }
      }
      mx0 = fmaxf(mx0, __shfl_xor_sync(~0u, mx0, 1)); mx0 = fmaxf(mx0, __shfl_xor_sync(~0u, mx0, 2));
      mx1 = fmaxf(mx1, __shfl_xor_sync(~0u, mx1, 1)); mx1 = fmaxf(mx1, __shfl_xor_sync(~0u, mx1, 2));
      for (int j = 0; j < 32; j++) {
        const uint64_t dk = make_desc(sK + j * 8 * 384, 128, 384, 0);
        wgmma_fence();
        wgmma_rs_n64(S, qa[0], qa[1], qa[2], qa[3], dk, 0);
        wgmma_rs_n64(S, qc[0], qc[1], qc[2], qc[3], dk + (256 >> 4), 1);
        wgmma_commit();
        wgmma_wait<0>();
        uint32_t P[16];
#pragma unroll
        for (int i = 0; i < 8; i++) {
          P[2 * i] = pack_bf16(ex2_mufu(S[4 * i] - mx0), ex2_mufu(S[4 * i + 1] - mx0));
          P[2 * i + 1] = pack_bf16(ex2_mufu(S[4 * i + 2] - mx1), ex2_mufu(S[4 * i + 3] - mx1));
        }
        wgmma_fence();
        const uint64_t dv = make_desc(sV + j * 8 * 384, 384, 128, 0);
#pragma unroll
        for (int ks = 0; ks < 4; ks++)
          wgmma_rs_n24_tb(O, P[4 * ks], P[4 * ks + 1], P[4 * ks + 2], P[4 * ks + 3], dv + ((ks * 768) >> 4), (j | ks) != 0);
        wgmma_commit();
      }
    }
    wgmma_wait<0>();
#pragma unroll
    for (int i = 0; i < 12; i++) asm volatile("" : "+f"(O[i]) :: "memory");
    const float l0 = __shfl_sync(~0u, O[8], (lane & ~3) | 2), l1 = __shfl_sync(~0u, O[10], (lane & ~3) | 2);
    const float r0 = 1.f / l0, r1 = 1.f / l1;
    uint32_t* o0 = (uint32_t*)(g_o + (size_t)(q0 + g) * DM + h * DH);
    uint32_t* o1 = (uint32_t*)(g_o + (size_t)(q0 + g + 8) * DM + h * DH);
    o0[t] = pack_bf16(O[0] * r0, O[1] * r0); o1[t] = pack_bf16(O[2] * r1, O[3] * r1);
    o0[t + 4] = pack_bf16(O[4] * r0, O[5] * r0); o1[t + 4] = pack_bf16(O[6] * r1, O[7] * r1);
    if (t < 2) { o0[t + 8] = pack_bf16(O[8] * r0, O[9] * r0); o1[t + 8] = pack_bf16(O[10] * r1, O[11] * r1); }
  }
  TS_END(2);
}

typedef CUresult (*EncodeFn)(CUtensorMap*, CUtensorMapDataType, cuuint32_t, void*, const cuuint64_t*, const cuuint64_t*, const cuuint32_t*,
                             const cuuint32_t*, CUtensorMapInterleave, CUtensorMapSwizzle, CUtensorMapL2promotion, CUtensorMapFloatOOBfill);
static EncodeFn get_encode() {
  static EncodeFn fn = nullptr;
  if (!fn) {
    void* p = nullptr; cudaDriverEntryPointQueryResult st;
    cudaGetDriverEntryPoint("cuTensorMapEncodeTiled", &p, cudaEnableDefault, &st);
    fn = (EncodeFn)p;
  }
  return fn;
}
static CUtensorMap make_map(const void* ptr, int rows, int cols, int box_rows, int box_cols = 64) {
  CUtensorMap m;
  cuuint64_t dims[2] = {(cuuint64_t)cols, (cuuint64_t)rows};
  cuuint64_t strides[1] = {(cuuint64_t)cols * 2};
  cuuint32_t box[2] = {(cuuint32_t)box_cols, (cuuint32_t)box_rows};
  cuuint32_t es[2] = {1, 1};
  get_encode()(&m, CU_TENSOR_MAP_DATA_TYPE_BFLOAT16, 2, const_cast<void*>(ptr), dims, strides, box, es, CU_TENSOR_MAP_INTERLEAVE_NONE,
               box_cols == 64 ? CU_TENSOR_MAP_SWIZZLE_128B : (box_cols == 32 ? CU_TENSOR_MAP_SWIZZLE_64B : CU_TENSOR_MAP_SWIZZLE_32B), CU_TENSOR_MAP_L2_PROMOTION_L2_128B, CU_TENSOR_MAP_FLOAT_OOB_FILL_NONE);
  return m;
}
template <typename... KArgs, typename... Args>
static void launch(void (*kern)(KArgs...), dim3 grid, dim3 block, size_t smem, bool pdl, dim3 cluster, Args... args) {
  cudaLaunchConfig_t cfg = {};
  cfg.gridDim = grid; cfg.blockDim = block; cfg.dynamicSmemBytes = smem; cfg.stream = cudaStreamPerThread;
  cudaLaunchAttribute at[2];
  int na = 0;
  if (pdl) { at[na].id = cudaLaunchAttributeProgrammaticStreamSerialization; at[na].val.programmaticStreamSerializationAllowed = 1; na++; }
  if (cluster.x * cluster.y > 1) { at[na].id = cudaLaunchAttributeClusterDimension; at[na].val.clusterDim.x = cluster.x; at[na].val.clusterDim.y = cluster.y; at[na].val.clusterDim.z = 1; na++; }
  cfg.attrs = at; cfg.numAttrs = na;
  cudaLaunchKernelEx(&cfg, kern, KArgs(args)...);
}

extern "C" void kernel_launch(void* const* d_in, const int* in_sizes, int n_in, void* d_out, int out_size) {
  const __nv_bfloat16* x = (const __nv_bfloat16*)d_in[0];
  const __nv_bfloat16* wqkv = (const __nv_bfloat16*)d_in[1];
  const __nv_bfloat16* wo = (const __nv_bfloat16*)d_in[2];
  const __nv_bfloat16* wgate = (const __nv_bfloat16*)d_in[4];
  const __nv_bfloat16* wup = (const __nv_bfloat16*)d_in[5];
  const __nv_bfloat16* wdown = (const __nv_bfloat16*)d_in[6];
  __nv_bfloat16* out = (__nv_bfloat16*)d_out;
  void *p_o, *p_h, *p_act;
  cudaGetSymbolAddress(&p_o, g_o); cudaGetSymbolAddress(&p_h, g_h); cudaGetSymbolAddress(&p_act, g_act);

#define A_CN 1
#define A_CM 1
#define D_CN 1
#define D_CM 1
  auto kA = gemm_kernel<256, 128, 1, DM, 4, EPI_QKV, 1, A_CN, A_CM>;
  auto kC = gemm_res_kernel<DM, true>;
  auto kD = gemm_kernel<128, 192, 2, DM, 3, EPI_GLU, 1, D_CN, D_CM>;
  auto kE = gemm_res_kernel<DFF, false>;
  constexpr int smA = GemmCfg<256, 128, 1, 4>::SMEM, smC = R_SMEM, smD = GemmCfg<128, 192, 2, 3>::SMEM;
  cudaFuncSetAttribute(kA, cudaFuncAttributeMaxDynamicSharedMemorySize, smA);
  cudaFuncSetAttribute(kC, cudaFuncAttributeMaxDynamicSharedMemorySize, smC);
  cudaFuncSetAttribute(kD, cudaFuncAttributeMaxDynamicSharedMemorySize, smD);
  cudaFuncSetAttribute(kE, cudaFuncAttributeMaxDynamicSharedMemorySize, smC);
  cudaFuncSetAttribute(attn_kernel, cudaFuncAttributeMaxDynamicSharedMemorySize, ATT_SMEM);

  const CUtensorMap tm_x = make_map(x, S_LEN, DM, 256 / A_CN), tm_wqkv = make_map(wqkv, DM, 3 * DM, 2 % A_CM ? 64 / A_CM : 64);
  const CUtensorMap tm_o = make_map(p_o, S_LEN, DM, 128), tm_wo = make_map(wo, DM, DM, 64, 16);
  const CUtensorMap tm_h = make_map(p_h, S_LEN, DM, 128 / D_CN), tm_wg = make_map(wgate, DM, DFF, 6 % D_CM ? 64 / D_CM : 64), tm_wu = make_map(wup, DM, DFF, 6 % D_CM ? 64 / D_CM : 64);
  const CUtensorMap tm_act = make_map(p_act, S_LEN, DFF, 128), tm_wd = make_map(wdown, DFF, DM, 64, 16);

  launch(pre_kernel, dim3(PRE_COL_BLOCKS + PRE_ROW_BLOCKS), dim3(256), 0, false, dim3(1, 1), x, wqkv);
  launch(kA, dim3(15, 8), dim3(288), smA, true, dim3(A_CN, A_CM), tm_x, tm_wqkv, tm_wqkv, (const __nv_bfloat16*)nullptr, (__nv_bfloat16*)nullptr);
  launch(attn_kernel, dim3(132), dim3(512), ATT_SMEM, true, dim3(1, 1), 0x800000, wgate, wup, wo, wdown);
  launch(kC, dim3(8, 16), dim3(288), smC, true, dim3(1, 1), tm_o, tm_wo, x, (__nv_bfloat16*)p_h);
  launch(kD, dim3(8, 16), dim3(384), smD, true, dim3(D_CN, D_CM), tm_h, tm_wg, tm_wu, (const __nv_bfloat16*)nullptr, (__nv_bfloat16*)p_act);
  launch(kE, dim3(8, 16), dim3(288), smC, true, dim3(1, 1), tm_act, tm_wd, (const __nv_bfloat16*)p_h, out);
}
```

```cpp
#include <cuda_runtime.h>
#include <cuda_bf16.h>
#include <cuda.h>
#include <stdint.h>

constexpr int S_LEN = 2048, DM = 640, NH = 32, DH = 20, DFF = 1536;

__device__ __align__(1024) __nv_bfloat16 g_q[S_LEN * DM];
__device__ __align__(1024) __nv_bfloat16 g_k[NH * S_LEN * 24];
__device__ __align__(1024) __nv_bfloat16 g_v[NH * S_LEN * 24];
__device__ __align__(1024) __nv_bfloat16 g_o[S_LEN * DM];
__device__ __align__(1024) __nv_bfloat16 g_h[S_LEN * DM];
__device__ __align__(1024) __nv_bfloat16 g_act[S_LEN * DFF];
__device__ float g_kn[8 * NH * 2];
__device__ float2 g_stat1[S_LEN];
__device__ float g_cs_qkv[3 * DM];
__device__ float g_cs_g[DFF];
__device__ float g_cs_u[DFF];
__device__ float2 g_part2[S_LEN * 10];

#define TS_BEGIN(k)
#define TS_END(k)
#define TS_MID(k, i)
__device__ __forceinline__ uint32_t smem_u32(const void* p) { return (uint32_t)__cvta_generic_to_shared(p); }
__device__ __forceinline__ void mbar_init(uint32_t bar, uint32_t cnt) { asm volatile("mbarrier.init.shared::cta.b64 [%0], %1;" :: "r"(bar), "r"(cnt)); }
__device__ __forceinline__ void mbar_expect_tx(uint32_t bar, uint32_t bytes) { asm volatile("mbarrier.arrive.expect_tx.shared::cta.b64 _, [%0], %1;" :: "r"(bar), "r"(bytes) : "memory"); }
__device__ __forceinline__ void mbar_arrive(uint32_t bar) { asm volatile("mbarrier.arrive.shared::cta.b64 _, [%0];" :: "r"(bar) : "memory"); }
__device__ __forceinline__ void mbar_wait(uint32_t bar, uint32_t parity) {
  uint32_t done;
  uint32_t spins = 0;
  do {
    asm volatile("{\n.reg .pred P1;\nmbarrier.try_wait.parity.shared::cta.b64 P1, [%1], %2;\nselp.u32 %0, 1, 0, P1;\n}" : "=r"(done) : "r"(bar), "r"(parity) : "memory");
  } while (!done && ++spins < (1u << 24));
}
__device__ __forceinline__ void bulk_g2s(uint32_t dst, const void* src, uint32_t bytes, uint32_t bar) {
  asm volatile("cp.async.bulk.shared::cluster.global.mbarrier::complete_tx::bytes [%0], [%1], %2, [%3];" :: "r"(dst), "l"(src), "r"(bytes), "r"(bar) : "memory");
}
__device__ __forceinline__ void tma_2d(uint32_t dst, const CUtensorMap* tm, int c0, int c1, uint32_t bar) {
  asm volatile("cp.async.bulk.tensor.2d.shared::cluster.global.mbarrier::complete_tx::bytes [%0], [%1, {%3, %4}], [%2];"
               :: "r"(dst), "l"(tm), "r"(bar), "r"(c0), "r"(c1) : "memory");
}
__device__ __forceinline__ void tma_3d(uint32_t dst, const CUtensorMap* tm, int c0, int c1, int c2, uint32_t bar) {
  asm volatile("cp.async.bulk.tensor.3d.shared::cluster.global.mbarrier::complete_tx::bytes [%0], [%1, {%3, %4, %5}], [%2];"
               :: "r"(dst), "l"(tm), "r"(bar), "r"(c0), "r"(c1), "r"(c2) : "memory");
}
__device__ __forceinline__ void tma_2d_mc(uint32_t dst, const CUtensorMap* tm, int c0, int c1, uint32_t bar, uint16_t mask) {
  asm volatile("cp.async.bulk.tensor.2d.shared::cluster.global.mbarrier::complete_tx::bytes.multicast::cluster [%0], [%1, {%3, %4}], [%2], %5;"
               :: "r"(dst), "l"(tm), "r"(bar), "r"(c0), "r"(c1), "h"(mask) : "memory");
}
__device__ __forceinline__ void mbar_arrive_remote(uint32_t bar, uint32_t rank) {
  asm volatile("{\n.reg .b32 ra;\nmapa.shared::cluster.u32 ra, %0, %1;\nmbarrier.arrive.release.cluster.shared::cluster.b64 _, [ra];\n}" :: "r"(bar), "r"(rank) : "memory");
}
__device__ __forceinline__ void cluster_arrive() { asm volatile("barrier.cluster.arrive.release.aligned;" ::: "memory"); }
__device__ __forceinline__ void cluster_wait() { asm volatile("barrier.cluster.wait.acquire.aligned;" ::: "memory"); }
__device__ __forceinline__ void wgmma_fence() { asm volatile("wgmma.fence.sync.aligned;" ::: "memory"); }
__device__ __forceinline__ void wgmma_commit() { asm volatile("wgmma.commit_group.sync.aligned;" ::: "memory"); }
template <int N> __device__ __forceinline__ void wgmma_wait() { asm volatile("wgmma.wait_group.sync.aligned %0;" :: "n"(N) : "memory"); }
__device__ __forceinline__ void pdl_wait() { asm volatile("griddepcontrol.wait;" ::: "memory"); }
__device__ __forceinline__ void pdl_launch() { asm volatile("griddepcontrol.launch_dependents;" ::: "memory"); }
__device__ __forceinline__ void named_bar(int id, int n) { asm volatile("bar.sync %0, %1;" :: "r"(id), "r"(n) : "memory"); }
__device__ __forceinline__ uint64_t make_desc(uint32_t addr, uint32_t lbo, uint32_t sbo, uint32_t swz) {
  return (uint64_t)((addr & 0x3FFFF) >> 4) | ((uint64_t)(lbo >> 4) << 16) | ((uint64_t)(sbo >> 4) << 32) | ((uint64_t)swz << 62);
}
__device__ __forceinline__ uint32_t pack_bf16(float lo, float hi) { uint32_t r; asm("cvt.rn.bf16x2.f32 %0, %1, %2;" : "=r"(r) : "f"(hi), "f"(lo)); return r; }
__device__ __forceinline__ float bf_lo(uint32_t u) { return __uint_as_float(u << 16); }
__device__ __forceinline__ float bf_hi(uint32_t u) { return __uint_as_float(u & 0xffff0000u); }
__device__ __forceinline__ float bf_round(float x) { return __bfloat162float(__float2bfloat16_rn(x)); }
__device__ __forceinline__ float ex2_mufu(float x) { float y; asm("ex2.approx.ftz.f32 %0, %1;" : "=f"(y) : "f"(x)); return y; }

__device__ __forceinline__ void wgmma_ss_n80(float (&d)[40], uint64_t da, uint64_t db, int scale_d) {
  asm volatile("{\n.reg .pred p;\nsetp.ne.b32 p, %42, 0;\n"
    "wgmma.mma_async.sync.aligned.m64n80k16.f32.bf16.bf16 {%0,%1,%2,%3,%4,%5,%6,%7,%8,%9,%10,%11,%12,%13,%14,%15,%16,%17,%18,%19,%20,%21,%22,%23,%24,%25,%26,%27,%28,%29,%30,%31,%32,%33,%34,%35,%36,%37,%38,%39}, %40, %41, p, 1, 1, 0, 1;\n}\n"
    : "+f"(d[0]),"+f"(d[1]),"+f"(d[2]),"+f"(d[3]),"+f"(d[4]),"+f"(d[5]),"+f"(d[6]),"+f"(d[7]),"+f"(d[8]),"+f"(d[9]),"+f"(d[10]),"+f"(d[11]),"+f"(d[12]),"+f"(d[13]),"+f"(d[14]),"+f"(d[15]),"+f"(d[16]),"+f"(d[17]),"+f"(d[18]),"+f"(d[19]),"+f"(d[20]),"+f"(d[21]),"+f"(d[22]),"+f"(d[23]),"+f"(d[24]),"+f"(d[25]),"+f"(d[26]),"+f"(d[27]),"+f"(d[28]),"+f"(d[29]),"+f"(d[30]),"+f"(d[31]),"+f"(d[32]),"+f"(d[33]),"+f"(d[34]),"+f"(d[35]),"+f"(d[36]),"+f"(d[37]),"+f"(d[38]),"+f"(d[39])
    : "l"(da), "l"(db), "r"(scale_d));
}
__device__ __forceinline__ void wgmma_ss_n128(float (&d)[64], uint64_t da, uint64_t db, int scale_d) {
  asm volatile("{\n.reg .pred p;\nsetp.ne.b32 p, %66, 0;\n"
    "wgmma.mma_async.sync.aligned.m64n128k16.f32.bf16.bf16 {%0,%1,%2,%3,%4,%5,%6,%7,%8,%9,%10,%11,%12,%13,%14,%15,%16,%17,%18,%19,%20,%21,%22,%23,%24,%25,%26,%27,%28,%29,%30,%31,%32,%33,%34,%35,%36,%37,%38,%39,%40,%41,%42,%43,%44,%45,%46,%47,%48,%49,%50,%51,%52,%53,%54,%55,%56,%57,%58,%59,%60,%61,%62,%63}, %64, %65, p, 1, 1, 0, 1;\n}\n"
    : "+f"(d[0]),"+f"(d[1]),"+f"(d[2]),"+f"(d[3]),"+f"(d[4]),"+f"(d[5]),"+f"(d[6]),"+f"(d[7]),"+f"(d[8]),"+f"(d[9]),"+f"(d[10]),"+f"(d[11]),"+f"(d[12]),"+f"(d[13]),"+f"(d[14]),"+f"(d[15]),"+f"(d[16]),"+f"(d[17]),"+f"(d[18]),"+f"(d[19]),"+f"(d[20]),"+f"(d[21]),"+f"(d[22]),"+f"(d[23]),"+f"(d[24]),"+f"(d[25]),"+f"(d[26]),"+f"(d[27]),"+f"(d[28]),"+f"(d[29]),"+f"(d[30]),"+f"(d[31]),"+f"(d[32]),"+f"(d[33]),"+f"(d[34]),"+f"(d[35]),"+f"(d[36]),"+f"(d[37]),"+f"(d[38]),"+f"(d[39]),"+f"(d[40]),"+f"(d[41]),"+f"(d[42]),"+f"(d[43]),"+f"(d[44]),"+f"(d[45]),"+f"(d[46]),"+f"(d[47]),"+f"(d[48]),"+f"(d[49]),"+f"(d[50]),"+f"(d[51]),"+f"(d[52]),"+f"(d[53]),"+f"(d[54]),"+f"(d[55]),"+f"(d[56]),"+f"(d[57]),"+f"(d[58]),"+f"(d[59]),"+f"(d[60]),"+f"(d[61]),"+f"(d[62]),"+f"(d[63])
    : "l"(da), "l"(db), "r"(scale_d));
}
__device__ __forceinline__ void wgmma_ss_n192(float (&d)[96], uint64_t da, uint64_t db, int scale_d) {
  asm volatile("{\n.reg .pred p;\nsetp.ne.b32 p, %98, 0;\n"
    "wgmma.mma_async.sync.aligned.m64n192k16.f32.bf16.bf16 {%0,%1,%2,%3,%4,%5,%6,%7,%8,%9,%10,%11,%12,%13,%14,%15,%16,%17,%18,%19,%20,%21,%22,%23,%24,%25,%26,%27,%28,%29,%30,%31,%32,%33,%34,%35,%36,%37,%38,%39,%40,%41,%42,%43,%44,%45,%46,%47,%48,%49,%50,%51,%52,%53,%54,%55,%56,%57,%58,%59,%60,%61,%62,%63,%64,%65,%66,%67,%68,%69,%70,%71,%72,%73,%74,%75,%76,%77,%78,%79,%80,%81,%82,%83,%84,%85,%86,%87,%88,%89,%90,%91,%92,%93,%94,%95}, %96, %97, p, 1, 1, 0, 1;\n}\n"
    : "+f"(d[0]),"+f"(d[1]),"+f"(d[2]),"+f"(d[3]),"+f"(d[4]),"+f"(d[5]),"+f"(d[6]),"+f"(d[7]),"+f"(d[8]),"+f"(d[9]),"+f"(d[10]),"+f"(d[11]),"+f"(d[12]),"+f"(d[13]),"+f"(d[14]),"+f"(d[15]),"+f"(d[16]),"+f"(d[17]),"+f"(d[18]),"+f"(d[19]),"+f"(d[20]),"+f"(d[21]),"+f"(d[22]),"+f"(d[23]),"+f"(d[24]),"+f"(d[25]),"+f"(d[26]),"+f"(d[27]),"+f"(d[28]),"+f"(d[29]),"+f"(d[30]),"+f"(d[31]),"+f"(d[32]),"+f"(d[33]),"+f"(d[34]),"+f"(d[35]),"+f"(d[36]),"+f"(d[37]),"+f"(d[38]),"+f"(d[39]),"+f"(d[40]),"+f"(d[41]),"+f"(d[42]),"+f"(d[43]),"+f"(d[44]),"+f"(d[45]),"+f"(d[46]),"+f"(d[47]),"+f"(d[48]),"+f"(d[49]),"+f"(d[50]),"+f"(d[51]),"+f"(d[52]),"+f"(d[53]),"+f"(d[54]),"+f"(d[55]),"+f"(d[56]),"+f"(d[57]),"+f"(d[58]),"+f"(d[59]),"+f"(d[60]),"+f"(d[61]),"+f"(d[62]),"+f"(d[63]),"+f"(d[64]),"+f"(d[65]),"+f"(d[66]),"+f"(d[67]),"+f"(d[68]),"+f"(d[69]),"+f"(d[70]),"+f"(d[71]),"+f"(d[72]),"+f"(d[73]),"+f"(d[74]),"+f"(d[75]),"+f"(d[76]),"+f"(d[77]),"+f"(d[78]),"+f"(d[79]),"+f"(d[80]),"+f"(d[81]),"+f"(d[82]),"+f"(d[83]),"+f"(d[84]),"+f"(d[85]),"+f"(d[86]),"+f"(d[87]),"+f"(d[88]),"+f"(d[89]),"+f"(d[90]),"+f"(d[91]),"+f"(d[92]),"+f"(d[93]),"+f"(d[94]),"+f"(d[95])
    : "l"(da), "l"(db), "r"(scale_d));
}
__device__ __forceinline__ void wgmma_rs_n64(float (&d)[32], uint32_t a0, uint32_t a1, uint32_t a2, uint32_t a3, uint64_t db, int scale_d) {
  asm volatile("{\n.reg .pred p;\nsetp.ne.b32 p, %37, 0;\n"
    "wgmma.mma_async.sync.aligned.m64n64k16.f32.bf16.bf16 {%0,%1,%2,%3,%4,%5,%6,%7,%8,%9,%10,%11,%12,%13,%14,%15,%16,%17,%18,%19,%20,%21,%22,%23,%24,%25,%26,%27,%28,%29,%30,%31}, {%32,%33,%34,%35}, %36, p, 1, 1, 0;\n}\n"
    : "+f"(d[0]),"+f"(d[1]),"+f"(d[2]),"+f"(d[3]),"+f"(d[4]),"+f"(d[5]),"+f"(d[6]),"+f"(d[7]),"+f"(d[8]),"+f"(d[9]),"+f"(d[10]),"+f"(d[11]),"+f"(d[12]),"+f"(d[13]),"+f"(d[14]),"+f"(d[15]),"+f"(d[16]),"+f"(d[17]),"+f"(d[18]),"+f"(d[19]),"+f"(d[20]),"+f"(d[21]),"+f"(d[22]),"+f"(d[23]),"+f"(d[24]),"+f"(d[25]),"+f"(d[26]),"+f"(d[27]),"+f"(d[28]),"+f"(d[29]),"+f"(d[30]),"+f"(d[31])
    : "r"(a0), "r"(a1), "r"(a2), "r"(a3), "l"(db), "r"(scale_d));
}
__device__ __forceinline__ void wgmma_rs_n24_tb(float (&d)[12], uint32_t a0, uint32_t a1, uint32_t a2, uint32_t a3, uint64_t db, int scale_d) {
  asm volatile("{\n.reg .pred p;\nsetp.ne.b32 p, %17, 0;\n"
    "wgmma.mma_async.sync.aligned.m64n24k16.f32.bf16.bf16 {%0,%1,%2,%3,%4,%5,%6,%7,%8,%9,%10,%11}, {%12,%13,%14,%15}, %16, p, 1, 1, 1;\n}\n"
    : "+f"(d[0]),"+f"(d[1]),"+f"(d[2]),"+f"(d[3]),"+f"(d[4]),"+f"(d[5]),"+f"(d[6]),"+f"(d[7]),"+f"(d[8]),"+f"(d[9]),"+f"(d[10]),"+f"(d[11])
    : "r"(a0), "r"(a1), "r"(a2), "r"(a3), "l"(db), "r"(scale_d));
}

constexpr int PRE_ROW_BLOCKS = 64;
constexpr int PRE_COL_BLOCKS = 3 * DM / 64;
__device__ __forceinline__ float2 ln_finish(float mean, float var) {
  float mb = bf_round(mean);
  float s = bf_round(sqrtf(bf_round(bf_round(var) + 1e-5f)));
  return make_float2(mb, 1.0f / s);
}
__device__ __forceinline__ void colsum64(const __nv_bfloat16* __restrict__ w, int ld, int c0, float* __restrict__ dst, float (*red)[65], int tid, int bar_id) {
  const int cg = tid & 7, r0 = tid >> 3;
  float acc[8];
#pragma unroll
  for (int i = 0; i < 8; i++) acc[i] = 0.f;
#pragma unroll 10
  for (int r = r0; r < DM; r += 32) {
    uint4 v = __ldg((const uint4*)(w + (size_t)r * ld + c0 + cg * 8));
    acc[0] += bf_lo(v.x); acc[1] += bf_hi(v.x); acc[2] += bf_lo(v.y); acc[3] += bf_hi(v.y);
    acc[4] += bf_lo(v.z); acc[5] += bf_hi(v.z); acc[6] += bf_lo(v.w); acc[7] += bf_hi(v.w);
  }
#pragma unroll
  for (int i = 0; i < 8; i++) red[r0][cg * 8 + i] = acc[i];
  named_bar(bar_id, 256);
  if (tid < 64) {
    float s = 0.f;
#pragma unroll
    for (int r = 0; r < 32; r++) s += red[r][tid];
    dst[c0 + tid] = s;
  }
  named_bar(bar_id, 256);
}
__global__ void __launch_bounds__(256) pre_kernel(const __nv_bfloat16* __restrict__ x, const __nv_bfloat16* __restrict__ wqkv) {
  TS_BEGIN(0);
  pdl_launch();
  const int tid = threadIdx.x, lane = tid & 31, warp = tid >> 5;
  if (blockIdx.x < PRE_COL_BLOCKS) {
    __shared__ float red[32][65];
    colsum64(wqkv, 3 * DM, blockIdx.x * 64, g_cs_qkv, red, tid, 1);
  } else {
    const int rb = blockIdx.x - PRE_COL_BLOCKS;
#pragma unroll
    for (int i = 0; i < 4; i++) {
      const int row = rb * 32 + warp * 4 + i;
      const uint4* p = (const uint4*)(x + (size_t)row * DM);
      uint4 v0 = __ldg(p + lane), v1 = __ldg(p + 32 + lane), v2 = make_uint4(0, 0, 0, 0);
      if (lane < 16) v2 = __ldg(p + 64 + lane);
      float f[24];
      uint32_t u[12] = {v0.x, v0.y, v0.z, v0.w, v1.x, v1.y, v1.z, v1.w, v2.x, v2.y, v2.z, v2.w};
#pragma unroll
      for (int j = 0; j < 12; j++) { f[2 * j] = bf_lo(u[j]); f[2 * j + 1] = bf_hi(u[j]); }
      float s = 0.f;
#pragma unroll
      for (int j = 0; j < 24; j++) s += f[j];
#pragma unroll
      for (int o = 16; o; o >>= 1) s += __shfl_xor_sync(~0u, s, o);
      const float mean = s * (1.0f / DM);
      float q = 0.f;
#pragma unroll
      for (int j = 0; j < 16; j++) { float d = f[j] - mean; q += d * d; }
      if (lane < 16) {
#pragma unroll
        for (int j = 16; j < 24; j++) { float d = f[j] - mean; q += d * d; }
      }
#pragma unroll
      for (int o = 16; o; o >>= 1) q += __shfl_xor_sync(~0u, q, o);
      if (lane == 0) g_stat1[row] = ln_finish(mean, q * (1.0f / DM));
    }
  }
  TS_END(0);
}

enum { EPI_QKV = 0, EPI_WO = 1, EPI_GLU = 2, EPI_DOWN = 3 };
template <int N> struct WG;
template <> struct WG<128> { static __device__ __forceinline__ void mma(float (&d)[64], uint64_t a, uint64_t b, int s) { wgmma_ss_n128(d, a, b, s); } };
template <> struct WG<192> { static __device__ __forceinline__ void mma(float (&d)[96], uint64_t a, uint64_t b, int s) { wgmma_ss_n192(d, a, b, s); } };

template <int BM, int BN, int NB, int STAGES> struct GemmCfg {
  static constexpr int A_BYTES = BM * 128;
  static constexpr int B_BYTES = NB * (BN / 64) * 8192;
  static constexpr int STAGE_BYTES = A_BYTES + B_BYTES;
  static constexpr int SMEM = STAGES * STAGE_BYTES + 1024   + 256   + 4096  ;
};

constexpr float QSCALE = 0.22360679774997896f * 1.4426950408889634f;

template <int BM, int BN, int NB, int KDIM, int STAGES, int EPI, int MINB, int CN, int CM>
__global__ void __launch_bounds__(EPI == EPI_GLU ? 384 : 288, MINB) gemm_kernel(const __grid_constant__ CUtensorMap tmA, const __grid_constant__ CUtensorMap tmB0,
                                                         const __grid_constant__ CUtensorMap tmB1,
                                                         const __nv_bfloat16* __restrict__ resid, __nv_bfloat16* __restrict__ out) {
  using Cfg = GemmCfg<BM, BN, NB, STAGES>;
  constexpr int MB = BM / 128;
  constexpr int KT = KDIM / 64;
  extern __shared__ uint8_t smem_raw[];
  const uint32_t sbase = (smem_u32(smem_raw) + 1023u) & ~1023u;
  uint8_t* sptr = smem_raw + (sbase - smem_u32(smem_raw));
  const uint32_t sbar = sbase + STAGES * Cfg::STAGE_BYTES;
  const int tid = threadIdx.x, warp = tid >> 5, lane = tid & 31;
  const int n0 = blockIdx.x * BN, m0 = blockIdx.y * BM;
  TS_BEGIN(EPI == EPI_QKV ? 1 : EPI + 2);
  constexpr int NCL = CN + CM - 1;
  const int cx = blockIdx.x % CN, cy = blockIdx.y % CM;
  if (tid == 0) {
    for (int i = 0; i < STAGES; i++) { mbar_init(sbar + 8 * i, 1); mbar_init(sbar + 8 * (STAGES + i), 2 * NCL); }
    asm volatile("fence.mbarrier_init.release.cluster;" ::: "memory");
  }
  __syncthreads();
  if constexpr (CN * CM > 1) { cluster_arrive(); cluster_wait(); }
  pdl_launch();
  if (warp >= 8) {
    if constexpr (EPI == EPI_GLU) asm volatile("setmaxnreg.dec.sync.aligned.u32 40;");
    if (warp == 8 && lane == 0) {
      auto load_a = [&](int kt, int s) { tma_2d(sbase + s * Cfg::STAGE_BYTES, &tmA, kt * 64, m0, sbar + 8 * s); };
      auto load_b = [&](int kt, int s) {
        const uint32_t sb = sbase + s * Cfg::STAGE_BYTES + Cfg::A_BYTES;
        tma_3d(sb, &tmB0, 0, kt * 64, blockIdx.x * (BN / 64), sbar + 8 * s);
        if constexpr (NB == 2) tma_3d(sb + (BN / 64) * 8192, &tmB1, 0, kt * 64, blockIdx.x * (BN / 64), sbar + 8 * s);
      };
      for (int s = 0; s < STAGES; s++) { mbar_expect_tx(sbar + 8 * s, Cfg::STAGE_BYTES); if (EPI != EPI_QKV || s == 0) load_b(s, s); }
      if (EPI != EPI_QKV) pdl_wait();
      for (int s = 0; s < STAGES; s++) { load_a(s, s); if (EPI == EPI_QKV && s > 0) load_b(s, s); }
      for (int kt = STAGES; kt < KT; kt++) {
        const int s = kt % STAGES;
        mbar_wait(sbar + 8 * (STAGES + s), ((kt / STAGES) - 1) & 1);
        mbar_expect_tx(sbar + 8 * s, Cfg::STAGE_BYTES);
        load_a(kt, s);
        load_b(kt, s);
      }
    }
    if constexpr (EPI == EPI_GLU) {
      if (warp > 8) {
        float2* s_st = (float2*)(sptr + STAGES * Cfg::STAGE_BYTES + 256);
        float* s_cs = (float*)(sptr + STAGES * Cfg::STAGE_BYTES + 256 + 1024);
        pdl_wait();
        for (int r = tid - 288; r < BM; r += 96) {
          const float2* pp = &g_part2[(m0 + r) * 8];
          float s = 0.f;
#pragma unroll
          for (int i = 0; i < 8; i++) s += pp[i].x;
          const float mean = s * (1.0f / DM);
          float q = 0.f;
#pragma unroll
          for (int i = 0; i < 8; i++) { const float2 p = pp[i]; const float d = p.x * (1.0f / 80.f) - mean; q += p.y + 80.f * d * d; }
          s_st[r] = ln_finish(mean, q * (1.0f / DM));
        }
        for (int c = tid - 288; c < BN; c += 96) { s_cs[c] = g_cs_g[n0 + c]; s_cs[BN + c] = g_cs_u[n0 + c]; }
        __threadfence_block();
        asm volatile("bar.arrive 2, 352;" ::: "memory");
      }
    }
    if constexpr (CN * CM > 1) { __syncwarp(); cluster_arrive(); cluster_wait(); }
    return;
  }
  if constexpr (EPI == EPI_GLU) asm volatile("setmaxnreg.inc.sync.aligned.u32 232;");
  const int wg = warp >> 2, g = lane >> 2, t = lane & 3;
  float acc[MB][NB][BN / 2];
#pragma unroll
  for (int mb = 0; mb < MB; mb++)
#pragma unroll
    for (int nb = 0; nb < NB; nb++)
#pragma unroll
      for (int i = 0; i < BN / 2; i++) acc[mb][nb][i] = 0.f;
  for (int kt = 0; kt < KT; kt++) {
    const int s = kt % STAGES;
    mbar_wait(sbar + 8 * s, (kt / STAGES) & 1);
    if (kt == 0) TS_MID(EPI == EPI_QKV ? 1 : EPI + 2, 0);
    const uint32_t sa = sbase + s * Cfg::STAGE_BYTES + wg * (MB * 64 * 128);
    const uint32_t sb = sbase + s * Cfg::STAGE_BYTES + Cfg::A_BYTES;
    wgmma_fence();
#pragma unroll
    for (int ks = 0; ks < 4; ks++) {
#pragma unroll
      for (int mb = 0; mb < MB; mb++) {
        const uint64_t da = make_desc(sa + mb * 8192 + ks * 32, 16, 1024, 1);
#pragma unroll
        for (int nb = 0; nb < NB; nb++) {
          const uint64_t db = make_desc(sb + nb * (BN / 64) * 8192 + ks * 2048, 8192, 1024, 1);
          WG<BN>::mma(acc[mb][nb], da, db, 1);
        }
      }
    }
    wgmma_commit();
    wgmma_wait<1>();
    if (kt > 0 && kt - 1 + STAGES < KT && (tid & 127) < NCL) {
      const uint32_t eb = sbar + 8 * (STAGES + (kt - 1) % STAGES);
      if constexpr (CN * CM > 1) {
        const int i = tid & 127;
        const uint32_t rank = i < CN ? cy * CN + i : ((i - CN + (i - CN >= cy ? 1 : 0)) * CN + cx);
        mbar_arrive_remote(eb, rank);
      } else mbar_arrive(eb);
    }
  }
  wgmma_wait<0>();
#pragma unroll
  for (int mb = 0; mb < MB; mb++)
#pragma unroll
    for (int nb = 0; nb < NB; nb++)
#pragma unroll
      for (int i = 0; i < BN / 2; i++) asm volatile("" : "+f"(acc[mb][nb][i]) :: "memory");
  if constexpr (CN * CM > 1) cluster_arrive();
  TS_MID(EPI == EPI_QKV ? 1 : EPI + 2, 1);
  pdl_wait();
  TS_MID(EPI == EPI_QKV ? 1 : EPI + 2, 2);
  named_bar(1, 256);
  constexpr int LDS = BN * 2 + 16;
  const int ctid = tid;

  if constexpr (EPI == EPI_QKV) {
    const int sec = n0 / DM;
#pragma unroll
    for (int mb = 0; mb < MB; mb++) {
      const int r0 = wg * (MB * 64) + mb * 64 + (warp & 3) * 16 + g;
      const float2 st0 = g_stat1[m0 + r0], st1 = g_stat1[m0 + r0 + 8];
      const float sc0 = sec == 0 ? st0.y * QSCALE : st0.y, sc1 = sec == 0 ? st1.y * QSCALE : st1.y;
#pragma unroll
      for (int j = 0; j < BN / 8; j++) {
        const float2 cs = *(const float2*)&g_cs_qkv[n0 + j * 8 + 2 * t];
        const float* a = &acc[mb][0][4 * j];
        *(uint32_t*)(sptr + r0 * LDS + j * 16 + t * 4) = pack_bf16((a[0] - st0.x * cs.x) * sc0, (a[1] - st0.x * cs.y) * sc0);
        *(uint32_t*)(sptr + (r0 + 8) * LDS + j * 16 + t * 4) = pack_bf16((a[2] - st1.x * cs.x) * sc1, (a[3] - st1.x * cs.y) * sc1);
      }
    }
    named_bar(1, 256);
    if (sec == 0) {
#pragma unroll
      for (int i = 0; i < BM * (BN / 8) / 256; i++) {
        const int idx = i * 256 + ctid, r = idx / (BN / 8), c = idx % (BN / 8);
        *(uint4*)(g_q + (size_t)(m0 + r) * DM + n0 + c * 8) = *(const uint4*)(sptr + r * LDS + c * 16);
      }
    } else {
      __nv_bfloat16* dst = sec == 1 ? g_k : g_v;
      const int cbase = n0 - sec * DM;
#pragma unroll 4
      for (int i = 0; i < BM * (BN / 4) / 256; i++) {
        const int idx = i * 256 + ctid;
        const int half = idx & 1, r8 = (idx >> 1) & 7, rest = idx >> 4;
        const int pq = rest % (BN / 8), rg = rest / (BN / 8);
        const int r = rg * 8 + r8, cq = pq * 2 + half;
        const int col = cbase + cq * 4, h = col / DH, qd = (col % DH) >> 2;
        const uint2 v = *(const uint2*)(sptr + r * LDS + cq * 8);
        const int j = m0 + r;
        uint8_t* p = (uint8_t*)dst + ((size_t)h * S_LEN * 24 + (j >> 3) * 192 + (qd >> 1) * 64 + (j & 7) * 8 + (qd & 1) * 4) * 2;
        if (qd == 4) *(uint4*)p = make_uint4(v.x, v.y, 0x00003f80u, 0u);
        else *(uint2*)p = v;
      }
      if (sec == 1) {
        __shared__ unsigned int s_kn[8];
        if (ctid < 8) s_kn[ctid] = 0u;
        named_bar(1, 256);
        const int hfirst = cbase / DH, hlast = (cbase + BN - 1) / DH;
        for (int hh = hfirst; hh <= hlast; hh++) {
          const int c_lo = max(hh * DH, cbase) - cbase, c_hi = min(hh * DH + DH, cbase + BN) - cbase;
          float mx = 0.f;
          for (int r = ctid; r < BM; r += 256) {
            float s = 0.f;
            for (int c = c_lo; c < c_hi; c += 4) {
              const uint2 v = *(const uint2*)(sptr + r * LDS + c * 2);
              s += bf_lo(v.x) * bf_lo(v.x) + bf_hi(v.x) * bf_hi(v.x) + bf_lo(v.y) * bf_lo(v.y) + bf_hi(v.y) * bf_hi(v.y);
            }
            mx = (s > mx || s != s) ? s : mx;
          }
          unsigned int mb_ = __float_as_uint(mx) & 0x7fffffffu;
          mb_ = __reduce_max_sync(~0u, mb_);
          if (lane == 0) atomicMax(&s_kn[hh - hfirst], mb_);
        }
        named_bar(1, 256);
        if (ctid <= hlast - hfirst) {
          const int hh = hfirst + ctid;
          const bool starts_here = hh * DH >= cbase, ends_here = hh * DH + DH <= cbase + BN;
          const float v = __uint_as_float(s_kn[ctid]);
          float* o = &g_kn[(blockIdx.y * NH + hh) * 2];
          if (starts_here) { o[0] = v; if (ends_here) o[1] = 0.f; }
          else o[1] = v;
        }
      }
    }
  } else if constexpr (EPI == EPI_WO || EPI == EPI_DOWN) {
    const int r0 = wg * 64 + (warp & 3) * 16 + g;
#pragma unroll
    for (int j = 0; j < BN / 8; j++) {
      const float* a = &acc[0][0][4 * j];
      *(uint32_t*)(sptr + r0 * LDS + j * 16 + t * 4) = pack_bf16(a[0], a[1]);
      *(uint32_t*)(sptr + (r0 + 8) * LDS + j * 16 + t * 4) = pack_bf16(a[2], a[3]);
    }
    named_bar(1, 256);
#pragma unroll
    for (int i = 0; i < BM * (BN / 8) / 256; i++) {
      const int idx = i * 256 + ctid, r = idx / (BN / 8), c = idx % (BN / 8);
      const uint4 a = *(const uint4*)(sptr + r * LDS + c * 16);
      const size_t go = (size_t)(m0 + r) * DM + n0 + c * 8;
      const uint4 b = *(const uint4*)(resid + go);
      uint4 o;
      o.x = pack_bf16(bf_lo(a.x) + bf_lo(b.x), bf_hi(a.x) + bf_hi(b.x));
      o.y = pack_bf16(bf_lo(a.y) + bf_lo(b.y), bf_hi(a.y) + bf_hi(b.y));
      o.z = pack_bf16(bf_lo(a.z) + bf_lo(b.z), bf_hi(a.z) + bf_hi(b.z));
      o.w = pack_bf16(bf_lo(a.w) + bf_lo(b.w), bf_hi(a.w) + bf_hi(b.w));
      *(uint4*)(out + go) = o;
      if constexpr (EPI == EPI_WO) {
        static_assert(BN == 64, "stats assume 8 lanes per row");
        const float f[8] = {bf_lo(o.x), bf_hi(o.x), bf_lo(o.y), bf_hi(o.y), bf_lo(o.z), bf_hi(o.z), bf_lo(o.w), bf_hi(o.w)};
        float s = 0.f;
#pragma unroll
        for (int k = 0; k < 8; k++) s += f[k];
        s += __shfl_xor_sync(~0u, s, 1); s += __shfl_xor_sync(~0u, s, 2); s += __shfl_xor_sync(~0u, s, 4);
        const float mu = s * (1.0f / 64.f);
        float q = 0.f;
#pragma unroll
        for (int k = 0; k < 8; k++) { const float d = f[k] - mu; q += d * d; }
        q += __shfl_xor_sync(~0u, q, 1); q += __shfl_xor_sync(~0u, q, 2); q += __shfl_xor_sync(~0u, q, 4);
        if (c == 0) g_part2[(m0 + r) * 10 + blockIdx.x] = make_float2(s, q);
      }
    }
  } else {
    const int r0 = wg * 64 + (warp & 3) * 16 + g;
    const float2* s_st = (const float2*)(sptr + STAGES * Cfg::STAGE_BYTES + 256);
    const float* s_cs = (const float*)(sptr + STAGES * Cfg::STAGE_BYTES + 256 + 1024);
    named_bar(2, 352);
    float2 st[2] = {s_st[r0], s_st[r0 + 8]};
#pragma unroll
    for (int j = 0; j < BN / 8; j++) {
      const float2 cg = *(const float2*)&s_cs[j * 8 + 2 * t], cu = *(const float2*)&s_cs[BN + j * 8 + 2 * t];
      const float* a = &acc[0][0][4 * j];
      const float* b = &acc[0][1][4 * j];
#pragma unroll
      for (int e = 0; e < 2; e++) {
        const float2 s_ = st[e];
        const uint32_t gp = pack_bf16(fmaf(-s_.x, cg.x, a[2 * e]) * s_.y, fmaf(-s_.x, cg.y, a[2 * e + 1]) * s_.y);
        const uint32_t up = pack_bf16(fmaf(-s_.x, cu.x, b[2 * e]) * s_.y, fmaf(-s_.x, cu.y, b[2 * e + 1]) * s_.y);
        uint32_t r;
        asm("{\n.reg .b32 z;\nmax.bf16x2 z, %1, %3;\nmul.rn.bf16x2 %0, z, %2;\n}" : "=r"(r) : "r"(gp), "r"(up), "r"(0u));
        *(uint32_t*)(sptr + (r0 + 8 * e) * LDS + j * 16 + t * 4) = r;
      }
    }
    named_bar(1, 256);
#pragma unroll
    for (int i = 0; i < BM * (BN / 8) / 256; i++) {
      const int idx = i * 256 + ctid, r = idx / (BN / 8), c = idx % (BN / 8);
      *(uint4*)(out + (size_t)(m0 + r) * DFF + n0 + c * 8) = *(const uint4*)(sptr + r * LDS + c * 16);
    }
  }
  if constexpr (CN * CM > 1) cluster_wait();
  TS_END(EPI == EPI_QKV ? 1 : EPI + 2);
}

constexpr int R_STAGES = 8;
constexpr int R_STAGE_BYTES = 16384 + 5 * 2048;
constexpr int R_BAR_OFF = R_STAGES * R_STAGE_BYTES;
constexpr int R_SMEM = R_BAR_OFF + 256 + 1024;
template <int KDIM, bool STATS>
__global__ void __launch_bounds__(288, 1) gemm_res_kernel(const __grid_constant__ CUtensorMap tmA, const __grid_constant__ CUtensorMap tmB,
                                                          const __nv_bfloat16* __restrict__ resid, __nv_bfloat16* __restrict__ out) {
  constexpr int KT = KDIM / 64;
  extern __shared__ uint8_t smem_raw[];
  const uint32_t sbase = (smem_u32(smem_raw) + 1023u) & ~1023u;
  uint8_t* sptr = smem_raw + (sbase - smem_u32(smem_raw));
  const uint32_t sbar = sbase + R_BAR_OFF;
  const int tid = threadIdx.x, warp = tid >> 5, lane = tid & 31;
  const int n0 = blockIdx.x * 80, m0 = blockIdx.y * 128;
  TS_BEGIN(STATS ? 3 : 5);
  if (tid == 0) {
    for (int i = 0; i < R_STAGES; i++) { mbar_init(sbar + 8 * i, 1); mbar_init(sbar + 8 * (R_STAGES + i), 2); }
    asm volatile("fence.mbarrier_init.release.cluster;" ::: "memory");
  }
  __syncthreads();
  pdl_launch();
  if (warp == 8) {
    if (lane == 0) {
      auto load_b = [&](int kt, int s) { tma_3d(sbase + s * R_STAGE_BYTES + 16384, &tmB, 0, kt * 64, blockIdx.x * 5, sbar + 8 * s); };
      for (int s = 0; s < R_STAGES; s++) { mbar_expect_tx(sbar + 8 * s, R_STAGE_BYTES); if (s < 3) load_b(s, s); }
      pdl_wait();
      for (int s = 0; s < R_STAGES; s++) { tma_2d(sbase + s * R_STAGE_BYTES, &tmA, s * 64, m0, sbar + 8 * s); if (s >= 3) load_b(s, s); }
      for (int kt = R_STAGES; kt < KT; kt++) {
        const int s = kt % R_STAGES;
        mbar_wait(sbar + 8 * (R_STAGES + s), ((kt / R_STAGES) - 1) & 1);
        mbar_expect_tx(sbar + 8 * s, R_STAGE_BYTES);
        tma_2d(sbase + s * R_STAGE_BYTES, &tmA, kt * 64, m0, sbar + 8 * s);
        load_b(kt, s);
      }
    }
    return;
  }
  const int wg = warp >> 2, g = lane >> 2, t = lane & 3;
  pdl_wait();
  uint4 rv[5];
#pragma unroll
  for (int i = 0; i < 5; i++) {
    const int idx = i * 256 + tid, r = idx / 10, c = idx % 10;
    rv[i] = *(const uint4*)(resid + (size_t)(m0 + r) * DM + n0 + c * 8);
  }
  float acc[40];
#pragma unroll
  for (int i = 0; i < 40; i++) acc[i] = 0.f;
  for (int kt = 0; kt < KT; kt++) {
    const int s = kt % R_STAGES;
    mbar_wait(sbar + 8 * s, (kt / R_STAGES) & 1);
    if (kt == 0) TS_MID(STATS ? 3 : 5, 0);
    const uint32_t sa = sbase + s * R_STAGE_BYTES + wg * 8192;
    const uint32_t sb = sbase + s * R_STAGE_BYTES + 16384;
    wgmma_fence();
#pragma unroll
    for (int ks = 0; ks < 4; ks++)
      wgmma_ss_n80(acc, make_desc(sa + ks * 32, 16, 1024, 1), make_desc(sb + ks * 512, 2048, 256, 3), 1);
    wgmma_commit();
    wgmma_wait<1>();
    if (kt > 0 && kt - 1 + R_STAGES < KT && (tid & 127) == 0) mbar_arrive(sbar + 8 * (R_STAGES + (kt - 1) % R_STAGES));
  }
  wgmma_wait<0>();
#pragma unroll
  for (int i = 0; i < 40; i++) asm volatile("" : "+f"(acc[i]) :: "memory");
  TS_MID(STATS ? 3 : 5, 1);
  named_bar(1, 256);
  constexpr int LDS = 176;
  const int r0 = wg * 64 + (warp & 3) * 16 + g;
#pragma unroll
  for (int i = 0; i < 10; i++) {
    *(uint32_t*)(sptr + r0 * LDS + i * 16 + t * 4) = pack_bf16(acc[4 * i], acc[4 * i + 1]);
    *(uint32_t*)(sptr + (r0 + 8) * LDS + i * 16 + t * 4) = pack_bf16(acc[4 * i + 2], acc[4 * i + 3]);
  }
  named_bar(1, 256);
#pragma unroll
  for (int i = 0; i < 5; i++) {
    const int idx = i * 256 + tid, r = idx / 10, c = idx % 10;
    const uint4 a = *(const uint4*)(sptr + r * LDS + c * 16);
    const uint4 b = rv[i];
    uint4 o;
    o.x = pack_bf16(bf_lo(a.x) + bf_lo(b.x), bf_hi(a.x) + bf_hi(b.x));
    o.y = pack_bf16(bf_lo(a.y) + bf_lo(b.y), bf_hi(a.y) + bf_hi(b.y));
    o.z = pack_bf16(bf_lo(a.z) + bf_lo(b.z), bf_hi(a.z) + bf_hi(b.z));
    o.w = pack_bf16(bf_lo(a.w) + bf_lo(b.w), bf_hi(a.w) + bf_hi(b.w));
    *(uint4*)(out + (size_t)(m0 + r) * DM + n0 + c * 8) = o;
    if constexpr (STATS) *(uint4*)(sptr + r * LDS + c * 16) = o;
  }
  TS_MID(STATS ? 3 : 5, 3);
  if constexpr (STATS) {
    named_bar(1, 256);
    const int r = tid >> 1, hf = tid & 1;
    float f[40];
#pragma unroll
    for (int i = 0; i < 5; i++) {
      const uint4 v = *(const uint4*)(sptr + r * LDS + hf * 80 + i * 16);
      f[8 * i] = bf_lo(v.x); f[8 * i + 1] = bf_hi(v.x); f[8 * i + 2] = bf_lo(v.y); f[8 * i + 3] = bf_hi(v.y);
      f[8 * i + 4] = bf_lo(v.z); f[8 * i + 5] = bf_hi(v.z); f[8 * i + 6] = bf_lo(v.w); f[8 * i + 7] = bf_hi(v.w);
    }
    float s = 0.f;
#pragma unroll
    for (int i = 0; i < 40; i++) s += f[i];
    s += __shfl_xor_sync(~0u, s, 1);
    const float mu = s * (1.0f / 80.f);
    float q = 0.f;
#pragma unroll
    for (int i = 0; i < 40; i++) { const float d = f[i] - mu; q += d * d; }
    q += __shfl_xor_sync(~0u, q, 1);
    if (hf == 0) g_part2[(m0 + r) * 8 + blockIdx.x] = make_float2(s, q);
  }
  TS_END(STATS ? 3 : 5);
}

#define POLY_NUM 5
__device__ __forceinline__ float ex2_poly(float x, int shl23) {
  const float MAGIC = 12582912.f;
  const float tt = x + MAGIC;
  const float f = x - (tt - MAGIC);
  float p = fmaf(0.0013276472454890609f, f, 0.009675540961325169f);
  p = fmaf(p, f, 0.05550713092088699f);
  p = fmaf(p, f, 0.24022120237350464f);
  p = fmaf(p, f, 0.6931469440460205f);
  p = fmaf(p, f, 1.0000001192092896f);
  return __int_as_float(__float_as_int(tt) * shl23 + __float_as_int(p));
}
constexpr int KV_BYTES = S_LEN * 48;
constexpr int ATT_SMEM = 2 * KV_BYTES + 256;

__global__ void __launch_bounds__(512, 1) attn_kernel(int shl23, const __nv_bfloat16* __restrict__ wg_, const __nv_bfloat16* __restrict__ wu_,
                                                      const __nv_bfloat16* __restrict__ wo_, const __nv_bfloat16* __restrict__ wd_) {
  extern __shared__ __align__(1024) uint8_t smem[];
  if (blockIdx.x >= 128) {
    pdl_launch();
    const int e = blockIdx.x - 128, half = threadIdx.x >> 8;
    if (threadIdx.x == 0) {
      for (int i = 0; i < 13; i++) asm volatile("cp.async.bulk.prefetch.L2.global [%0], %1;" :: "l"((const uint8_t*)wo_ + (e * 13 + i) * 16384 * 0 + (size_t)(e * 13 + i >= 50 ? 0 : (e * 13 + i)) * 16384), "r"(16384));
      for (int i = 0; i < 30; i++) asm volatile("cp.async.bulk.prefetch.L2.global [%0], %1;" :: "l"((const uint8_t*)wd_ + (size_t)(e * 30 + i) * 16384), "r"(16384));
    }
    float (*red)[65] = (float (*)[65])(smem + half * 16384);
    for (int b = e * 12 + half; b < e * 12 + 12; b += 2) {
      if (b < 24) colsum64(wg_, DFF, b * 64, g_cs_g, red, threadIdx.x & 255, 1 + half);
      else colsum64(wu_, DFF, (b - 24) * 64, g_cs_u, red, threadIdx.x & 255, 1 + half);
    }
    return;
  }
  const int h = blockIdx.x >> 2, qb = blockIdx.x & 3;
  const uint32_t sK = smem_u32(smem), sV = sK + KV_BYTES, sBar = sV + KV_BYTES;
  const int tid = threadIdx.x;
  TS_BEGIN(2);
  if (tid == 0) {
    for (int i = 0; i < 8; i++) mbar_init(sBar + 8 * i, 1);
    asm volatile("fence.mbarrier_init.release.cluster;" ::: "memory");
  }
  pdl_launch();
  pdl_wait();
  if (tid == 0) {
    const uint8_t* gk = (const uint8_t*)(g_k + (size_t)h * S_LEN * 24);
    const uint8_t* gv = (const uint8_t*)(g_v + (size_t)h * S_LEN * 24);
    for (int i = 0; i < 8; i++) {
      mbar_expect_tx(sBar + 8 * i, 2 * 12288);
      bulk_g2s(sK + i * 12288, gk + i * 12288, 12288, sBar + 8 * i);
      bulk_g2s(sV + i * 12288, gv + i * 12288, 12288, sBar + 8 * i);
    }
  }
  __syncthreads();
  const int wg = tid >> 7, warp = (tid >> 5) & 3, lane = tid & 31, g = lane >> 2, t = lane & 3;
  float ka = 0.f, kb = 0.f;
#pragma unroll
  for (int i = 0; i < 8; i++) {
    const float2 v = *(const float2*)&g_kn[(i * NH + h) * 2];
    ka = (v.x > ka || v.x != v.x) ? v.x : ka;
    kb = (v.y > kb || v.y != v.y) ? v.y : kb;
  }
  const float kn = sqrtf(ka + kb);
  for (int it = 0; it < 2; it++) {
    const int q0 = qb * 512 + (it * 4 + wg) * 64 + warp * 16;
    uint32_t qa[4], qc[4];
    const uint32_t* qr0 = (const uint32_t*)(g_q + (size_t)(q0 + g) * DM + h * DH);
    const uint32_t* qr1 = (const uint32_t*)(g_q + (size_t)(q0 + g + 8) * DM + h * DH);
    qa[0] = qr0[t]; qa[1] = qr1[t]; qa[2] = qr0[t + 4]; qa[3] = qr1[t + 4];
    qc[0] = (t < 2) ? qr0[t + 8] : 0u; qc[1] = (t < 2) ? qr1[t + 8] : 0u; qc[2] = 0; qc[3] = 0;
    auto sq = [](uint32_t u) { const float a = bf_lo(u), b = bf_hi(u); return a * a + b * b; };
    float n0 = sq(qa[0]) + sq(qa[2]) + sq(qc[0]);
    float n1 = sq(qa[1]) + sq(qa[3]) + sq(qc[1]);
    n0 += __shfl_xor_sync(~0u, n0, 1); n0 += __shfl_xor_sync(~0u, n0, 2);
    n1 += __shfl_xor_sync(~0u, n1, 1); n1 += __shfl_xor_sync(~0u, n1, 2);
    const float m0 = ceilf(sqrtf(n0) * kn * 1.001f) + 1.f, m1 = ceilf(sqrtf(n1) * kn * 1.001f) + 1.f;
    const bool unsafe = !(m0 <= 62.f && m1 <= 62.f);
    uint32_t any_unsafe;
    asm volatile("{\n.reg .pred p, q;\nsetp.ne.u32 p, %1, 0;\nbarrier.cta.red.or.pred q, %2, 128, p;\nselp.u32 %0, 1, 0, q;\n}"
                 : "=r"(any_unsafe) : "r"((uint32_t)unsafe), "r"(1 + wg) : "memory");
    float O[12];
    float S[32];
    if (!__any_sync(~0u, any_unsafe)) {
      if (t == 2) { qc[0] = pack_bf16(-m0, 0.f); qc[1] = pack_bf16(-m1, 0.f); }
      for (int j = 0; j < 32; j++) {
        if (it == 0 && (j & 3) == 0) mbar_wait(sBar + 8 * (j >> 2), 0);
        const uint64_t dk = make_desc(sK + j * 8 * 384, 128, 384, 0);
        wgmma_fence();
        wgmma_rs_n64(S, qa[0], qa[1], qa[2], qa[3], dk, 0);
        wgmma_rs_n64(S, qc[0], qc[1], qc[2], qc[3], dk + (256 >> 4), 1);
        wgmma_commit();
        wgmma_wait<0>();
        uint32_t P[16];
#pragma unroll
        for (int i = 0; i < 16; i++) {
          const bool usepoly = ((i + 1) * POLY_NUM / 16) != (i * POLY_NUM / 16);
          float a, b;
          if (usepoly) { a = ex2_poly(S[2 * i], shl23); b = ex2_poly(S[2 * i + 1], shl23); }
          else { a = ex2_mufu(S[2 * i]); b = ex2_mufu(S[2 * i + 1]); }
          P[i] = pack_bf16(a, b);
        }
        wgmma_fence();
        const uint64_t dv = make_desc(sV + j * 8 * 384, 384, 128, 0);
#pragma unroll
        for (int ks = 0; ks < 4; ks++)
          wgmma_rs_n24_tb(O, P[4 * ks], P[4 * ks + 1], P[4 * ks + 2], P[4 * ks + 3], dv + ((ks * 768) >> 4), (j | ks) != 0);
        wgmma_commit();
      }
    } else {
      float mx0 = -INFINITY, mx1 = -INFINITY;
      for (int j = 0; j < 32; j++) {
        if (it == 0 && (j & 3) == 0) mbar_wait(sBar + 8 * (j >> 2), 0);
        const uint64_t dk = make_desc(sK + j * 8 * 384, 128, 384, 0);
        wgmma_fence();
        wgmma_rs_n64(S, qa[0], qa[1], qa[2], qa[3], dk, 0);
        wgmma_rs_n64(S, qc[0], qc[1], qc[2], qc[3], dk + (256 >> 4), 1);
        wgmma_commit();
        wgmma_wait<0>();
#pragma unroll
        for (int i = 0; i < 8; i++) {
          mx0 = fmaxf(mx0, fmaxf(S[4 * i], S[4 * i + 1]));
          mx1 = fmaxf(mx1, fmaxf(S[4 * i + 2], S[4 * i + 3]));
        }
      }
      mx0 = fmaxf(mx0, __shfl_xor_sync(~0u, mx0, 1)); mx0 = fmaxf(mx0, __shfl_xor_sync(~0u, mx0, 2));
      mx1 = fmaxf(mx1, __shfl_xor_sync(~0u, mx1, 1)); mx1 = fmaxf(mx1, __shfl_xor_sync(~0u, mx1, 2));
      for (int j = 0; j < 32; j++) {
        const uint64_t dk = make_desc(sK + j * 8 * 384, 128, 384, 0);
        wgmma_fence();
        wgmma_rs_n64(S, qa[0], qa[1], qa[2], qa[3], dk, 0);
        wgmma_rs_n64(S, qc[0], qc[1], qc[2], qc[3], dk + (256 >> 4), 1);
        wgmma_commit();
        wgmma_wait<0>();
        uint32_t P[16];
#pragma unroll
        for (int i = 0; i < 8; i++) {
          P[2 * i] = pack_bf16(ex2_mufu(S[4 * i] - mx0), ex2_mufu(S[4 * i + 1] - mx0));
          P[2 * i + 1] = pack_bf16(ex2_mufu(S[4 * i + 2] - mx1), ex2_mufu(S[4 * i + 3] - mx1));
        }
        wgmma_fence();
        const uint64_t dv = make_desc(sV + j * 8 * 384, 384, 128, 0);
#pragma unroll
        for (int ks = 0; ks < 4; ks++)
          wgmma_rs_n24_tb(O, P[4 * ks], P[4 * ks + 1], P[4 * ks + 2], P[4 * ks + 3], dv + ((ks * 768) >> 4), (j | ks) != 0);
        wgmma_commit();
      }
    }
    wgmma_wait<0>();
#pragma unroll
    for (int i = 0; i < 12; i++) asm volatile("" : "+f"(O[i]) :: "memory");
    const float l0 = __shfl_sync(~0u, O[8], (lane & ~3) | 2), l1 = __shfl_sync(~0u, O[10], (lane & ~3) | 2);
    const float r0 = 1.f / l0, r1 = 1.f / l1;
    uint32_t* o0 = (uint32_t*)(g_o + (size_t)(q0 + g) * DM + h * DH);
    uint32_t* o1 = (uint32_t*)(g_o + (size_t)(q0 + g + 8) * DM + h * DH);
    o0[t] = pack_bf16(O[0] * r0, O[1] * r0); o1[t] = pack_bf16(O[2] * r1, O[3] * r1);
    o0[t + 4] = pack_bf16(O[4] * r0, O[5] * r0); o1[t + 4] = pack_bf16(O[6] * r1, O[7] * r1);
    if (t < 2) { o0[t + 8] = pack_bf16(O[8] * r0, O[9] * r0); o1[t + 8] = pack_bf16(O[10] * r1, O[11] * r1); }
  }
  TS_END(2);
}

typedef CUresult (*EncodeFn)(CUtensorMap*, CUtensorMapDataType, cuuint32_t, void*, const cuuint64_t*, const cuuint64_t*, const cuuint32_t*,
                             const cuuint32_t*, CUtensorMapInterleave, CUtensorMapSwizzle, CUtensorMapL2promotion, CUtensorMapFloatOOBfill);
static EncodeFn get_encode() {
  static EncodeFn fn = nullptr;
  if (!fn) {
    void* p = nullptr; cudaDriverEntryPointQueryResult st;
    cudaGetDriverEntryPoint("cuTensorMapEncodeTiled", &p, cudaEnableDefault, &st);
    fn = (EncodeFn)p;
  }
  return fn;
}
static CUtensorMap make_map(const void* ptr, int rows, int cols, int box_rows, int box_cols = 64) {
  CUtensorMap m;
  cuuint64_t dims[2] = {(cuuint64_t)cols, (cuuint64_t)rows};
  cuuint64_t strides[1] = {(cuuint64_t)cols * 2};
  cuuint32_t box[2] = {(cuuint32_t)box_cols, (cuuint32_t)box_rows};
  cuuint32_t es[2] = {1, 1};
  get_encode()(&m, CU_TENSOR_MAP_DATA_TYPE_BFLOAT16, 2, const_cast<void*>(ptr), dims, strides, box, es, CU_TENSOR_MAP_INTERLEAVE_NONE,
               box_cols == 64 ? CU_TENSOR_MAP_SWIZZLE_128B : (box_cols == 32 ? CU_TENSOR_MAP_SWIZZLE_64B : CU_TENSOR_MAP_SWIZZLE_32B), CU_TENSOR_MAP_L2_PROMOTION_L2_128B, CU_TENSOR_MAP_FLOAT_OOB_FILL_NONE);
  return m;
}
static CUtensorMap make_map_w(const void* ptr, int rows, int cols, int bc, int nblk) {
  CUtensorMap m;
  cuuint64_t dims[3] = {(cuuint64_t)bc, (cuuint64_t)rows, (cuuint64_t)(cols / bc)};
  cuuint64_t strides[2] = {(cuuint64_t)cols * 2, (cuuint64_t)bc * 2};
  cuuint32_t box[3] = {(cuuint32_t)bc, 64, (cuuint32_t)nblk};
  cuuint32_t es[3] = {1, 1, 1};
  get_encode()(&m, CU_TENSOR_MAP_DATA_TYPE_BFLOAT16, 3, const_cast<void*>(ptr), dims, strides, box, es, CU_TENSOR_MAP_INTERLEAVE_NONE,
               bc == 64 ? CU_TENSOR_MAP_SWIZZLE_128B : (bc == 32 ? CU_TENSOR_MAP_SWIZZLE_64B : CU_TENSOR_MAP_SWIZZLE_32B),
               CU_TENSOR_MAP_L2_PROMOTION_L2_128B, CU_TENSOR_MAP_FLOAT_OOB_FILL_NONE);
  return m;
}
template <typename... KArgs, typename... Args>
static void launch(void (*kern)(KArgs...), dim3 grid, dim3 block, size_t smem, bool pdl, dim3 cluster, Args... args) {
  cudaLaunchConfig_t cfg = {};
  cfg.gridDim = grid; cfg.blockDim = block; cfg.dynamicSmemBytes = smem; cfg.stream = cudaStreamPerThread;
  cudaLaunchAttribute at[2];
  int na = 0;
  if (pdl) { at[na].id = cudaLaunchAttributeProgrammaticStreamSerialization; at[na].val.programmaticStreamSerializationAllowed = 1; na++; }
  if (cluster.x * cluster.y > 1) { at[na].id = cudaLaunchAttributeClusterDimension; at[na].val.clusterDim.x = cluster.x; at[na].val.clusterDim.y = cluster.y; at[na].val.clusterDim.z = 1; na++; }
  cfg.attrs = at; cfg.numAttrs = na;
  cudaLaunchKernelEx(&cfg, kern, KArgs(args)...);
}

extern "C" void kernel_launch(void* const* d_in, const int* in_sizes, int n_in, void* d_out, int out_size) {
  const __nv_bfloat16* x = (const __nv_bfloat16*)d_in[0];
  const __nv_bfloat16* wqkv = (const __nv_bfloat16*)d_in[1];
  const __nv_bfloat16* wo = (const __nv_bfloat16*)d_in[2];
  const __nv_bfloat16* wgate = (const __nv_bfloat16*)d_in[4];
  const __nv_bfloat16* wup = (const __nv_bfloat16*)d_in[5];
  const __nv_bfloat16* wdown = (const __nv_bfloat16*)d_in[6];
  __nv_bfloat16* out = (__nv_bfloat16*)d_out;
  void *p_o, *p_h, *p_act;
  cudaGetSymbolAddress(&p_o, g_o); cudaGetSymbolAddress(&p_h, g_h); cudaGetSymbolAddress(&p_act, g_act);

#define A_CN 1
#define A_CM 1
#define D_CN 1
#define D_CM 1
  auto kA = gemm_kernel<256, 128, 1, DM, 4, EPI_QKV, 1, A_CN, A_CM>;
  auto kC = gemm_res_kernel<DM, true>;
  auto kD = gemm_kernel<128, 192, 2, DM, 3, EPI_GLU, 1, D_CN, D_CM>;
  auto kE = gemm_res_kernel<DFF, false>;
  constexpr int smA = GemmCfg<256, 128, 1, 4>::SMEM, smC = R_SMEM, smD = GemmCfg<128, 192, 2, 3>::SMEM;
  cudaFuncSetAttribute(kA, cudaFuncAttributeMaxDynamicSharedMemorySize, smA);
  cudaFuncSetAttribute(kC, cudaFuncAttributeMaxDynamicSharedMemorySize, smC);
  cudaFuncSetAttribute(kD, cudaFuncAttributeMaxDynamicSharedMemorySize, smD);
  cudaFuncSetAttribute(kE, cudaFuncAttributeMaxDynamicSharedMemorySize, smC);
  cudaFuncSetAttribute(attn_kernel, cudaFuncAttributeMaxDynamicSharedMemorySize, ATT_SMEM);

  const CUtensorMap tm_x = make_map(x, S_LEN, DM, 256), tm_wqkv = make_map_w(wqkv, DM, 3 * DM, 64, 2);
  const CUtensorMap tm_o = make_map(p_o, S_LEN, DM, 128), tm_wo = make_map_w(wo, DM, DM, 16, 5);
  const CUtensorMap tm_h = make_map(p_h, S_LEN, DM, 128), tm_wg = make_map_w(wgate, DM, DFF, 64, 3), tm_wu = make_map_w(wup, DM, DFF, 64, 3);
  const CUtensorMap tm_act = make_map(p_act, S_LEN, DFF, 128), tm_wd = make_map_w(wdown, DFF, DM, 16, 5);

  launch(pre_kernel, dim3(PRE_COL_BLOCKS + PRE_ROW_BLOCKS), dim3(256), 0, false, dim3(1, 1), x, wqkv);
  launch(kA, dim3(15, 8), dim3(288), smA, true, dim3(A_CN, A_CM), tm_x, tm_wqkv, tm_wqkv, (const __nv_bfloat16*)nullptr, (__nv_bfloat16*)nullptr);
  launch(attn_kernel, dim3(132), dim3(512), ATT_SMEM, true, dim3(1, 1), 0x800000, wgate, wup, wo, wdown);
  launch(kC, dim3(8, 16), dim3(288), smC, true, dim3(1, 1), tm_o, tm_wo, x, (__nv_bfloat16*)p_h);
  launch(kD, dim3(8, 16), dim3(384), smD, true, dim3(D_CN, D_CM), tm_h, tm_wg, tm_wu, (const __nv_bfloat16*)nullptr, (__nv_bfloat16*)p_act);
  launch(kE, dim3(8, 16), dim3(288), smC, true, dim3(1, 1), tm_act, tm_wd, (const __nv_bfloat16*)p_h, out);
}
```

```cpp
#include <cuda_runtime.h>
#include <cuda_bf16.h>
#include <cuda.h>
#include <stdint.h>

constexpr int S_LEN = 2048, DM = 640, NH = 32, DH = 20, DFF = 1536;

__device__ __align__(1024) __nv_bfloat16 g_q[S_LEN * DM];
__device__ __align__(1024) __nv_bfloat16 g_k[NH * S_LEN * 24];
__device__ __align__(1024) __nv_bfloat16 g_v[NH * S_LEN * 24];
__device__ __align__(1024) __nv_bfloat16 g_o[S_LEN * DM];
__device__ __align__(1024) __nv_bfloat16 g_h[S_LEN * DM];
__device__ __align__(1024) __nv_bfloat16 g_act[S_LEN * DFF];
__device__ float g_kn[8 * NH * 2];
__device__ float2 g_stat1[S_LEN];
__device__ float g_cs_qkv[3 * DM];
__device__ float g_cs_g[DFF];
__device__ float g_cs_u[DFF];
__device__ float2 g_part2[S_LEN * 10];

#define TS_BEGIN(k)
#define TS_END(k)
#define TS_MID(k, i)
__device__ __forceinline__ uint32_t smem_u32(const void* p) { return (uint32_t)__cvta_generic_to_shared(p); }
__device__ __forceinline__ void mbar_init(uint32_t bar, uint32_t cnt) { asm volatile("mbarrier.init.shared::cta.b64 [%0], %1;" :: "r"(bar), "r"(cnt)); }
__device__ __forceinline__ void mbar_expect_tx(uint32_t bar, uint32_t bytes) { asm volatile("mbarrier.arrive.expect_tx.shared::cta.b64 _, [%0], %1;" :: "r"(bar), "r"(bytes) : "memory"); }
__device__ __forceinline__ void mbar_arrive(uint32_t bar) { asm volatile("mbarrier.arrive.shared::cta.b64 _, [%0];" :: "r"(bar) : "memory"); }
__device__ __forceinline__ void mbar_wait(uint32_t bar, uint32_t parity) {
  uint32_t done;
  uint32_t spins = 0;
  do {
    asm volatile("{\n.reg .pred P1;\nmbarrier.try_wait.parity.shared::cta.b64 P1, [%1], %2;\nselp.u32 %0, 1, 0, P1;\n}" : "=r"(done) : "r"(bar), "r"(parity) : "memory");
  } while (!done && ++spins < (1u << 24));
}
__device__ __forceinline__ void bulk_g2s(uint32_t dst, const void* src, uint32_t bytes, uint32_t bar) {
  asm volatile("cp.async.bulk.shared::cluster.global.mbarrier::complete_tx::bytes [%0], [%1], %2, [%3];" :: "r"(dst), "l"(src), "r"(bytes), "r"(bar) : "memory");
}
__device__ __forceinline__ void tma_2d(uint32_t dst, const CUtensorMap* tm, int c0, int c1, uint32_t bar) {
  asm volatile("cp.async.bulk.tensor.2d.shared::cluster.global.mbarrier::complete_tx::bytes [%0], [%1, {%3, %4}], [%2];"
               :: "r"(dst), "l"(tm), "r"(bar), "r"(c0), "r"(c1) : "memory");
}
__device__ __forceinline__ void tma_3d(uint32_t dst, const CUtensorMap* tm, int c0, int c1, int c2, uint32_t bar) {
  asm volatile("cp.async.bulk.tensor.3d.shared::cluster.global.mbarrier::complete_tx::bytes [%0], [%1, {%3, %4, %5}], [%2];"
               :: "r"(dst), "l"(tm), "r"(bar), "r"(c0), "r"(c1), "r"(c2) : "memory");
}
__device__ __forceinline__ void tma_2d_mc(uint32_t dst, const CUtensorMap* tm, int c0, int c1, uint32_t bar, uint16_t mask) {
  asm volatile("cp.async.bulk.tensor.2d.shared::cluster.global.mbarrier::complete_tx::bytes.multicast::cluster [%0], [%1, {%3, %4}], [%2], %5;"
               :: "r"(dst), "l"(tm), "r"(bar), "r"(c0), "r"(c1), "h"(mask) : "memory");
}
__device__ __forceinline__ void mbar_arrive_remote(uint32_t bar, uint32_t rank) {
  asm volatile("{\n.reg .b32 ra;\nmapa.shared::cluster.u32 ra, %0, %1;\nmbarrier.arrive.release.cluster.shared::cluster.b64 _, [ra];\n}" :: "r"(bar), "r"(rank) : "memory");
}
__device__ __forceinline__ void cluster_arrive() { asm volatile("barrier.cluster.arrive.release.aligned;" ::: "memory"); }
__device__ __forceinline__ void cluster_wait() { asm volatile("barrier.cluster.wait.acquire.aligned;" ::: "memory"); }
__device__ __forceinline__ void wgmma_fence() { asm volatile("wgmma.fence.sync.aligned;" ::: "memory"); }
__device__ __forceinline__ void wgmma_commit() { asm volatile("wgmma.commit_group.sync.aligned;" ::: "memory"); }
template <int N> __device__ __forceinline__ void wgmma_wait() { asm volatile("wgmma.wait_group.sync.aligned %0;" :: "n"(N) : "memory"); }
__device__ __forceinline__ void pdl_wait() { asm volatile("griddepcontrol.wait;" ::: "memory"); }
__device__ __forceinline__ void pdl_launch() { asm volatile("griddepcontrol.launch_dependents;" ::: "memory"); }
__device__ __forceinline__ void named_bar(int id, int n) { asm volatile("bar.sync %0, %1;" :: "r"(id), "r"(n) : "memory"); }
__device__ __forceinline__ uint64_t make_desc(uint32_t addr, uint32_t lbo, uint32_t sbo, uint32_t swz) {
  return (uint64_t)((addr & 0x3FFFF) >> 4) | ((uint64_t)(lbo >> 4) << 16) | ((uint64_t)(sbo >> 4) << 32) | ((uint64_t)swz << 62);
}
__device__ __forceinline__ void st_g16(void* p, uint4 v) { asm volatile("st.global.v4.b32 [%0], {%1, %2, %3, %4};" :: "l"(p), "r"(v.x), "r"(v.y), "r"(v.z), "r"(v.w) : "memory"); }
__device__ __forceinline__ void st_g8(void* p, uint2 v) { asm volatile("st.global.v2.b32 [%0], {%1, %2};" :: "l"(p), "r"(v.x), "r"(v.y) : "memory"); }
__device__ __forceinline__ uint4 ld_g16(const void* p) { uint4 v; asm volatile("ld.global.v4.b32 {%0, %1, %2, %3}, [%4];" : "=r"(v.x), "=r"(v.y), "=r"(v.z), "=r"(v.w) : "l"(p) : "memory"); return v; }
__device__ __forceinline__ uint32_t pack_bf16(float lo, float hi) { uint32_t r; asm("cvt.rn.bf16x2.f32 %0, %1, %2;" : "=r"(r) : "f"(hi), "f"(lo)); return r; }
__device__ __forceinline__ float bf_lo(uint32_t u) { return __uint_as_float(u << 16); }
__device__ __forceinline__ float bf_hi(uint32_t u) { return __uint_as_float(u & 0xffff0000u); }
__device__ __forceinline__ float bf_round(float x) { return __bfloat162float(__float2bfloat16_rn(x)); }
__device__ __forceinline__ float ex2_mufu(float x) { float y; asm("ex2.approx.ftz.f32 %0, %1;" : "=f"(y) : "f"(x)); return y; }

__device__ __forceinline__ void wgmma_ss_n80(float (&d)[40], uint64_t da, uint64_t db, int scale_d) {
  asm volatile("{\n.reg .pred p;\nsetp.ne.b32 p, %42, 0;\n"
    "wgmma.mma_async.sync.aligned.m64n80k16.f32.bf16.bf16 {%0,%1,%2,%3,%4,%5,%6,%7,%8,%9,%10,%11,%12,%13,%14,%15,%16,%17,%18,%19,%20,%21,%22,%23,%24,%25,%26,%27,%28,%29,%30,%31,%32,%33,%34,%35,%36,%37,%38,%39}, %40, %41, p, 1, 1, 0, 1;\n}\n"
    : "+f"(d[0]),"+f"(d[1]),"+f"(d[2]),"+f"(d[3]),"+f"(d[4]),"+f"(d[5]),"+f"(d[6]),"+f"(d[7]),"+f"(d[8]),"+f"(d[9]),"+f"(d[10]),"+f"(d[11]),"+f"(d[12]),"+f"(d[13]),"+f"(d[14]),"+f"(d[15]),"+f"(d[16]),"+f"(d[17]),"+f"(d[18]),"+f"(d[19]),"+f"(d[20]),"+f"(d[21]),"+f"(d[22]),"+f"(d[23]),"+f"(d[24]),"+f"(d[25]),"+f"(d[26]),"+f"(d[27]),"+f"(d[28]),"+f"(d[29]),"+f"(d[30]),"+f"(d[31]),"+f"(d[32]),"+f"(d[33]),"+f"(d[34]),"+f"(d[35]),"+f"(d[36]),"+f"(d[37]),"+f"(d[38]),"+f"(d[39])
    : "l"(da), "l"(db), "r"(scale_d));
}
__device__ __forceinline__ void wgmma_ss_n128(float (&d)[64], uint64_t da, uint64_t db, int scale_d) {
  asm volatile("{\n.reg .pred p;\nsetp.ne.b32 p, %66, 0;\n"
    "wgmma.mma_async.sync.aligned.m64n128k16.f32.bf16.bf16 {%0,%1,%2,%3,%4,%5,%6,%7,%8,%9,%10,%11,%12,%13,%14,%15,%16,%17,%18,%19,%20,%21,%22,%23,%24,%25,%26,%27,%28,%29,%30,%31,%32,%33,%34,%35,%36,%37,%38,%39,%40,%41,%42,%43,%44,%45,%46,%47,%48,%49,%50,%51,%52,%53,%54,%55,%56,%57,%58,%59,%60,%61,%62,%63}, %64, %65, p, 1, 1, 0, 1;\n}\n"
    : "+f"(d[0]),"+f"(d[1]),"+f"(d[2]),"+f"(d[3]),"+f"(d[4]),"+f"(d[5]),"+f"(d[6]),"+f"(d[7]),"+f"(d[8]),"+f"(d[9]),"+f"(d[10]),"+f"(d[11]),"+f"(d[12]),"+f"(d[13]),"+f"(d[14]),"+f"(d[15]),"+f"(d[16]),"+f"(d[17]),"+f"(d[18]),"+f"(d[19]),"+f"(d[20]),"+f"(d[21]),"+f"(d[22]),"+f"(d[23]),"+f"(d[24]),"+f"(d[25]),"+f"(d[26]),"+f"(d[27]),"+f"(d[28]),"+f"(d[29]),"+f"(d[30]),"+f"(d[31]),"+f"(d[32]),"+f"(d[33]),"+f"(d[34]),"+f"(d[35]),"+f"(d[36]),"+f"(d[37]),"+f"(d[38]),"+f"(d[39]),"+f"(d[40]),"+f"(d[41]),"+f"(d[42]),"+f"(d[43]),"+f"(d[44]),"+f"(d[45]),"+f"(d[46]),"+f"(d[47]),"+f"(d[48]),"+f"(d[49]),"+f"(d[50]),"+f"(d[51]),"+f"(d[52]),"+f"(d[53]),"+f"(d[54]),"+f"(d[55]),"+f"(d[56]),"+f"(d[57]),"+f"(d[58]),"+f"(d[59]),"+f"(d[60]),"+f"(d[61]),"+f"(d[62]),"+f"(d[63])
    : "l"(da), "l"(db), "r"(scale_d));
}
__device__ __forceinline__ void wgmma_ss_n192(float (&d)[96], uint64_t da, uint64_t db, int scale_d) {
  asm volatile("{\n.reg .pred p;\nsetp.ne.b32 p, %98, 0;\n"
    "wgmma.mma_async.sync.aligned.m64n192k16.f32.bf16.bf16 {%0,%1,%2,%3,%4,%5,%6,%7,%8,%9,%10,%11,%12,%13,%14,%15,%16,%17,%18,%19,%20,%21,%22,%23,%24,%25,%26,%27,%28,%29,%30,%31,%32,%33,%34,%35,%36,%37,%38,%39,%40,%41,%42,%43,%44,%45,%46,%47,%48,%49,%50,%51,%52,%53,%54,%55,%56,%57,%58,%59,%60,%61,%62,%63,%64,%65,%66,%67,%68,%69,%70,%71,%72,%73,%74,%75,%76,%77,%78,%79,%80,%81,%82,%83,%84,%85,%86,%87,%88,%89,%90,%91,%92,%93,%94,%95}, %96, %97, p, 1, 1, 0, 1;\n}\n"
    : "+f"(d[0]),"+f"(d[1]),"+f"(d[2]),"+f"(d[3]),"+f"(d[4]),"+f"(d[5]),"+f"(d[6]),"+f"(d[7]),"+f"(d[8]),"+f"(d[9]),"+f"(d[10]),"+f"(d[11]),"+f"(d[12]),"+f"(d[13]),"+f"(d[14]),"+f"(d[15]),"+f"(d[16]),"+f"(d[17]),"+f"(d[18]),"+f"(d[19]),"+f"(d[20]),"+f"(d[21]),"+f"(d[22]),"+f"(d[23]),"+f"(d[24]),"+f"(d[25]),"+f"(d[26]),"+f"(d[27]),"+f"(d[28]),"+f"(d[29]),"+f"(d[30]),"+f"(d[31]),"+f"(d[32]),"+f"(d[33]),"+f"(d[34]),"+f"(d[35]),"+f"(d[36]),"+f"(d[37]),"+f"(d[38]),"+f"(d[39]),"+f"(d[40]),"+f"(d[41]),"+f"(d[42]),"+f"(d[43]),"+f"(d[44]),"+f"(d[45]),"+f"(d[46]),"+f"(d[47]),"+f"(d[48]),"+f"(d[49]),"+f"(d[50]),"+f"(d[51]),"+f"(d[52]),"+f"(d[53]),"+f"(d[54]),"+f"(d[55]),"+f"(d[56]),"+f"(d[57]),"+f"(d[58]),"+f"(d[59]),"+f"(d[60]),"+f"(d[61]),"+f"(d[62]),"+f"(d[63]),"+f"(d[64]),"+f"(d[65]),"+f"(d[66]),"+f"(d[67]),"+f"(d[68]),"+f"(d[69]),"+f"(d[70]),"+f"(d[71]),"+f"(d[72]),"+f"(d[73]),"+f"(d[74]),"+f"(d[75]),"+f"(d[76]),"+f"(d[77]),"+f"(d[78]),"+f"(d[79]),"+f"(d[80]),"+f"(d[81]),"+f"(d[82]),"+f"(d[83]),"+f"(d[84]),"+f"(d[85]),"+f"(d[86]),"+f"(d[87]),"+f"(d[88]),"+f"(d[89]),"+f"(d[90]),"+f"(d[91]),"+f"(d[92]),"+f"(d[93]),"+f"(d[94]),"+f"(d[95])
    : "l"(da), "l"(db), "r"(scale_d));
}
__device__ __forceinline__ void wgmma_rs_n64(float (&d)[32], uint32_t a0, uint32_t a1, uint32_t a2, uint32_t a3, uint64_t db, int scale_d) {
  asm volatile("{\n.reg .pred p;\nsetp.ne.b32 p, %37, 0;\n"
    "wgmma.mma_async.sync.aligned.m64n64k16.f32.bf16.bf16 {%0,%1,%2,%3,%4,%5,%6,%7,%8,%9,%10,%11,%12,%13,%14,%15,%16,%17,%18,%19,%20,%21,%22,%23,%24,%25,%26,%27,%28,%29,%30,%31}, {%32,%33,%34,%35}, %36, p, 1, 1, 0;\n}\n"
    : "+f"(d[0]),"+f"(d[1]),"+f"(d[2]),"+f"(d[3]),"+f"(d[4]),"+f"(d[5]),"+f"(d[6]),"+f"(d[7]),"+f"(d[8]),"+f"(d[9]),"+f"(d[10]),"+f"(d[11]),"+f"(d[12]),"+f"(d[13]),"+f"(d[14]),"+f"(d[15]),"+f"(d[16]),"+f"(d[17]),"+f"(d[18]),"+f"(d[19]),"+f"(d[20]),"+f"(d[21]),"+f"(d[22]),"+f"(d[23]),"+f"(d[24]),"+f"(d[25]),"+f"(d[26]),"+f"(d[27]),"+f"(d[28]),"+f"(d[29]),"+f"(d[30]),"+f"(d[31])
    : "r"(a0), "r"(a1), "r"(a2), "r"(a3), "l"(db), "r"(scale_d));
}
__device__ __forceinline__ void wgmma_rs_n24_tb(float (&d)[12], uint32_t a0, uint32_t a1, uint32_t a2, uint32_t a3, uint64_t db, int scale_d) {
  asm volatile("{\n.reg .pred p;\nsetp.ne.b32 p, %17, 0;\n"
    "wgmma.mma_async.sync.aligned.m64n24k16.f32.bf16.bf16 {%0,%1,%2,%3,%4,%5,%6,%7,%8,%9,%10,%11}, {%12,%13,%14,%15}, %16, p, 1, 1, 1;\n}\n"
    : "+f"(d[0]),"+f"(d[1]),"+f"(d[2]),"+f"(d[3]),"+f"(d[4]),"+f"(d[5]),"+f"(d[6]),"+f"(d[7]),"+f"(d[8]),"+f"(d[9]),"+f"(d[10]),"+f"(d[11])
    : "r"(a0), "r"(a1), "r"(a2), "r"(a3), "l"(db), "r"(scale_d));
}

constexpr int PRE_ROW_BLOCKS = 64;
constexpr int PRE_COL_BLOCKS = 3 * DM / 64;
__device__ __forceinline__ float2 ln_finish(float mean, float var) {
  float mb = bf_round(mean);
  float s = bf_round(sqrtf(bf_round(bf_round(var) + 1e-5f)));
  return make_float2(mb, 1.0f / s);
}
__device__ __forceinline__ void colsum64(const __nv_bfloat16* __restrict__ w, int ld, int c0, float* __restrict__ dst, float (*red)[65], int tid, int bar_id) {
  const int cg = tid & 7, r0 = tid >> 3;
  float acc[8];
#pragma unroll
  for (int i = 0; i < 8; i++) acc[i] = 0.f;
#pragma unroll 10
  for (int r = r0; r < DM; r += 32) {
    uint4 v = __ldg((const uint4*)(w + (size_t)r * ld + c0 + cg * 8));
    acc[0] += bf_lo(v.x); acc[1] += bf_hi(v.x); acc[2] += bf_lo(v.y); acc[3] += bf_hi(v.y);
    acc[4] += bf_lo(v.z); acc[5] += bf_hi(v.z); acc[6] += bf_lo(v.w); acc[7] += bf_hi(v.w);
  }
#pragma unroll
  for (int i = 0; i < 8; i++) red[r0][cg * 8 + i] = acc[i];
  named_bar(bar_id, 256);
  if (tid < 64) {
    float s = 0.f;
#pragma unroll
    for (int r = 0; r < 32; r++) s += red[r][tid];
    dst[c0 + tid] = s;
  }
  named_bar(bar_id, 256);
}
__global__ void __launch_bounds__(256) pre_kernel(const __nv_bfloat16* __restrict__ x, const __nv_bfloat16* __restrict__ wqkv) {
  TS_BEGIN(0);
  pdl_launch();
  const int tid = threadIdx.x, lane = tid & 31, warp = tid >> 5;
  if (blockIdx.x < PRE_COL_BLOCKS) {
    __shared__ float red[32][65];
    colsum64(wqkv, 3 * DM, blockIdx.x * 64, g_cs_qkv, red, tid, 1);
  } else {
    const int rb = blockIdx.x - PRE_COL_BLOCKS;
#pragma unroll
    for (int i = 0; i < 4; i++) {
      const int row = rb * 32 + warp * 4 + i;
      const uint4* p = (const uint4*)(x + (size_t)row * DM);
      uint4 v0 = __ldg(p + lane), v1 = __ldg(p + 32 + lane), v2 = make_uint4(0, 0, 0, 0);
      if (lane < 16) v2 = __ldg(p + 64 + lane);
      float f[24];
      uint32_t u[12] = {v0.x, v0.y, v0.z, v0.w, v1.x, v1.y, v1.z, v1.w, v2.x, v2.y, v2.z, v2.w};
#pragma unroll
      for (int j = 0; j < 12; j++) { f[2 * j] = bf_lo(u[j]); f[2 * j + 1] = bf_hi(u[j]); }
      float s = 0.f;
#pragma unroll
      for (int j = 0; j < 24; j++) s += f[j];
#pragma unroll
      for (int o = 16; o; o >>= 1) s += __shfl_xor_sync(~0u, s, o);
      const float mean = s * (1.0f / DM);
      float q = 0.f;
#pragma unroll
      for (int j = 0; j < 16; j++) { float d = f[j] - mean; q += d * d; }
      if (lane < 16) {
#pragma unroll
        for (int j = 16; j < 24; j++) { float d = f[j] - mean; q += d * d; }
      }
#pragma unroll
      for (int o = 16; o; o >>= 1) q += __shfl_xor_sync(~0u, q, o);
      if (lane == 0) g_stat1[row] = ln_finish(mean, q * (1.0f / DM));
    }
  }
  TS_END(0);
}

enum { EPI_QKV = 0, EPI_WO = 1, EPI_GLU = 2, EPI_DOWN = 3 };
template <int N> struct WG;
template <> struct WG<128> { static __device__ __forceinline__ void mma(float (&d)[64], uint64_t a, uint64_t b, int s) { wgmma_ss_n128(d, a, b, s); } };
template <> struct WG<192> { static __device__ __forceinline__ void mma(float (&d)[96], uint64_t a, uint64_t b, int s) { wgmma_ss_n192(d, a, b, s); } };

template <int BM, int BN, int NB, int STAGES> struct GemmCfg {
  static constexpr int A_BYTES = BM * 128;
  static constexpr int B_BYTES = NB * (BN / 64) * 8192;
  static constexpr int STAGE_BYTES = A_BYTES + B_BYTES;
  static constexpr int SMEM = STAGES * STAGE_BYTES + 1024   + 256   + 4096  ;
};

constexpr float QSCALE = 0.22360679774997896f * 1.4426950408889634f;

template <int BM, int BN, int NB, int KDIM, int STAGES, int EPI, int MINB, int CN, int CM>
__global__ void __launch_bounds__(EPI == EPI_GLU ? 384 : 288, MINB) gemm_kernel(const __grid_constant__ CUtensorMap tmA, const __grid_constant__ CUtensorMap tmB0,
                                                         const __grid_constant__ CUtensorMap tmB1,
                                                         const __nv_bfloat16* resid, __nv_bfloat16* out) {
  using Cfg = GemmCfg<BM, BN, NB, STAGES>;
  constexpr int MB = BM / 128;
  constexpr int KT = KDIM / 64;
  extern __shared__ uint8_t smem_raw[];
  const uint32_t sbase = (smem_u32(smem_raw) + 1023u) & ~1023u;
  uint8_t* sptr = smem_raw + (sbase - smem_u32(smem_raw));
  const uint32_t sbar = sbase + STAGES * Cfg::STAGE_BYTES;
  const int tid = threadIdx.x, warp = tid >> 5, lane = tid & 31;
  const int n0 = blockIdx.x * BN, m0 = blockIdx.y * BM;
  TS_BEGIN(EPI == EPI_QKV ? 1 : EPI + 2);
  constexpr int NCL = CN + CM - 1;
  const int cx = blockIdx.x % CN, cy = blockIdx.y % CM;
  if (tid == 0) {
    for (int i = 0; i < STAGES; i++) { mbar_init(sbar + 8 * i, 1); mbar_init(sbar + 8 * (STAGES + i), 2 * NCL); }
    asm volatile("fence.mbarrier_init.release.cluster;" ::: "memory");
  }
  __syncthreads();
  if constexpr (CN * CM > 1) { cluster_arrive(); cluster_wait(); }
  pdl_launch();
  if (warp >= 8) {
    if constexpr (EPI == EPI_GLU) asm volatile("setmaxnreg.dec.sync.aligned.u32 40;");
    if (warp == 8 && lane == 0) {
      auto load_a = [&](int kt, int s) { tma_2d(sbase + s * Cfg::STAGE_BYTES, &tmA, kt * 64, m0, sbar + 8 * s); };
      auto load_b = [&](int kt, int s) {
        const uint32_t sb = sbase + s * Cfg::STAGE_BYTES + Cfg::A_BYTES;
        tma_3d(sb, &tmB0, 0, kt * 64, blockIdx.x * (BN / 64), sbar + 8 * s);
        if constexpr (NB == 2) tma_3d(sb + (BN / 64) * 8192, &tmB1, 0, kt * 64, blockIdx.x * (BN / 64), sbar + 8 * s);
      };
      for (int s = 0; s < STAGES; s++) { mbar_expect_tx(sbar + 8 * s, Cfg::STAGE_BYTES); if (EPI != EPI_QKV || s == 0) load_b(s, s); }
      if (EPI != EPI_QKV) pdl_wait();
      for (int s = 0; s < STAGES; s++) { load_a(s, s); if (EPI == EPI_QKV && s > 0) load_b(s, s); }
      for (int kt = STAGES; kt < KT; kt++) {
        const int s = kt % STAGES;
        mbar_wait(sbar + 8 * (STAGES + s), ((kt / STAGES) - 1) & 1);
        mbar_expect_tx(sbar + 8 * s, Cfg::STAGE_BYTES);
        load_a(kt, s);
        load_b(kt, s);
      }
    }
    if constexpr (EPI == EPI_GLU) {
      if (warp > 8) {
        float2* s_st = (float2*)(sptr + STAGES * Cfg::STAGE_BYTES + 256);
        float* s_cs = (float*)(sptr + STAGES * Cfg::STAGE_BYTES + 256 + 1024);
        pdl_wait();
        for (int r = tid - 288; r < BM; r += 96) {
          const float2* pp = &g_part2[(m0 + r) * 8];
          float s = 0.f;
#pragma unroll
          for (int i = 0; i < 8; i++) s += pp[i].x;
          const float mean = s * (1.0f / DM);
          float q = 0.f;
#pragma unroll
          for (int i = 0; i < 8; i++) { const float2 p = pp[i]; const float d = p.x * (1.0f / 80.f) - mean; q += p.y + 80.f * d * d; }
          s_st[r] = ln_finish(mean, q * (1.0f / DM));
        }
        for (int c = tid - 288; c < BN; c += 96) { s_cs[c] = g_cs_g[n0 + c]; s_cs[BN + c] = g_cs_u[n0 + c]; }
        __threadfence_block();
        asm volatile("bar.arrive 2, 352;" ::: "memory");
      }
    }
    if constexpr (CN * CM > 1) { __syncwarp(); cluster_arrive(); cluster_wait(); }
    return;
  }
  if constexpr (EPI == EPI_GLU) asm volatile("setmaxnreg.inc.sync.aligned.u32 232;");
  const int wg = warp >> 2, g = lane >> 2, t = lane & 3;
  float acc[MB][NB][BN / 2];
#pragma unroll
  for (int mb = 0; mb < MB; mb++)
#pragma unroll
    for (int nb = 0; nb < NB; nb++)
#pragma unroll
      for (int i = 0; i < BN / 2; i++) acc[mb][nb][i] = 0.f;
  for (int kt = 0; kt < KT; kt++) {
    const int s = kt % STAGES;
    mbar_wait(sbar + 8 * s, (kt / STAGES) & 1);
    if (kt == 0) TS_MID(EPI == EPI_QKV ? 1 : EPI + 2, 0);
    const uint32_t sa = sbase + s * Cfg::STAGE_BYTES + wg * (MB * 64 * 128);
    const uint32_t sb = sbase + s * Cfg::STAGE_BYTES + Cfg::A_BYTES;
    wgmma_fence();
#pragma unroll
    for (int ks = 0; ks < 4; ks++) {
#pragma unroll
      for (int mb = 0; mb < MB; mb++) {
        const uint64_t da = make_desc(sa + mb * 8192 + ks * 32, 16, 1024, 1);
#pragma unroll
        for (int nb = 0; nb < NB; nb++) {
          const uint64_t db = make_desc(sb + nb * (BN / 64) * 8192 + ks * 2048, 8192, 1024, 1);
          WG<BN>::mma(acc[mb][nb], da, db, 1);
        }
      }
    }
    wgmma_commit();
    wgmma_wait<1>();
    if (kt > 0 && kt - 1 + STAGES < KT && (tid & 127) < NCL) {
      const uint32_t eb = sbar + 8 * (STAGES + (kt - 1) % STAGES);
      if constexpr (CN * CM > 1) {
        const int i = tid & 127;
        const uint32_t rank = i < CN ? cy * CN + i : ((i - CN + (i - CN >= cy ? 1 : 0)) * CN + cx);
        mbar_arrive_remote(eb, rank);
      } else mbar_arrive(eb);
    }
  }
  wgmma_wait<0>();
#pragma unroll
  for (int mb = 0; mb < MB; mb++)
#pragma unroll
    for (int nb = 0; nb < NB; nb++)
#pragma unroll
      for (int i = 0; i < BN / 2; i++) asm volatile("" : "+f"(acc[mb][nb][i]) :: "memory");
  if constexpr (CN * CM > 1) cluster_arrive();
  TS_MID(EPI == EPI_QKV ? 1 : EPI + 2, 1);
  pdl_wait();
  TS_MID(EPI == EPI_QKV ? 1 : EPI + 2, 2);
  named_bar(1, 256);
  constexpr int LDS = BN * 2 + 16;
  const int ctid = tid;

  if constexpr (EPI == EPI_QKV) {
    const int sec = n0 / DM;
#pragma unroll
    for (int mb = 0; mb < MB; mb++) {
      const int r0 = wg * (MB * 64) + mb * 64 + (warp & 3) * 16 + g;
      const float2 st0 = g_stat1[m0 + r0], st1 = g_stat1[m0 + r0 + 8];
      const float sc0 = sec == 0 ? st0.y * QSCALE : st0.y, sc1 = sec == 0 ? st1.y * QSCALE : st1.y;
#pragma unroll
      for (int j = 0; j < BN / 8; j++) {
        const float2 cs = *(const float2*)&g_cs_qkv[n0 + j * 8 + 2 * t];
        const float* a = &acc[mb][0][4 * j];
        *(uint32_t*)(sptr + r0 * LDS + j * 16 + t * 4) = pack_bf16((a[0] - st0.x * cs.x) * sc0, (a[1] - st0.x * cs.y) * sc0);
        *(uint32_t*)(sptr + (r0 + 8) * LDS + j * 16 + t * 4) = pack_bf16((a[2] - st1.x * cs.x) * sc1, (a[3] - st1.x * cs.y) * sc1);
      }
    }
    named_bar(1, 256);
    if (sec == 0) {
#pragma unroll
      for (int i = 0; i < BM * (BN / 8) / 256; i++) {
        const int idx = i * 256 + ctid, r = idx / (BN / 8), c = idx % (BN / 8);
        st_g16(g_q + (size_t)(m0 + r) * DM + n0 + c * 8, *(const uint4*)(sptr + r * LDS + c * 16));
      }
    } else {
      __nv_bfloat16* dst = sec == 1 ? g_k : g_v;
      const int cbase = n0 - sec * DM;
#pragma unroll 4
      for (int i = 0; i < BM * (BN / 4) / 256; i++) {
        const int idx = i * 256 + ctid;
        const int half = idx & 1, r8 = (idx >> 1) & 7, rest = idx >> 4;
        const int pq = rest % (BN / 8), rg = rest / (BN / 8);
        const int r = rg * 8 + r8, cq = pq * 2 + half;
        const int col = cbase + cq * 4, h = col / DH, qd = (col % DH) >> 2;
        const uint2 v = *(const uint2*)(sptr + r * LDS + cq * 8);
        const int j = m0 + r;
        uint8_t* p = (uint8_t*)dst + ((size_t)h * S_LEN * 24 + (j >> 3) * 192 + (qd >> 1) * 64 + (j & 7) * 8 + (qd & 1) * 4) * 2;
        if (qd == 4) st_g16(p, make_uint4(v.x, v.y, 0x00003f80u, 0u));
        else st_g8(p, v);
      }
      if (sec == 1) {
        __shared__ unsigned int s_kn[8];
        if (ctid < 8) s_kn[ctid] = 0u;
        named_bar(1, 256);
        const int hfirst = cbase / DH, hlast = (cbase + BN - 1) / DH;
        for (int hh = hfirst; hh <= hlast; hh++) {
          const int c_lo = max(hh * DH, cbase) - cbase, c_hi = min(hh * DH + DH, cbase + BN) - cbase;
          float mx = 0.f;
          for (int r = ctid; r < BM; r += 256) {
            float s = 0.f;
            for (int c = c_lo; c < c_hi; c += 4) {
              const uint2 v = *(const uint2*)(sptr + r * LDS + c * 2);
              s += bf_lo(v.x) * bf_lo(v.x) + bf_hi(v.x) * bf_hi(v.x) + bf_lo(v.y) * bf_lo(v.y) + bf_hi(v.y) * bf_hi(v.y);
            }
            mx = (s > mx || s != s) ? s : mx;
          }
          unsigned int mb_ = __float_as_uint(mx) & 0x7fffffffu;
          mb_ = __reduce_max_sync(~0u, mb_);
          if (lane == 0) atomicMax(&s_kn[hh - hfirst], mb_);
        }
        named_bar(1, 256);
        if (ctid <= hlast - hfirst) {
          const int hh = hfirst + ctid;
          const bool starts_here = hh * DH >= cbase, ends_here = hh * DH + DH <= cbase + BN;
          const float v = __uint_as_float(s_kn[ctid]);
          float* o = &g_kn[(blockIdx.y * NH + hh) * 2];
          if (starts_here) { o[0] = v; if (ends_here) o[1] = 0.f; }
          else o[1] = v;
        }
      }
    }
  } else if constexpr (EPI == EPI_WO || EPI == EPI_DOWN) {
    const int r0 = wg * 64 + (warp & 3) * 16 + g;
#pragma unroll
    for (int j = 0; j < BN / 8; j++) {
      const float* a = &acc[0][0][4 * j];
      *(uint32_t*)(sptr + r0 * LDS + j * 16 + t * 4) = pack_bf16(a[0], a[1]);
      *(uint32_t*)(sptr + (r0 + 8) * LDS + j * 16 + t * 4) = pack_bf16(a[2], a[3]);
    }
    named_bar(1, 256);
#pragma unroll
    for (int i = 0; i < BM * (BN / 8) / 256; i++) {
      const int idx = i * 256 + ctid, r = idx / (BN / 8), c = idx % (BN / 8);
      const uint4 a = *(const uint4*)(sptr + r * LDS + c * 16);
      const size_t go = (size_t)(m0 + r) * DM + n0 + c * 8;
      const uint4 b = ld_g16(resid + go);
      uint4 o;
      o.x = pack_bf16(bf_lo(a.x) + bf_lo(b.x), bf_hi(a.x) + bf_hi(b.x));
      o.y = pack_bf16(bf_lo(a.y) + bf_lo(b.y), bf_hi(a.y) + bf_hi(b.y));
      o.z = pack_bf16(bf_lo(a.z) + bf_lo(b.z), bf_hi(a.z) + bf_hi(b.z));
      o.w = pack_bf16(bf_lo(a.w) + bf_lo(b.w), bf_hi(a.w) + bf_hi(b.w));
      st_g16(out + go, o);
      if constexpr (EPI == EPI_WO) {
        static_assert(BN == 64, "stats assume 8 lanes per row");
        const float f[8] = {bf_lo(o.x), bf_hi(o.x), bf_lo(o.y), bf_hi(o.y), bf_lo(o.z), bf_hi(o.z), bf_lo(o.w), bf_hi(o.w)};
        float s = 0.f;
#pragma unroll
        for (int k = 0; k < 8; k++) s += f[k];
        s += __shfl_xor_sync(~0u, s, 1); s += __shfl_xor_sync(~0u, s, 2); s += __shfl_xor_sync(~0u, s, 4);
        const float mu = s * (1.0f / 64.f);
        float q = 0.f;
#pragma unroll
        for (int k = 0; k < 8; k++) { const float d = f[k] - mu; q += d * d; }
        q += __shfl_xor_sync(~0u, q, 1); q += __shfl_xor_sync(~0u, q, 2); q += __shfl_xor_sync(~0u, q, 4);
        if (c == 0) g_part2[(m0 + r) * 10 + blockIdx.x] = make_float2(s, q);
      }
    }
  } else {
    const int r0 = wg * 64 + (warp & 3) * 16 + g;
    const float2* s_st = (const float2*)(sptr + STAGES * Cfg::STAGE_BYTES + 256);
    const float* s_cs = (const float*)(sptr + STAGES * Cfg::STAGE_BYTES + 256 + 1024);
    named_bar(2, 352);
    float2 st[2] = {s_st[r0], s_st[r0 + 8]};
#pragma unroll
    for (int j = 0; j < BN / 8; j++) {
      const float2 cg = *(const float2*)&s_cs[j * 8 + 2 * t], cu = *(const float2*)&s_cs[BN + j * 8 + 2 * t];
      const float* a = &acc[0][0][4 * j];
      const float* b = &acc[0][1][4 * j];
#pragma unroll
      for (int e = 0; e < 2; e++) {
        const float2 s_ = st[e];
        const uint32_t gp = pack_bf16(fmaf(-s_.x, cg.x, a[2 * e]) * s_.y, fmaf(-s_.x, cg.y, a[2 * e + 1]) * s_.y);
        const uint32_t up = pack_bf16(fmaf(-s_.x, cu.x, b[2 * e]) * s_.y, fmaf(-s_.x, cu.y, b[2 * e + 1]) * s_.y);
        uint32_t r;
        asm("{\n.reg .b32 z;\nmax.bf16x2 z, %1, %3;\nmul.rn.bf16x2 %0, z, %2;\n}" : "=r"(r) : "r"(gp), "r"(up), "r"(0u));
        *(uint32_t*)(sptr + (r0 + 8 * e) * LDS + j * 16 + t * 4) = r;
      }
    }
    named_bar(1, 256);
#pragma unroll
    for (int i = 0; i < BM * (BN / 8) / 256; i++) {
      const int idx = i * 256 + ctid, r = idx / (BN / 8), c = idx % (BN / 8);
      st_g16(out + (size_t)(m0 + r) * DFF + n0 + c * 8, *(const uint4*)(sptr + r * LDS + c * 16));
    }
  }
  if constexpr (CN * CM > 1) cluster_wait();
  TS_END(EPI == EPI_QKV ? 1 : EPI + 2);
}

constexpr int R_STAGES = 8;
constexpr int R_STAGE_BYTES = 16384 + 5 * 2048;
constexpr int R_BAR_OFF = R_STAGES * R_STAGE_BYTES;
constexpr int R_SMEM = R_BAR_OFF + 256 + 1024;
template <int KDIM, bool STATS>
__global__ void __launch_bounds__(288, 1) gemm_res_kernel(const __grid_constant__ CUtensorMap tmA, const __grid_constant__ CUtensorMap tmB,
                                                          const __nv_bfloat16* resid, __nv_bfloat16* out) {
  constexpr int KT = KDIM / 64;
  extern __shared__ uint8_t smem_raw[];
  const uint32_t sbase = (smem_u32(smem_raw) + 1023u) & ~1023u;
  uint8_t* sptr = smem_raw + (sbase - smem_u32(smem_raw));
  const uint32_t sbar = sbase + R_BAR_OFF;
  const int tid = threadIdx.x, warp = tid >> 5, lane = tid & 31;
  const int n0 = blockIdx.x * 80, m0 = blockIdx.y * 128;
  TS_BEGIN(STATS ? 3 : 5);
  if (tid == 0) {
    for (int i = 0; i < R_STAGES; i++) { mbar_init(sbar + 8 * i, 1); mbar_init(sbar + 8 * (R_STAGES + i), 2); }
    asm volatile("fence.mbarrier_init.release.cluster;" ::: "memory");
  }
  __syncthreads();
  pdl_launch();
  if (warp == 8) {
    if (lane == 0) {
      auto load_b = [&](int kt, int s) { tma_3d(sbase + s * R_STAGE_BYTES + 16384, &tmB, 0, kt * 64, blockIdx.x * 5, sbar + 8 * s); };
      for (int s = 0; s < R_STAGES; s++) { mbar_expect_tx(sbar + 8 * s, R_STAGE_BYTES); if (s < 3) load_b(s, s); }
      pdl_wait();
      for (int s = 0; s < R_STAGES; s++) { tma_2d(sbase + s * R_STAGE_BYTES, &tmA, s * 64, m0, sbar + 8 * s); if (s >= 3) load_b(s, s); }
      for (int kt = R_STAGES; kt < KT; kt++) {
        const int s = kt % R_STAGES;
        mbar_wait(sbar + 8 * (R_STAGES + s), ((kt / R_STAGES) - 1) & 1);
        mbar_expect_tx(sbar + 8 * s, R_STAGE_BYTES);
        tma_2d(sbase + s * R_STAGE_BYTES, &tmA, kt * 64, m0, sbar + 8 * s);
        load_b(kt, s);
      }
    }
    return;
  }
  const int wg = warp >> 2, g = lane >> 2, t = lane & 3;
  pdl_wait();
  uint4 rv[5];
#pragma unroll
  for (int i = 0; i < 5; i++) {
    const int idx = i * 256 + tid, r = idx / 10, c = idx % 10;
    rv[i] = ld_g16(resid + (size_t)(m0 + r) * DM + n0 + c * 8);
  }
  float acc[40];
#pragma unroll
  for (int i = 0; i < 40; i++) acc[i] = 0.f;
  for (int kt = 0; kt < KT; kt++) {
    const int s = kt % R_STAGES;
    mbar_wait(sbar + 8 * s, (kt / R_STAGES) & 1);
    if (kt == 0) TS_MID(STATS ? 3 : 5, 0);
    const uint32_t sa = sbase + s * R_STAGE_BYTES + wg * 8192;
    const uint32_t sb = sbase + s * R_STAGE_BYTES + 16384;
    wgmma_fence();
#pragma unroll
    for (int ks = 0; ks < 4; ks++)
      wgmma_ss_n80(acc, make_desc(sa + ks * 32, 16, 1024, 1), make_desc(sb + ks * 512, 2048, 256, 3), 1);
    wgmma_commit();
    wgmma_wait<1>();
    if (kt > 0 && kt - 1 + R_STAGES < KT && (tid & 127) == 0) mbar_arrive(sbar + 8 * (R_STAGES + (kt - 1) % R_STAGES));
  }
  wgmma_wait<0>();
#pragma unroll
  for (int i = 0; i < 40; i++) asm volatile("" : "+f"(acc[i]) :: "memory");
  TS_MID(STATS ? 3 : 5, 1);
  named_bar(1, 256);
  constexpr int LDS = 176;
  const int r0 = wg * 64 + (warp & 3) * 16 + g;
#pragma unroll
  for (int i = 0; i < 10; i++) {
    *(uint32_t*)(sptr + r0 * LDS + i * 16 + t * 4) = pack_bf16(acc[4 * i], acc[4 * i + 1]);
    *(uint32_t*)(sptr + (r0 + 8) * LDS + i * 16 + t * 4) = pack_bf16(acc[4 * i + 2], acc[4 * i + 3]);
  }
  named_bar(1, 256);
  TS_MID(STATS ? 3 : 5, 2);
#pragma unroll
  for (int i = 0; i < 5; i++) {
    const int idx = i * 256 + tid, r = idx / 10, c = idx % 10;
    const uint4 a = *(const uint4*)(sptr + r * LDS + c * 16);
    const uint4 b = rv[i];
    uint4 o;
    o.x = pack_bf16(bf_lo(a.x) + bf_lo(b.x), bf_hi(a.x) + bf_hi(b.x));
    o.y = pack_bf16(bf_lo(a.y) + bf_lo(b.y), bf_hi(a.y) + bf_hi(b.y));
    o.z = pack_bf16(bf_lo(a.z) + bf_lo(b.z), bf_hi(a.z) + bf_hi(b.z));
    o.w = pack_bf16(bf_lo(a.w) + bf_lo(b.w), bf_hi(a.w) + bf_hi(b.w));
    st_g16(out + (size_t)(m0 + r) * DM + n0 + c * 8, o);
    if constexpr (STATS) *(uint4*)(sptr + r * LDS + c * 16) = o;
  }
  TS_MID(STATS ? 3 : 5, 3);
  if constexpr (STATS) {
    named_bar(1, 256);
    const int r = tid >> 1, hf = tid & 1;
    float f[40];
#pragma unroll
    for (int i = 0; i < 5; i++) {
      const uint4 v = *(const uint4*)(sptr + r * LDS + hf * 80 + i * 16);
      f[8 * i] = bf_lo(v.x); f[8 * i + 1] = bf_hi(v.x); f[8 * i + 2] = bf_lo(v.y); f[8 * i + 3] = bf_hi(v.y);
      f[8 * i + 4] = bf_lo(v.z); f[8 * i + 5] = bf_hi(v.z); f[8 * i + 6] = bf_lo(v.w); f[8 * i + 7] = bf_hi(v.w);
    }
    float s = 0.f;
#pragma unroll
    for (int i = 0; i < 40; i++) s += f[i];
    s += __shfl_xor_sync(~0u, s, 1);
    const float mu = s * (1.0f / 80.f);
    float q = 0.f;
#pragma unroll
    for (int i = 0; i < 40; i++) { const float d = f[i] - mu; q += d * d; }
    q += __shfl_xor_sync(~0u, q, 1);
    if (hf == 0) g_part2[(m0 + r) * 8 + blockIdx.x] = make_float2(s, q);
  }
  TS_END(STATS ? 3 : 5);
}

#define POLY_NUM 5
__device__ __forceinline__ float ex2_poly(float x, int shl23) {
  const float MAGIC = 12582912.f;
  const float tt = x + MAGIC;
  const float f = x - (tt - MAGIC);
  float p = fmaf(0.0013276472454890609f, f, 0.009675540961325169f);
  p = fmaf(p, f, 0.05550713092088699f);
  p = fmaf(p, f, 0.24022120237350464f);
  p = fmaf(p, f, 0.6931469440460205f);
  p = fmaf(p, f, 1.0000001192092896f);
  return __int_as_float(__float_as_int(tt) * shl23 + __float_as_int(p));
}
constexpr int KV_BYTES = S_LEN * 48;
constexpr int ATT_SMEM = 2 * KV_BYTES + 256;

__global__ void __launch_bounds__(512, 1) attn_kernel(int shl23, const __nv_bfloat16* __restrict__ wg_, const __nv_bfloat16* __restrict__ wu_,
                                                      const __nv_bfloat16* __restrict__ wo_, const __nv_bfloat16* __restrict__ wd_) {
  extern __shared__ __align__(1024) uint8_t smem[];
  if (blockIdx.x >= 128) {
    pdl_launch();
    const int e = blockIdx.x - 128, half = threadIdx.x >> 8;
    if (threadIdx.x == 0) {
      for (int i = 0; i < 13; i++) asm volatile("cp.async.bulk.prefetch.L2.global [%0], %1;" :: "l"((const uint8_t*)wo_ + (e * 13 + i) * 16384 * 0 + (size_t)(e * 13 + i >= 50 ? 0 : (e * 13 + i)) * 16384), "r"(16384));
      for (int i = 0; i < 30; i++) asm volatile("cp.async.bulk.prefetch.L2.global [%0], %1;" :: "l"((const uint8_t*)wd_ + (size_t)(e * 30 + i) * 16384), "r"(16384));
    }
    float (*red)[65] = (float (*)[65])(smem + half * 16384);
    for (int b = e * 12 + half; b < e * 12 + 12; b += 2) {
      if (b < 24) colsum64(wg_, DFF, b * 64, g_cs_g, red, threadIdx.x & 255, 1 + half);
      else colsum64(wu_, DFF, (b - 24) * 64, g_cs_u, red, threadIdx.x & 255, 1 + half);
    }
    return;
  }
  const int h = blockIdx.x >> 2, qb = blockIdx.x & 3;
  const uint32_t sK = smem_u32(smem), sV = sK + KV_BYTES, sBar = sV + KV_BYTES;
  const int tid = threadIdx.x;
  TS_BEGIN(2);
  if (tid == 0) {
    for (int i = 0; i < 8; i++) mbar_init(sBar + 8 * i, 1);
    asm volatile("fence.mbarrier_init.release.cluster;" ::: "memory");
  }
  pdl_launch();
  pdl_wait();
  if (tid == 0) {
    const uint8_t* gk = (const uint8_t*)(g_k + (size_t)h * S_LEN * 24);
    const uint8_t* gv = (const uint8_t*)(g_v + (size_t)h * S_LEN * 24);
    for (int i = 0; i < 8; i++) {
      mbar_expect_tx(sBar + 8 * i, 2 * 12288);
      bulk_g2s(sK + i * 12288, gk + i * 12288, 12288, sBar + 8 * i);
      bulk_g2s(sV + i * 12288, gv + i * 12288, 12288, sBar + 8 * i);
    }
  }
  __syncthreads();
  const int wg = tid >> 7, warp = (tid >> 5) & 3, lane = tid & 31, g = lane >> 2, t = lane & 3;
  float ka = 0.f, kb = 0.f;
#pragma unroll
  for (int i = 0; i < 8; i++) {
    const float2 v = *(const float2*)&g_kn[(i * NH + h) * 2];
    ka = (v.x > ka || v.x != v.x) ? v.x : ka;
    kb = (v.y > kb || v.y != v.y) ? v.y : kb;
  }
  const float kn = sqrtf(ka + kb);
  for (int it = 0; it < 2; it++) {
    const int q0 = qb * 512 + (it * 4 + wg) * 64 + warp * 16;
    uint32_t qa[4], qc[4];
    const uint32_t* qr0 = (const uint32_t*)(g_q + (size_t)(q0 + g) * DM + h * DH);
    const uint32_t* qr1 = (const uint32_t*)(g_q + (size_t)(q0 + g + 8) * DM + h * DH);
    qa[0] = qr0[t]; qa[1] = qr1[t]; qa[2] = qr0[t + 4]; qa[3] = qr1[t + 4];
    qc[0] = (t < 2) ? qr0[t + 8] : 0u; qc[1] = (t < 2) ? qr1[t + 8] : 0u; qc[2] = 0; qc[3] = 0;
    auto sq = [](uint32_t u) { const float a = bf_lo(u), b = bf_hi(u); return a * a + b * b; };
    float n0 = sq(qa[0]) + sq(qa[2]) + sq(qc[0]);
    float n1 = sq(qa[1]) + sq(qa[3]) + sq(qc[1]);
    n0 += __shfl_xor_sync(~0u, n0, 1); n0 += __shfl_xor_sync(~0u, n0, 2);
    n1 += __shfl_xor_sync(~0u, n1, 1); n1 += __shfl_xor_sync(~0u, n1, 2);
    const float m0 = ceilf(sqrtf(n0) * kn * 1.001f) + 1.f, m1 = ceilf(sqrtf(n1) * kn * 1.001f) + 1.f;
    const bool unsafe = !(m0 <= 62.f && m1 <= 62.f);
    uint32_t any_unsafe;
    asm volatile("{\n.reg .pred p, q;\nsetp.ne.u32 p, %1, 0;\nbarrier.cta.red.or.pred q, %2, 128, p;\nselp.u32 %0, 1, 0, q;\n}"
                 : "=r"(any_unsafe) : "r"((uint32_t)unsafe), "r"(1 + wg) : "memory");
    float O[12];
    float S[32];
    if (!__any_sync(~0u, any_unsafe)) {
      if (t == 2) { qc[0] = pack_bf16(-m0, 0.f); qc[1] = pack_bf16(-m1, 0.f); }
      for (int j = 0; j < 32; j++) {
        if (it == 0 && (j & 3) == 0) mbar_wait(sBar + 8 * (j >> 2), 0);
        const uint64_t dk = make_desc(sK + j * 8 * 384, 128, 384, 0);
        wgmma_fence();
        wgmma_rs_n64(S, qa[0], qa[1], qa[2], qa[3], dk, 0);
        wgmma_rs_n64(S, qc[0], qc[1], qc[2], qc[3], dk + (256 >> 4), 1);
        wgmma_commit();
        wgmma_wait<0>();
        uint32_t P[16];
#pragma unroll
        for (int i = 0; i < 16; i++) {
          const bool usepoly = ((i + 1) * POLY_NUM / 16) != (i * POLY_NUM / 16);
          float a, b;
          if (usepoly) { a = ex2_poly(S[2 * i], shl23); b = ex2_poly(S[2 * i + 1], shl23); }
          else { a = ex2_mufu(S[2 * i]); b = ex2_mufu(S[2 * i + 1]); }
          P[i] = pack_bf16(a, b);
        }
        wgmma_fence();
        const uint64_t dv = make_desc(sV + j * 8 * 384, 384, 128, 0);
#pragma unroll
        for (int ks = 0; ks < 4; ks++)
          wgmma_rs_n24_tb(O, P[4 * ks], P[4 * ks + 1], P[4 * ks + 2], P[4 * ks + 3], dv + ((ks * 768) >> 4), (j | ks) != 0);
        wgmma_commit();
      }
    } else {
      float mx0 = -INFINITY, mx1 = -INFINITY;
      for (int j = 0; j < 32; j++) {
        if (it == 0 && (j & 3) == 0) mbar_wait(sBar + 8 * (j >> 2), 0);
        const uint64_t dk = make_desc(sK + j * 8 * 384, 128, 384, 0);
        wgmma_fence();
        wgmma_rs_n64(S, qa[0], qa[1], qa[2], qa[3], dk, 0);
        wgmma_rs_n64(S, qc[0], qc[1], qc[2], qc[3], dk + (256 >> 4), 1);
        wgmma_commit();
        wgmma_wait<0>();
#pragma unroll
        for (int i = 0; i < 8; i++) {
          mx0 = fmaxf(mx0, fmaxf(S[4 * i], S[4 * i + 1]));
          mx1 = fmaxf(mx1, fmaxf(S[4 * i + 2], S[4 * i + 3]));
        }
      }
      mx0 = fmaxf(mx0, __shfl_xor_sync(~0u, mx0, 1)); mx0 = fmaxf(mx0, __shfl_xor_sync(~0u, mx0, 2));
      mx1 = fmaxf(mx1, __shfl_xor_sync(~0u, mx1, 1)); mx1 = fmaxf(mx1, __shfl_xor_sync(~0u, mx1, 2));
      for (int j = 0; j < 32; j++) {
        const uint64_t dk = make_desc(sK + j * 8 * 384, 128, 384, 0);
        wgmma_fence();
        wgmma_rs_n64(S, qa[0], qa[1], qa[2], qa[3], dk, 0);
        wgmma_rs_n64(S, qc[0], qc[1], qc[2], qc[3], dk + (256 >> 4), 1);
        wgmma_commit();
        wgmma_wait<0>();
        uint32_t P[16];
#pragma unroll
        for (int i = 0; i < 8; i++) {
          P[2 * i] = pack_bf16(ex2_mufu(S[4 * i] - mx0), ex2_mufu(S[4 * i + 1] - mx0));
          P[2 * i + 1] = pack_bf16(ex2_mufu(S[4 * i + 2] - mx1), ex2_mufu(S[4 * i + 3] - mx1));
        }
        wgmma_fence();
        const uint64_t dv = make_desc(sV + j * 8 * 384, 384, 128, 0);
#pragma unroll
        for (int ks = 0; ks < 4; ks++)
          wgmma_rs_n24_tb(O, P[4 * ks], P[4 * ks + 1], P[4 * ks + 2], P[4 * ks + 3], dv + ((ks * 768) >> 4), (j | ks) != 0);
        wgmma_commit();
      }
    }
    wgmma_wait<0>();
#pragma unroll
    for (int i = 0; i < 12; i++) asm volatile("" : "+f"(O[i]) :: "memory");
    const float l0 = __shfl_sync(~0u, O[8], (lane & ~3) | 2), l1 = __shfl_sync(~0u, O[10], (lane & ~3) | 2);
    const float r0 = 1.f / l0, r1 = 1.f / l1;
    uint32_t* o0 = (uint32_t*)(g_o + (size_t)(q0 + g) * DM + h * DH);
    uint32_t* o1 = (uint32_t*)(g_o + (size_t)(q0 + g + 8) * DM + h * DH);
    o0[t] = pack_bf16(O[0] * r0, O[1] * r0); o1[t] = pack_bf16(O[2] * r1, O[3] * r1);
    o0[t + 4] = pack_bf16(O[4] * r0, O[5] * r0); o1[t + 4] = pack_bf16(O[6] * r1, O[7] * r1);
    if (t < 2) { o0[t + 8] = pack_bf16(O[8] * r0, O[9] * r0); o1[t + 8] = pack_bf16(O[10] * r1, O[11] * r1); }
  }
  TS_END(2);
}

typedef CUresult (*EncodeFn)(CUtensorMap*, CUtensorMapDataType, cuuint32_t, void*, const cuuint64_t*, const cuuint64_t*, const cuuint32_t*,
                             const cuuint32_t*, CUtensorMapInterleave, CUtensorMapSwizzle, CUtensorMapL2promotion, CUtensorMapFloatOOBfill);
static EncodeFn get_encode() {
  static EncodeFn fn = nullptr;
  if (!fn) {
    void* p = nullptr; cudaDriverEntryPointQueryResult st;
    cudaGetDriverEntryPoint("cuTensorMapEncodeTiled", &p, cudaEnableDefault, &st);
    fn = (EncodeFn)p;
  }
  return fn;
}
static CUtensorMap make_map(const void* ptr, int rows, int cols, int box_rows, int box_cols = 64) {
  CUtensorMap m;
  cuuint64_t dims[2] = {(cuuint64_t)cols, (cuuint64_t)rows};
  cuuint64_t strides[1] = {(cuuint64_t)cols * 2};
  cuuint32_t box[2] = {(cuuint32_t)box_cols, (cuuint32_t)box_rows};
  cuuint32_t es[2] = {1, 1};
  get_encode()(&m, CU_TENSOR_MAP_DATA_TYPE_BFLOAT16, 2, const_cast<void*>(ptr), dims, strides, box, es, CU_TENSOR_MAP_INTERLEAVE_NONE,
               box_cols == 64 ? CU_TENSOR_MAP_SWIZZLE_128B : (box_cols == 32 ? CU_TENSOR_MAP_SWIZZLE_64B : CU_TENSOR_MAP_SWIZZLE_32B), CU_TENSOR_MAP_L2_PROMOTION_L2_128B, CU_TENSOR_MAP_FLOAT_OOB_FILL_NONE);
  return m;
}
static CUtensorMap make_map_w(const void* ptr, int rows, int cols, int bc, int nblk) {
  CUtensorMap m;
  cuuint64_t dims[3] = {(cuuint64_t)bc, (cuuint64_t)rows, (cuuint64_t)(cols / bc)};
  cuuint64_t strides[2] = {(cuuint64_t)cols * 2, (cuuint64_t)bc * 2};
  cuuint32_t box[3] = {(cuuint32_t)bc, 64, (cuuint32_t)nblk};
  cuuint32_t es[3] = {1, 1, 1};
  get_encode()(&m, CU_TENSOR_MAP_DATA_TYPE_BFLOAT16, 3, const_cast<void*>(ptr), dims, strides, box, es, CU_TENSOR_MAP_INTERLEAVE_NONE,
               bc == 64 ? CU_TENSOR_MAP_SWIZZLE_128B : (bc == 32 ? CU_TENSOR_MAP_SWIZZLE_64B : CU_TENSOR_MAP_SWIZZLE_32B),
               CU_TENSOR_MAP_L2_PROMOTION_L2_128B, CU_TENSOR_MAP_FLOAT_OOB_FILL_NONE);
  return m;
}
template <typename... KArgs, typename... Args>
static void launch(void (*kern)(KArgs...), dim3 grid, dim3 block, size_t smem, bool pdl, dim3 cluster, Args... args) {
  cudaLaunchConfig_t cfg = {};
  cfg.gridDim = grid; cfg.blockDim = block; cfg.dynamicSmemBytes = smem; cfg.stream = cudaStreamPerThread;
  cudaLaunchAttribute at[2];
  int na = 0;
  if (pdl) { at[na].id = cudaLaunchAttributeProgrammaticStreamSerialization; at[na].val.programmaticStreamSerializationAllowed = 1; na++; }
  if (cluster.x * cluster.y > 1) { at[na].id = cudaLaunchAttributeClusterDimension; at[na].val.clusterDim.x = cluster.x; at[na].val.clusterDim.y = cluster.y; at[na].val.clusterDim.z = 1; na++; }
  cfg.attrs = at; cfg.numAttrs = na;
  cudaLaunchKernelEx(&cfg, kern, KArgs(args)...);
}

extern "C" void kernel_launch(void* const* d_in, const int* in_sizes, int n_in, void* d_out, int out_size) {
  const __nv_bfloat16* x = (const __nv_bfloat16*)d_in[0];
  const __nv_bfloat16* wqkv = (const __nv_bfloat16*)d_in[1];
  const __nv_bfloat16* wo = (const __nv_bfloat16*)d_in[2];
  const __nv_bfloat16* wgate = (const __nv_bfloat16*)d_in[4];
  const __nv_bfloat16* wup = (const __nv_bfloat16*)d_in[5];
  const __nv_bfloat16* wdown = (const __nv_bfloat16*)d_in[6];
  __nv_bfloat16* out = (__nv_bfloat16*)d_out;
  void *p_o, *p_h, *p_act;
  cudaGetSymbolAddress(&p_o, g_o); cudaGetSymbolAddress(&p_h, g_h); cudaGetSymbolAddress(&p_act, g_act);

#define A_CN 1
#define A_CM 1
#define D_CN 1
#define D_CM 1
  auto kA = gemm_kernel<256, 128, 1, DM, 4, EPI_QKV, 1, A_CN, A_CM>;
  auto kC = gemm_res_kernel<DM, true>;
  auto kD = gemm_kernel<128, 192, 2, DM, 3, EPI_GLU, 1, D_CN, D_CM>;
  auto kE = gemm_res_kernel<DFF, false>;
  constexpr int smA = GemmCfg<256, 128, 1, 4>::SMEM, smC = R_SMEM, smD = GemmCfg<128, 192, 2, 3>::SMEM;
  cudaFuncSetAttribute(kA, cudaFuncAttributeMaxDynamicSharedMemorySize, smA);
  cudaFuncSetAttribute(kC, cudaFuncAttributeMaxDynamicSharedMemorySize, smC);
  cudaFuncSetAttribute(kD, cudaFuncAttributeMaxDynamicSharedMemorySize, smD);
  cudaFuncSetAttribute(kE, cudaFuncAttributeMaxDynamicSharedMemorySize, smC);
  cudaFuncSetAttribute(attn_kernel, cudaFuncAttributeMaxDynamicSharedMemorySize, ATT_SMEM);

  const CUtensorMap tm_x = make_map(x, S_LEN, DM, 256), tm_wqkv = make_map_w(wqkv, DM, 3 * DM, 64, 2);
  const CUtensorMap tm_o = make_map(p_o, S_LEN, DM, 128), tm_wo = make_map_w(wo, DM, DM, 16, 5);
  const CUtensorMap tm_h = make_map(p_h, S_LEN, DM, 128), tm_wg = make_map_w(wgate, DM, DFF, 64, 3), tm_wu = make_map_w(wup, DM, DFF, 64, 3);
  const CUtensorMap tm_act = make_map(p_act, S_LEN, DFF, 128), tm_wd = make_map_w(wdown, DFF, DM, 16, 5);

  launch(pre_kernel, dim3(PRE_COL_BLOCKS + PRE_ROW_BLOCKS), dim3(256), 0, false, dim3(1, 1), x, wqkv);
  launch(kA, dim3(15, 8), dim3(288), smA, true, dim3(A_CN, A_CM), tm_x, tm_wqkv, tm_wqkv, (const __nv_bfloat16*)nullptr, (__nv_bfloat16*)nullptr);
  launch(attn_kernel, dim3(132), dim3(512), ATT_SMEM, true, dim3(1, 1), 0x800000, wgate, wup, wo, wdown);
  launch(kC, dim3(8, 16), dim3(288), smC, true, dim3(1, 1), tm_o, tm_wo, x, (__nv_bfloat16*)p_h);
  launch(kD, dim3(8, 16), dim3(384), smD, true, dim3(D_CN, D_CM), tm_h, tm_wg, tm_wu, (const __nv_bfloat16*)nullptr, (__nv_bfloat16*)p_act);
  launch(kE, dim3(8, 16), dim3(288), smC, true, dim3(1, 1), tm_act, tm_wd, (const __nv_bfloat16*)p_h, out);
}
```

```cpp
#include <cuda_runtime.h>
#include <cuda_bf16.h>
#include <cuda.h>
#include <stdint.h>

constexpr int S_LEN = 2048, DM = 640, NH = 32, DH = 20, DFF = 1536;

__device__ __align__(1024) __nv_bfloat16 g_q[S_LEN * DM];
__device__ __align__(1024) __nv_bfloat16 g_k[NH * S_LEN * 24];
__device__ __align__(1024) __nv_bfloat16 g_v[NH * S_LEN * 24];
__device__ __align__(1024) __nv_bfloat16 g_o[S_LEN * DM];
__device__ __align__(1024) __nv_bfloat16 g_h[S_LEN * DM];
__device__ __align__(1024) __nv_bfloat16 g_act[S_LEN * DFF];
__device__ float g_kn[8 * NH * 2];
__device__ float2 g_stat1[S_LEN];
__device__ float g_cs_qkv[3 * DM];
__device__ float g_cs_g[DFF];
__device__ float g_cs_u[DFF];
__device__ float2 g_part2[S_LEN * 10];

#define TS_BEGIN(k)
#define TS_END(k)
#define TS_MID(k, i)
__device__ __forceinline__ uint32_t smem_u32(const void* p) { return (uint32_t)__cvta_generic_to_shared(p); }
__device__ __forceinline__ void mbar_init(uint32_t bar, uint32_t cnt) { asm volatile("mbarrier.init.shared::cta.b64 [%0], %1;" :: "r"(bar), "r"(cnt)); }
__device__ __forceinline__ void mbar_expect_tx(uint32_t bar, uint32_t bytes) { asm volatile("mbarrier.arrive.expect_tx.shared::cta.b64 _, [%0], %1;" :: "r"(bar), "r"(bytes) : "memory"); }
__device__ __forceinline__ void mbar_arrive(uint32_t bar) { asm volatile("mbarrier.arrive.shared::cta.b64 _, [%0];" :: "r"(bar) : "memory"); }
__device__ __forceinline__ void mbar_wait(uint32_t bar, uint32_t parity) {
  uint32_t done;
  uint32_t spins = 0;
  do {
    asm volatile("{\n.reg .pred P1;\nmbarrier.try_wait.parity.shared::cta.b64 P1, [%1], %2;\nselp.u32 %0, 1, 0, P1;\n}" : "=r"(done) : "r"(bar), "r"(parity) : "memory");
  } while (!done && ++spins < (1u << 24));
}
__device__ __forceinline__ void bulk_g2s(uint32_t dst, const void* src, uint32_t bytes, uint32_t bar) {
  asm volatile("cp.async.bulk.shared::cluster.global.mbarrier::complete_tx::bytes [%0], [%1], %2, [%3];" :: "r"(dst), "l"(src), "r"(bytes), "r"(bar) : "memory");
}
__device__ __forceinline__ void tma_2d(uint32_t dst, const CUtensorMap* tm, int c0, int c1, uint32_t bar) {
  asm volatile("cp.async.bulk.tensor.2d.shared::cluster.global.mbarrier::complete_tx::bytes [%0], [%1, {%3, %4}], [%2];"
               :: "r"(dst), "l"(tm), "r"(bar), "r"(c0), "r"(c1) : "memory");
}
__device__ __forceinline__ void tma_3d(uint32_t dst, const CUtensorMap* tm, int c0, int c1, int c2, uint32_t bar) {
  asm volatile("cp.async.bulk.tensor.3d.shared::cluster.global.mbarrier::complete_tx::bytes [%0], [%1, {%3, %4, %5}], [%2];"
               :: "r"(dst), "l"(tm), "r"(bar), "r"(c0), "r"(c1), "r"(c2) : "memory");
}
__device__ __forceinline__ void tma_2d_mc(uint32_t dst, const CUtensorMap* tm, int c0, int c1, uint32_t bar, uint16_t mask) {
  asm volatile("cp.async.bulk.tensor.2d.shared::cluster.global.mbarrier::complete_tx::bytes.multicast::cluster [%0], [%1, {%3, %4}], [%2], %5;"
               :: "r"(dst), "l"(tm), "r"(bar), "r"(c0), "r"(c1), "h"(mask) : "memory");
}
__device__ __forceinline__ void mbar_arrive_remote(uint32_t bar, uint32_t rank) {
  asm volatile("{\n.reg .b32 ra;\nmapa.shared::cluster.u32 ra, %0, %1;\nmbarrier.arrive.release.cluster.shared::cluster.b64 _, [ra];\n}" :: "r"(bar), "r"(rank) : "memory");
}
__device__ __forceinline__ void cluster_arrive() { asm volatile("barrier.cluster.arrive.release.aligned;" ::: "memory"); }
__device__ __forceinline__ void cluster_wait() { asm volatile("barrier.cluster.wait.acquire.aligned;" ::: "memory"); }
__device__ __forceinline__ void wgmma_fence() { asm volatile("wgmma.fence.sync.aligned;" ::: "memory"); }
__device__ __forceinline__ void wgmma_commit() { asm volatile("wgmma.commit_group.sync.aligned;" ::: "memory"); }
template <int N> __device__ __forceinline__ void wgmma_wait() { asm volatile("wgmma.wait_group.sync.aligned %0;" :: "n"(N) : "memory"); }
__device__ __forceinline__ void pdl_wait() { asm volatile("griddepcontrol.wait;" ::: "memory"); }
__device__ __forceinline__ void pdl_launch() { asm volatile("griddepcontrol.launch_dependents;" ::: "memory"); }
__device__ __forceinline__ void named_bar(int id, int n) { asm volatile("bar.sync %0, %1;" :: "r"(id), "r"(n) : "memory"); }
__device__ __forceinline__ uint64_t make_desc(uint32_t addr, uint32_t lbo, uint32_t sbo, uint32_t swz) {
  return (uint64_t)((addr & 0x3FFFF) >> 4) | ((uint64_t)(lbo >> 4) << 16) | ((uint64_t)(sbo >> 4) << 32) | ((uint64_t)swz << 62);
}
__device__ __forceinline__ void st_g16(void* p, uint4 v) { asm volatile("st.global.v4.b32 [%0], {%1, %2, %3, %4};" :: "l"(p), "r"(v.x), "r"(v.y), "r"(v.z), "r"(v.w) : "memory"); }
__device__ __forceinline__ void st_g8(void* p, uint2 v) { asm volatile("st.global.v2.b32 [%0], {%1, %2};" :: "l"(p), "r"(v.x), "r"(v.y) : "memory"); }
__device__ __forceinline__ uint4 ld_g16(const void* p) { uint4 v; asm volatile("ld.global.v4.b32 {%0, %1, %2, %3}, [%4];" : "=r"(v.x), "=r"(v.y), "=r"(v.z), "=r"(v.w) : "l"(p) : "memory"); return v; }
__device__ __forceinline__ uint32_t pack_bf16(float lo, float hi) { uint32_t r; asm("cvt.rn.bf16x2.f32 %0, %1, %2;" : "=r"(r) : "f"(hi), "f"(lo)); return r; }
__device__ __forceinline__ float bf_lo(uint32_t u) { return __uint_as_float(u << 16); }
__device__ __forceinline__ float bf_hi(uint32_t u) { return __uint_as_float(u & 0xffff0000u); }
__device__ __forceinline__ float bf_round(float x) { return __bfloat162float(__float2bfloat16_rn(x)); }
__device__ __forceinline__ float ex2_mufu(float x) { float y; asm("ex2.approx.ftz.f32 %0, %1;" : "=f"(y) : "f"(x)); return y; }

__device__ __forceinline__ void wgmma_ss_n80(float (&d)[40], uint64_t da, uint64_t db, int scale_d) {
  asm volatile("{\n.reg .pred p;\nsetp.ne.b32 p, %42, 0;\n"
    "wgmma.mma_async.sync.aligned.m64n80k16.f32.bf16.bf16 {%0,%1,%2,%3,%4,%5,%6,%7,%8,%9,%10,%11,%12,%13,%14,%15,%16,%17,%18,%19,%20,%21,%22,%23,%24,%25,%26,%27,%28,%29,%30,%31,%32,%33,%34,%35,%36,%37,%38,%39}, %40, %41, p, 1, 1, 0, 1;\n}\n"
    : "+f"(d[0]),"+f"(d[1]),"+f"(d[2]),"+f"(d[3]),"+f"(d[4]),"+f"(d[5]),"+f"(d[6]),"+f"(d[7]),"+f"(d[8]),"+f"(d[9]),"+f"(d[10]),"+f"(d[11]),"+f"(d[12]),"+f"(d[13]),"+f"(d[14]),"+f"(d[15]),"+f"(d[16]),"+f"(d[17]),"+f"(d[18]),"+f"(d[19]),"+f"(d[20]),"+f"(d[21]),"+f"(d[22]),"+f"(d[23]),"+f"(d[24]),"+f"(d[25]),"+f"(d[26]),"+f"(d[27]),"+f"(d[28]),"+f"(d[29]),"+f"(d[30]),"+f"(d[31]),"+f"(d[32]),"+f"(d[33]),"+f"(d[34]),"+f"(d[35]),"+f"(d[36]),"+f"(d[37]),"+f"(d[38]),"+f"(d[39])
    : "l"(da), "l"(db), "r"(scale_d));
}
__device__ __forceinline__ void wgmma_ss_n128(float (&d)[64], uint64_t da, uint64_t db, int scale_d) {
  asm volatile("{\n.reg .pred p;\nsetp.ne.b32 p, %66, 0;\n"
    "wgmma.mma_async.sync.aligned.m64n128k16.f32.bf16.bf16 {%0,%1,%2,%3,%4,%5,%6,%7,%8,%9,%10,%11,%12,%13,%14,%15,%16,%17,%18,%19,%20,%21,%22,%23,%24,%25,%26,%27,%28,%29,%30,%31,%32,%33,%34,%35,%36,%37,%38,%39,%40,%41,%42,%43,%44,%45,%46,%47,%48,%49,%50,%51,%52,%53,%54,%55,%56,%57,%58,%59,%60,%61,%62,%63}, %64, %65, p, 1, 1, 0, 1;\n}\n"
    : "+f"(d[0]),"+f"(d[1]),"+f"(d[2]),"+f"(d[3]),"+f"(d[4]),"+f"(d[5]),"+f"(d[6]),"+f"(d[7]),"+f"(d[8]),"+f"(d[9]),"+f"(d[10]),"+f"(d[11]),"+f"(d[12]),"+f"(d[13]),"+f"(d[14]),"+f"(d[15]),"+f"(d[16]),"+f"(d[17]),"+f"(d[18]),"+f"(d[19]),"+f"(d[20]),"+f"(d[21]),"+f"(d[22]),"+f"(d[23]),"+f"(d[24]),"+f"(d[25]),"+f"(d[26]),"+f"(d[27]),"+f"(d[28]),"+f"(d[29]),"+f"(d[30]),"+f"(d[31]),"+f"(d[32]),"+f"(d[33]),"+f"(d[34]),"+f"(d[35]),"+f"(d[36]),"+f"(d[37]),"+f"(d[38]),"+f"(d[39]),"+f"(d[40]),"+f"(d[41]),"+f"(d[42]),"+f"(d[43]),"+f"(d[44]),"+f"(d[45]),"+f"(d[46]),"+f"(d[47]),"+f"(d[48]),"+f"(d[49]),"+f"(d[50]),"+f"(d[51]),"+f"(d[52]),"+f"(d[53]),"+f"(d[54]),"+f"(d[55]),"+f"(d[56]),"+f"(d[57]),"+f"(d[58]),"+f"(d[59]),"+f"(d[60]),"+f"(d[61]),"+f"(d[62]),"+f"(d[63])
    : "l"(da), "l"(db), "r"(scale_d));
}
__device__ __forceinline__ void wgmma_ss_n192(float (&d)[96], uint64_t da, uint64_t db, int scale_d) {
  asm volatile("{\n.reg .pred p;\nsetp.ne.b32 p, %98, 0;\n"
    "wgmma.mma_async.sync.aligned.m64n192k16.f32.bf16.bf16 {%0,%1,%2,%3,%4,%5,%6,%7,%8,%9,%10,%11,%12,%13,%14,%15,%16,%17,%18,%19,%20,%21,%22,%23,%24,%25,%26,%27,%28,%29,%30,%31,%32,%33,%34,%35,%36,%37,%38,%39,%40,%41,%42,%43,%44,%45,%46,%47,%48,%49,%50,%51,%52,%53,%54,%55,%56,%57,%58,%59,%60,%61,%62,%63,%64,%65,%66,%67,%68,%69,%70,%71,%72,%73,%74,%75,%76,%77,%78,%79,%80,%81,%82,%83,%84,%85,%86,%87,%88,%89,%90,%91,%92,%93,%94,%95}, %96, %97, p, 1, 1, 0, 1;\n}\n"
    : "+f"(d[0]),"+f"(d[1]),"+f"(d[2]),"+f"(d[3]),"+f"(d[4]),"+f"(d[5]),"+f"(d[6]),"+f"(d[7]),"+f"(d[8]),"+f"(d[9]),"+f"(d[10]),"+f"(d[11]),"+f"(d[12]),"+f"(d[13]),"+f"(d[14]),"+f"(d[15]),"+f"(d[16]),"+f"(d[17]),"+f"(d[18]),"+f"(d[19]),"+f"(d[20]),"+f"(d[21]),"+f"(d[22]),"+f"(d[23]),"+f"(d[24]),"+f"(d[25]),"+f"(d[26]),"+f"(d[27]),"+f"(d[28]),"+f"(d[29]),"+f"(d[30]),"+f"(d[31]),"+f"(d[32]),"+f"(d[33]),"+f"(d[34]),"+f"(d[35]),"+f"(d[36]),"+f"(d[37]),"+f"(d[38]),"+f"(d[39]),"+f"(d[40]),"+f"(d[41]),"+f"(d[42]),"+f"(d[43]),"+f"(d[44]),"+f"(d[45]),"+f"(d[46]),"+f"(d[47]),"+f"(d[48]),"+f"(d[49]),"+f"(d[50]),"+f"(d[51]),"+f"(d[52]),"+f"(d[53]),"+f"(d[54]),"+f"(d[55]),"+f"(d[56]),"+f"(d[57]),"+f"(d[58]),"+f"(d[59]),"+f"(d[60]),"+f"(d[61]),"+f"(d[62]),"+f"(d[63]),"+f"(d[64]),"+f"(d[65]),"+f"(d[66]),"+f"(d[67]),"+f"(d[68]),"+f"(d[69]),"+f"(d[70]),"+f"(d[71]),"+f"(d[72]),"+f"(d[73]),"+f"(d[74]),"+f"(d[75]),"+f"(d[76]),"+f"(d[77]),"+f"(d[78]),"+f"(d[79]),"+f"(d[80]),"+f"(d[81]),"+f"(d[82]),"+f"(d[83]),"+f"(d[84]),"+f"(d[85]),"+f"(d[86]),"+f"(d[87]),"+f"(d[88]),"+f"(d[89]),"+f"(d[90]),"+f"(d[91]),"+f"(d[92]),"+f"(d[93]),"+f"(d[94]),"+f"(d[95])
    : "l"(da), "l"(db), "r"(scale_d));
}
__device__ __forceinline__ void wgmma_rs_n64(float (&d)[32], uint32_t a0, uint32_t a1, uint32_t a2, uint32_t a3, uint64_t db, int scale_d) {
  asm volatile("{\n.reg .pred p;\nsetp.ne.b32 p, %37, 0;\n"
    "wgmma.mma_async.sync.aligned.m64n64k16.f32.bf16.bf16 {%0,%1,%2,%3,%4,%5,%6,%7,%8,%9,%10,%11,%12,%13,%14,%15,%16,%17,%18,%19,%20,%21,%22,%23,%24,%25,%26,%27,%28,%29,%30,%31}, {%32,%33,%34,%35}, %36, p, 1, 1, 0;\n}\n"
    : "+f"(d[0]),"+f"(d[1]),"+f"(d[2]),"+f"(d[3]),"+f"(d[4]),"+f"(d[5]),"+f"(d[6]),"+f"(d[7]),"+f"(d[8]),"+f"(d[9]),"+f"(d[10]),"+f"(d[11]),"+f"(d[12]),"+f"(d[13]),"+f"(d[14]),"+f"(d[15]),"+f"(d[16]),"+f"(d[17]),"+f"(d[18]),"+f"(d[19]),"+f"(d[20]),"+f"(d[21]),"+f"(d[22]),"+f"(d[23]),"+f"(d[24]),"+f"(d[25]),"+f"(d[26]),"+f"(d[27]),"+f"(d[28]),"+f"(d[29]),"+f"(d[30]),"+f"(d[31])
    : "r"(a0), "r"(a1), "r"(a2), "r"(a3), "l"(db), "r"(scale_d));
}
__device__ __forceinline__ void wgmma_rs_n24_tb(float (&d)[12], uint32_t a0, uint32_t a1, uint32_t a2, uint32_t a3, uint64_t db, int scale_d) {
  asm volatile("{\n.reg .pred p;\nsetp.ne.b32 p, %17, 0;\n"
    "wgmma.mma_async.sync.aligned.m64n24k16.f32.bf16.bf16 {%0,%1,%2,%3,%4,%5,%6,%7,%8,%9,%10,%11}, {%12,%13,%14,%15}, %16, p, 1, 1, 1;\n}\n"
    : "+f"(d[0]),"+f"(d[1]),"+f"(d[2]),"+f"(d[3]),"+f"(d[4]),"+f"(d[5]),"+f"(d[6]),"+f"(d[7]),"+f"(d[8]),"+f"(d[9]),"+f"(d[10]),"+f"(d[11])
    : "r"(a0), "r"(a1), "r"(a2), "r"(a3), "l"(db), "r"(scale_d));
}

constexpr int PRE_ROW_BLOCKS = 64;
constexpr int PRE_COL_BLOCKS = 3 * DM / 64;
__device__ __forceinline__ float2 ln_finish(float mean, float var) {
  float mb = bf_round(mean);
  float s = bf_round(sqrtf(bf_round(bf_round(var) + 1e-5f)));
  return make_float2(mb, 1.0f / s);
}
__device__ __forceinline__ void colsum64(const __nv_bfloat16* __restrict__ w, int ld, int c0, float* __restrict__ dst, float (*red)[65], int tid, int bar_id) {
  const int cg = tid & 7, r0 = tid >> 3;
  float acc[8];
#pragma unroll
  for (int i = 0; i < 8; i++) acc[i] = 0.f;
#pragma unroll 10
  for (int r = r0; r < DM; r += 32) {
    uint4 v = __ldg((const uint4*)(w + (size_t)r * ld + c0 + cg * 8));
    acc[0] += bf_lo(v.x); acc[1] += bf_hi(v.x); acc[2] += bf_lo(v.y); acc[3] += bf_hi(v.y);
    acc[4] += bf_lo(v.z); acc[5] += bf_hi(v.z); acc[6] += bf_lo(v.w); acc[7] += bf_hi(v.w);
  }
#pragma unroll
  for (int i = 0; i < 8; i++) red[r0][cg * 8 + i] = acc[i];
  named_bar(bar_id, 256);
  if (tid < 64) {
    float s = 0.f;
#pragma unroll
    for (int r = 0; r < 32; r++) s += red[r][tid];
    dst[c0 + tid] = s;
  }
  named_bar(bar_id, 256);
}
__global__ void __launch_bounds__(1024) pre_kernel(const __nv_bfloat16* __restrict__ x, const __nv_bfloat16* __restrict__ wqkv) {
  TS_BEGIN(0);
  pdl_launch();
  __shared__ float red[51][161];
  const int tid = threadIdx.x, lane = tid & 31, warp = tid >> 5;
  {
    const int ch = tid % 20, rl = tid / 20;
    if (rl < 51) {
      const __nv_bfloat16* w = wqkv + blockIdx.x * 160 + ch * 8;
      uint4 v[13];
#pragma unroll
      for (int i = 0; i < 13; i++) { const int r = rl + i * 51; v[i] = r < DM ? __ldg((const uint4*)(w + (size_t)r * (3 * DM))) : make_uint4(0, 0, 0, 0); }
      float acc[8];
#pragma unroll
      for (int i = 0; i < 8; i++) acc[i] = 0.f;
#pragma unroll
      for (int i = 0; i < 13; i++) {
        acc[0] += bf_lo(v[i].x); acc[1] += bf_hi(v[i].x); acc[2] += bf_lo(v[i].y); acc[3] += bf_hi(v[i].y);
        acc[4] += bf_lo(v[i].z); acc[5] += bf_hi(v[i].z); acc[6] += bf_lo(v[i].w); acc[7] += bf_hi(v[i].w);
      }
#pragma unroll
      for (int i = 0; i < 8; i++) red[rl][ch * 8 + i] = acc[i];
    }
  }
  const int rbeg = blockIdx.x * 171, rend = min(rbeg + 171, S_LEN);
  for (int row0 = rbeg + warp * 2; row0 < rend; row0 += 64) {
    uint4 v[2][3];
#pragma unroll
    for (int k = 0; k < 2; k++) {
      const int row = min(row0 + k, rend - 1);
      const uint4* p = (const uint4*)(x + (size_t)row * DM);
      v[k][0] = __ldg(p + lane); v[k][1] = __ldg(p + 32 + lane);
      v[k][2] = lane < 16 ? __ldg(p + 64 + lane) : make_uint4(0, 0, 0, 0);
    }
#pragma unroll
    for (int k = 0; k < 2; k++) {
      float f[24];
      const uint32_t u[12] = {v[k][0].x, v[k][0].y, v[k][0].z, v[k][0].w, v[k][1].x, v[k][1].y, v[k][1].z, v[k][1].w, v[k][2].x, v[k][2].y, v[k][2].z, v[k][2].w};
#pragma unroll
      for (int j = 0; j < 12; j++) { f[2 * j] = bf_lo(u[j]); f[2 * j + 1] = bf_hi(u[j]); }
      float s = 0.f;
#pragma unroll
      for (int j = 0; j < 24; j++) s += f[j];
#pragma unroll
      for (int o = 16; o; o >>= 1) s += __shfl_xor_sync(~0u, s, o);
      const float mean = s * (1.0f / DM);
      float q = 0.f;
#pragma unroll
      for (int j = 0; j < 16; j++) { const float d = f[j] - mean; q += d * d; }
      if (lane < 16) {
#pragma unroll
        for (int j = 16; j < 24; j++) { const float d = f[j] - mean; q += d * d; }
      }
#pragma unroll
      for (int o = 16; o; o >>= 1) q += __shfl_xor_sync(~0u, q, o);
      if (lane == 0 && row0 + k < rend) g_stat1[row0 + k] = ln_finish(mean, q * (1.0f / DM));
    }
  }
  __syncthreads();
  if (tid < 160) {
    float s = 0.f;
#pragma unroll 17
    for (int r = 0; r < 51; r++) s += red[r][tid];
    g_cs_qkv[blockIdx.x * 160 + tid] = s;
  }
  TS_END(0);
}

enum { EPI_QKV = 0, EPI_WO = 1, EPI_GLU = 2, EPI_DOWN = 3 };
template <int N> struct WG;
template <> struct WG<128> { static __device__ __forceinline__ void mma(float (&d)[64], uint64_t a, uint64_t b, int s) { wgmma_ss_n128(d, a, b, s); } };
template <> struct WG<192> { static __device__ __forceinline__ void mma(float (&d)[96], uint64_t a, uint64_t b, int s) { wgmma_ss_n192(d, a, b, s); } };

template <int BM, int BN, int NB, int STAGES> struct GemmCfg {
  static constexpr int A_BYTES = BM * 128;
  static constexpr int B_BYTES = NB * (BN / 64) * 8192;
  static constexpr int STAGE_BYTES = A_BYTES + B_BYTES;
  static constexpr int SMEM = STAGES * STAGE_BYTES + 1024   + 256   + 4096  ;
};

constexpr float QSCALE = 0.22360679774997896f * 1.4426950408889634f;

template <int BM, int BN, int NB, int KDIM, int STAGES, int EPI, int MINB, int CN, int CM>
__global__ void __launch_bounds__(EPI == EPI_GLU ? 384 : 288, MINB) gemm_kernel(const __grid_constant__ CUtensorMap tmA, const __grid_constant__ CUtensorMap tmB0,
                                                         const __grid_constant__ CUtensorMap tmB1,
                                                         const __nv_bfloat16* resid, __nv_bfloat16* out) {
  using Cfg = GemmCfg<BM, BN, NB, STAGES>;
  constexpr int MB = BM / 128;
  constexpr int KT = KDIM / 64;
  extern __shared__ uint8_t smem_raw[];
  const uint32_t sbase = (smem_u32(smem_raw) + 1023u) & ~1023u;
  uint8_t* sptr = smem_raw + (sbase - smem_u32(smem_raw));
  const uint32_t sbar = sbase + STAGES * Cfg::STAGE_BYTES;
  const int tid = threadIdx.x, warp = tid >> 5, lane = tid & 31;
  const int n0 = blockIdx.x * BN, m0 = blockIdx.y * BM;
  TS_BEGIN(EPI == EPI_QKV ? 1 : EPI + 2);
  TS_MID(EPI == EPI_QKV ? 1 : EPI + 2, 3);
  constexpr int NCL = CN + CM - 1;
  const int cx = blockIdx.x % CN, cy = blockIdx.y % CM;
  if (tid == 0) {
    for (int i = 0; i < STAGES; i++) { mbar_init(sbar + 8 * i, 1); mbar_init(sbar + 8 * (STAGES + i), 2 * NCL); }
    asm volatile("fence.mbarrier_init.release.cluster;" ::: "memory");
  }
  __syncthreads();
  if constexpr (CN * CM > 1) { cluster_arrive(); cluster_wait(); }
  pdl_launch();
  if (warp >= 8) {
    if constexpr (EPI == EPI_GLU) asm volatile("setmaxnreg.dec.sync.aligned.u32 40;");
    if (warp == 8 && lane == 0) {
      auto load_a = [&](int kt, int s) { tma_2d(sbase + s * Cfg::STAGE_BYTES, &tmA, kt * 64, m0, sbar + 8 * s); };
      auto load_b = [&](int kt, int s) {
        const uint32_t sb = sbase + s * Cfg::STAGE_BYTES + Cfg::A_BYTES;
        tma_3d(sb, &tmB0, 0, kt * 64, blockIdx.x * (BN / 64), sbar + 8 * s);
        if constexpr (NB == 2) tma_3d(sb + (BN / 64) * 8192, &tmB1, 0, kt * 64, blockIdx.x * (BN / 64), sbar + 8 * s);
      };
      if constexpr (EPI == EPI_QKV) {
        const int cta = blockIdx.y * gridDim.x + blockIdx.x;
        const uint32_t xb = S_LEN * DM * 2, xs = 21888;
        if (cta * xs < xb) asm volatile("cp.async.bulk.prefetch.L2.global [%0], %1;" :: "l"((const uint8_t*)resid + (size_t)cta * xs), "r"(min(xs, xb - cta * xs)));
        asm volatile("cp.async.bulk.prefetch.L2.global [%0], %1;" :: "l"((const uint8_t*)out + (size_t)cta * 20480), "r"(20480));
      }
      for (int s = 0; s < STAGES; s++) { mbar_expect_tx(sbar + 8 * s, Cfg::STAGE_BYTES); if (EPI != EPI_QKV || s == 0) load_b(s, s); }
      if (EPI != EPI_QKV) pdl_wait();
      for (int s = 0; s < STAGES; s++) { load_a(s, s); if (EPI == EPI_QKV && s > 0) load_b(s, s); }
      for (int kt = STAGES; kt < KT; kt++) {
        const int s = kt % STAGES;
        mbar_wait(sbar + 8 * (STAGES + s), ((kt / STAGES) - 1) & 1);
        mbar_expect_tx(sbar + 8 * s, Cfg::STAGE_BYTES);
        load_a(kt, s);
        load_b(kt, s);
      }
    }
    if constexpr (EPI == EPI_GLU) {
      if (warp > 8) {
        float2* s_st = (float2*)(sptr + STAGES * Cfg::STAGE_BYTES + 256);
        float* s_cs = (float*)(sptr + STAGES * Cfg::STAGE_BYTES + 256 + 1024);
        pdl_wait();
        for (int r = tid - 288; r < BM; r += 96) {
          const float2* pp = &g_part2[(m0 + r) * 8];
          float s = 0.f;
#pragma unroll
          for (int i = 0; i < 8; i++) s += pp[i].x;
          const float mean = s * (1.0f / DM);
          float q = 0.f;
#pragma unroll
          for (int i = 0; i < 8; i++) { const float2 p = pp[i]; const float d = p.x * (1.0f / 80.f) - mean; q += p.y + 80.f * d * d; }
          s_st[r] = ln_finish(mean, q * (1.0f / DM));
        }
        for (int c = tid - 288; c < BN; c += 96) { s_cs[c] = g_cs_g[n0 + c]; s_cs[BN + c] = g_cs_u[n0 + c]; }
        __threadfence_block();
        asm volatile("bar.arrive 2, 352;" ::: "memory");
      }
    }
    if constexpr (CN * CM > 1) { __syncwarp(); cluster_arrive(); cluster_wait(); }
    return;
  }
  if constexpr (EPI == EPI_GLU) asm volatile("setmaxnreg.inc.sync.aligned.u32 232;");
  const int wg = warp >> 2, g = lane >> 2, t = lane & 3;
  float acc[MB][NB][BN / 2];
#pragma unroll
  for (int mb = 0; mb < MB; mb++)
#pragma unroll
    for (int nb = 0; nb < NB; nb++)
#pragma unroll
      for (int i = 0; i < BN / 2; i++) acc[mb][nb][i] = 0.f;
  for (int kt = 0; kt < KT; kt++) {
    const int s = kt % STAGES;
    mbar_wait(sbar + 8 * s, (kt / STAGES) & 1);
    if (kt == 0) TS_MID(EPI == EPI_QKV ? 1 : EPI + 2, 0);
    const uint32_t sa = sbase + s * Cfg::STAGE_BYTES + wg * (MB * 64 * 128);
    const uint32_t sb = sbase + s * Cfg::STAGE_BYTES + Cfg::A_BYTES;
    wgmma_fence();
#pragma unroll
    for (int ks = 0; ks < 4; ks++) {
#pragma unroll
      for (int mb = 0; mb < MB; mb++) {
        const uint64_t da = make_desc(sa + mb * 8192 + ks * 32, 16, 1024, 1);
#pragma unroll
        for (int nb = 0; nb < NB; nb++) {
          const uint64_t db = make_desc(sb + nb * (BN / 64) * 8192 + ks * 2048, 8192, 1024, 1);
          WG<BN>::mma(acc[mb][nb], da, db, 1);
        }
      }
    }
    wgmma_commit();
    wgmma_wait<1>();
    if (kt > 0 && kt - 1 + STAGES < KT && (tid & 127) < NCL) {
      const uint32_t eb = sbar + 8 * (STAGES + (kt - 1) % STAGES);
      if constexpr (CN * CM > 1) {
        const int i = tid & 127;
        const uint32_t rank = i < CN ? cy * CN + i : ((i - CN + (i - CN >= cy ? 1 : 0)) * CN + cx);
        mbar_arrive_remote(eb, rank);
      } else mbar_arrive(eb);
    }
  }
  wgmma_wait<0>();
#pragma unroll
  for (int mb = 0; mb < MB; mb++)
#pragma unroll
    for (int nb = 0; nb < NB; nb++)
#pragma unroll
      for (int i = 0; i < BN / 2; i++) asm volatile("" : "+f"(acc[mb][nb][i]) :: "memory");
  if constexpr (CN * CM > 1) cluster_arrive();
  TS_MID(EPI == EPI_QKV ? 1 : EPI + 2, 1);
  pdl_wait();
  TS_MID(EPI == EPI_QKV ? 1 : EPI + 2, 2);
  named_bar(1, 256);
  constexpr int LDS = BN * 2 + 16;
  const int ctid = tid;

  if constexpr (EPI == EPI_QKV) {
    const int sec = n0 / DM;
#pragma unroll
    for (int mb = 0; mb < MB; mb++) {
      const int r0 = wg * (MB * 64) + mb * 64 + (warp & 3) * 16 + g;
      const float2 st0 = g_stat1[m0 + r0], st1 = g_stat1[m0 + r0 + 8];
      const float sc0 = sec == 0 ? st0.y * QSCALE : st0.y, sc1 = sec == 0 ? st1.y * QSCALE : st1.y;
#pragma unroll
      for (int j = 0; j < BN / 8; j++) {
        const float2 cs = *(const float2*)&g_cs_qkv[n0 + j * 8 + 2 * t];
        const float* a = &acc[mb][0][4 * j];
        *(uint32_t*)(sptr + r0 * LDS + j * 16 + t * 4) = pack_bf16((a[0] - st0.x * cs.x) * sc0, (a[1] - st0.x * cs.y) * sc0);
        *(uint32_t*)(sptr + (r0 + 8) * LDS + j * 16 + t * 4) = pack_bf16((a[2] - st1.x * cs.x) * sc1, (a[3] - st1.x * cs.y) * sc1);
      }
    }
    named_bar(1, 256);
    if (sec == 0) {
#pragma unroll
      for (int i = 0; i < BM * (BN / 8) / 256; i++) {
        const int idx = i * 256 + ctid, r = idx / (BN / 8), c = idx % (BN / 8);
        st_g16(g_q + (size_t)(m0 + r) * DM + n0 + c * 8, *(const uint4*)(sptr + r * LDS + c * 16));
      }
    } else {
      __nv_bfloat16* dst = sec == 1 ? g_k : g_v;
      const int cbase = n0 - sec * DM;
#pragma unroll 4
      for (int i = 0; i < BM * (BN / 4) / 256; i++) {
        const int idx = i * 256 + ctid;
        const int half = idx & 1, r8 = (idx >> 1) & 7, rest = idx >> 4;
        const int pq = rest % (BN / 8), rg = rest / (BN / 8);
        const int r = rg * 8 + r8, cq = pq * 2 + half;
        const int col = cbase + cq * 4, h = col / DH, qd = (col % DH) >> 2;
        const uint2 v = *(const uint2*)(sptr + r * LDS + cq * 8);
        const int j = m0 + r;
        uint8_t* p = (uint8_t*)dst + ((size_t)h * S_LEN * 24 + (j >> 3) * 192 + (qd >> 1) * 64 + (j & 7) * 8 + (qd & 1) * 4) * 2;
        if (qd == 4) st_g16(p, make_uint4(v.x, v.y, 0x00003f80u, 0u));
        else st_g8(p, v);
      }
      if (sec == 1) {
        __shared__ unsigned int s_kn[8];
        if (ctid < 8) s_kn[ctid] = 0u;
        named_bar(1, 256);
        const int hfirst = cbase / DH, hlast = (cbase + BN - 1) / DH;
        for (int hh = hfirst; hh <= hlast; hh++) {
          const int c_lo = max(hh * DH, cbase) - cbase, c_hi = min(hh * DH + DH, cbase + BN) - cbase;
          float mx = 0.f;
          for (int r = ctid; r < BM; r += 256) {
            float s = 0.f;
            for (int c = c_lo; c < c_hi; c += 4) {
              const uint2 v = *(const uint2*)(sptr + r * LDS + c * 2);
              s += bf_lo(v.x) * bf_lo(v.x) + bf_hi(v.x) * bf_hi(v.x) + bf_lo(v.y) * bf_lo(v.y) + bf_hi(v.y) * bf_hi(v.y);
            }
            mx = (s > mx || s != s) ? s : mx;
          }
          unsigned int mb_ = __float_as_uint(mx) & 0x7fffffffu;
          mb_ = __reduce_max_sync(~0u, mb_);
          if (lane == 0) atomicMax(&s_kn[hh - hfirst], mb_);
        }
        named_bar(1, 256);
        if (ctid <= hlast - hfirst) {
          const int hh = hfirst + ctid;
          const bool starts_here = hh * DH >= cbase, ends_here = hh * DH + DH <= cbase + BN;
          const float v = __uint_as_float(s_kn[ctid]);
          float* o = &g_kn[(blockIdx.y * NH + hh) * 2];
          if (starts_here) { o[0] = v; if (ends_here) o[1] = 0.f; }
          else o[1] = v;
        }
      }
    }
  } else if constexpr (EPI == EPI_WO || EPI == EPI_DOWN) {
    const int r0 = wg * 64 + (warp & 3) * 16 + g;
#pragma unroll
    for (int j = 0; j < BN / 8; j++) {
      const float* a = &acc[0][0][4 * j];
      *(uint32_t*)(sptr + r0 * LDS + j * 16 + t * 4) = pack_bf16(a[0], a[1]);
      *(uint32_t*)(sptr + (r0 + 8) * LDS + j * 16 + t * 4) = pack_bf16(a[2], a[3]);
    }
    named_bar(1, 256);
#pragma unroll
    for (int i = 0; i < BM * (BN / 8) / 256; i++) {
      const int idx = i * 256 + ctid, r = idx / (BN / 8), c = idx % (BN / 8);
      const uint4 a = *(const uint4*)(sptr + r * LDS + c * 16);
      const size_t go = (size_t)(m0 + r) * DM + n0 + c * 8;
      const uint4 b = ld_g16(resid + go);
      uint4 o;
      o.x = pack_bf16(bf_lo(a.x) + bf_lo(b.x), bf_hi(a.x) + bf_hi(b.x));
      o.y = pack_bf16(bf_lo(a.y) + bf_lo(b.y), bf_hi(a.y) + bf_hi(b.y));
      o.z = pack_bf16(bf_lo(a.z) + bf_lo(b.z), bf_hi(a.z) + bf_hi(b.z));
      o.w = pack_bf16(bf_lo(a.w) + bf_lo(b.w), bf_hi(a.w) + bf_hi(b.w));
      st_g16(out + go, o);
      if constexpr (EPI == EPI_WO) {
        static_assert(BN == 64, "stats assume 8 lanes per row");
        const float f[8] = {bf_lo(o.x), bf_hi(o.x), bf_lo(o.y), bf_hi(o.y), bf_lo(o.z), bf_hi(o.z), bf_lo(o.w), bf_hi(o.w)};
        float s = 0.f;
#pragma unroll
        for (int k = 0; k < 8; k++) s += f[k];
        s += __shfl_xor_sync(~0u, s, 1); s += __shfl_xor_sync(~0u, s, 2); s += __shfl_xor_sync(~0u, s, 4);
        const float mu = s * (1.0f / 64.f);
        float q = 0.f;
#pragma unroll
        for (int k = 0; k < 8; k++) { const float d = f[k] - mu; q += d * d; }
        q += __shfl_xor_sync(~0u, q, 1); q += __shfl_xor_sync(~0u, q, 2); q += __shfl_xor_sync(~0u, q, 4);
        if (c == 0) g_part2[(m0 + r) * 10 + blockIdx.x] = make_float2(s, q);
      }
    }
  } else {
    const int r0 = wg * 64 + (warp & 3) * 16 + g;
    const float2* s_st = (const float2*)(sptr + STAGES * Cfg::STAGE_BYTES + 256);
    const float* s_cs = (const float*)(sptr + STAGES * Cfg::STAGE_BYTES + 256 + 1024);
    named_bar(2, 352);
    float2 st[2] = {s_st[r0], s_st[r0 + 8]};
#pragma unroll
    for (int j = 0; j < BN / 8; j++) {
      const float2 cg = *(const float2*)&s_cs[j * 8 + 2 * t], cu = *(const float2*)&s_cs[BN + j * 8 + 2 * t];
      const float* a = &acc[0][0][4 * j];
      const float* b = &acc[0][1][4 * j];
#pragma unroll
      for (int e = 0; e < 2; e++) {
        const float2 s_ = st[e];
        const uint32_t gp = pack_bf16(fmaf(-s_.x, cg.x, a[2 * e]) * s_.y, fmaf(-s_.x, cg.y, a[2 * e + 1]) * s_.y);
        const uint32_t up = pack_bf16(fmaf(-s_.x, cu.x, b[2 * e]) * s_.y, fmaf(-s_.x, cu.y, b[2 * e + 1]) * s_.y);
        uint32_t r;
        asm("{\n.reg .b32 z;\nmax.bf16x2 z, %1, %3;\nmul.rn.bf16x2 %0, z, %2;\n}" : "=r"(r) : "r"(gp), "r"(up), "r"(0u));
        *(uint32_t*)(sptr + (r0 + 8 * e) * LDS + j * 16 + t * 4) = r;
      }
    }
    named_bar(1, 256);
#pragma unroll
    for (int i = 0; i < BM * (BN / 8) / 256; i++) {
      const int idx = i * 256 + ctid, r = idx / (BN / 8), c = idx % (BN / 8);
      st_g16(out + (size_t)(m0 + r) * DFF + n0 + c * 8, *(const uint4*)(sptr + r * LDS + c * 16));
    }
  }
  if constexpr (CN * CM > 1) cluster_wait();
  TS_END(EPI == EPI_QKV ? 1 : EPI + 2);
}

constexpr int R_STAGES = 8;
constexpr int R_STAGE_BYTES = 16384 + 5 * 2048;
constexpr int R_BAR_OFF = R_STAGES * R_STAGE_BYTES;
constexpr int R_SMEM = R_BAR_OFF + 256 + 1024;
template <int KDIM, bool STATS>
__global__ void __launch_bounds__(288, 1) gemm_res_kernel(const __grid_constant__ CUtensorMap tmA, const __grid_constant__ CUtensorMap tmB,
                                                          const __nv_bfloat16* resid, __nv_bfloat16* out) {
  constexpr int KT = KDIM / 64;
  extern __shared__ uint8_t smem_raw[];
  const uint32_t sbase = (smem_u32(smem_raw) + 1023u) & ~1023u;
  uint8_t* sptr = smem_raw + (sbase - smem_u32(smem_raw));
  const uint32_t sbar = sbase + R_BAR_OFF;
  const int tid = threadIdx.x, warp = tid >> 5, lane = tid & 31;
  const int n0 = blockIdx.x * 80, m0 = blockIdx.y * 128;
  TS_BEGIN(STATS ? 3 : 5);
  if (tid == 0) {
    for (int i = 0; i < R_STAGES; i++) { mbar_init(sbar + 8 * i, 1); mbar_init(sbar + 8 * (R_STAGES + i), 2); }
    asm volatile("fence.mbarrier_init.release.cluster;" ::: "memory");
  }
  __syncthreads();
  pdl_launch();
  if (warp == 8) {
    if (lane == 0) {
      auto load_b = [&](int kt, int s) { tma_3d(sbase + s * R_STAGE_BYTES + 16384, &tmB, 0, kt * 64, blockIdx.x * 5, sbar + 8 * s); };
      for (int s = 0; s < R_STAGES; s++) { mbar_expect_tx(sbar + 8 * s, R_STAGE_BYTES); if (s < 3) load_b(s, s); }
      pdl_wait();
      for (int s = 0; s < R_STAGES; s++) { tma_2d(sbase + s * R_STAGE_BYTES, &tmA, s * 64, m0, sbar + 8 * s); if (s >= 3) load_b(s, s); }
      for (int kt = R_STAGES; kt < KT; kt++) {
        const int s = kt % R_STAGES;
        mbar_wait(sbar + 8 * (R_STAGES + s), ((kt / R_STAGES) - 1) & 1);
        mbar_expect_tx(sbar + 8 * s, R_STAGE_BYTES);
        tma_2d(sbase + s * R_STAGE_BYTES, &tmA, kt * 64, m0, sbar + 8 * s);
        load_b(kt, s);
      }
    }
    return;
  }
  const int wg = warp >> 2, g = lane >> 2, t = lane & 3;
  pdl_wait();
  uint4 rv[5];
#pragma unroll
  for (int i = 0; i < 5; i++) {
    const int idx = i * 256 + tid, r = idx / 10, c = idx % 10;
    rv[i] = ld_g16(resid + (size_t)(m0 + r) * DM + n0 + c * 8);
  }
  float acc[40];
#pragma unroll
  for (int i = 0; i < 40; i++) acc[i] = 0.f;
  for (int kt = 0; kt < KT; kt++) {
    const int s = kt % R_STAGES;
    mbar_wait(sbar + 8 * s, (kt / R_STAGES) & 1);
    if (kt == 0) TS_MID(STATS ? 3 : 5, 0);
    const uint32_t sa = sbase + s * R_STAGE_BYTES + wg * 8192;
    const uint32_t sb = sbase + s * R_STAGE_BYTES + 16384;
    wgmma_fence();
#pragma unroll
    for (int ks = 0; ks < 4; ks++)
      wgmma_ss_n80(acc, make_desc(sa + ks * 32, 16, 1024, 1), make_desc(sb + ks * 512, 2048, 256, 3), 1);
    wgmma_commit();
    wgmma_wait<1>();
    if (kt > 0 && kt - 1 + R_STAGES < KT && (tid & 127) == 0) mbar_arrive(sbar + 8 * (R_STAGES + (kt - 1) % R_STAGES));
  }
  wgmma_wait<0>();
#pragma unroll
  for (int i = 0; i < 40; i++) asm volatile("" : "+f"(acc[i]) :: "memory");
  TS_MID(STATS ? 3 : 5, 1);
  named_bar(1, 256);
  constexpr int LDS = 176;
  const int r0 = wg * 64 + (warp & 3) * 16 + g;
#pragma unroll
  for (int i = 0; i < 10; i++) {
    *(uint32_t*)(sptr + r0 * LDS + i * 16 + t * 4) = pack_bf16(acc[4 * i], acc[4 * i + 1]);
    *(uint32_t*)(sptr + (r0 + 8) * LDS + i * 16 + t * 4) = pack_bf16(acc[4 * i + 2], acc[4 * i + 3]);
  }
  named_bar(1, 256);
  TS_MID(STATS ? 3 : 5, 2);
#pragma unroll
  for (int i = 0; i < 5; i++) {
    const int idx = i * 256 + tid, r = idx / 10, c = idx % 10;
    const uint4 a = *(const uint4*)(sptr + r * LDS + c * 16);
    const uint4 b = rv[i];
    uint4 o;
    o.x = pack_bf16(bf_lo(a.x) + bf_lo(b.x), bf_hi(a.x) + bf_hi(b.x));
    o.y = pack_bf16(bf_lo(a.y) + bf_lo(b.y), bf_hi(a.y) + bf_hi(b.y));
    o.z = pack_bf16(bf_lo(a.z) + bf_lo(b.z), bf_hi(a.z) + bf_hi(b.z));
    o.w = pack_bf16(bf_lo(a.w) + bf_lo(b.w), bf_hi(a.w) + bf_hi(b.w));
    st_g16(out + (size_t)(m0 + r) * DM + n0 + c * 8, o);
    if constexpr (STATS) *(uint4*)(sptr + r * LDS + c * 16) = o;
  }
  TS_MID(STATS ? 3 : 5, 3);
  if constexpr (STATS) {
    named_bar(1, 256);
    const int r = tid >> 1, hf = tid & 1;
    float f[40];
#pragma unroll
    for (int i = 0; i < 5; i++) {
      const uint4 v = *(const uint4*)(sptr + r * LDS + hf * 80 + i * 16);
      f[8 * i] = bf_lo(v.x); f[8 * i + 1] = bf_hi(v.x); f[8 * i + 2] = bf_lo(v.y); f[8 * i + 3] = bf_hi(v.y);
      f[8 * i + 4] = bf_lo(v.z); f[8 * i + 5] = bf_hi(v.z); f[8 * i + 6] = bf_lo(v.w); f[8 * i + 7] = bf_hi(v.w);
    }
    float s = 0.f;
#pragma unroll
    for (int i = 0; i < 40; i++) s += f[i];
    s += __shfl_xor_sync(~0u, s, 1);
    const float mu = s * (1.0f / 80.f);
    float q = 0.f;
#pragma unroll
    for (int i = 0; i < 40; i++) { const float d = f[i] - mu; q += d * d; }
    q += __shfl_xor_sync(~0u, q, 1);
    if (hf == 0) g_part2[(m0 + r) * 8 + blockIdx.x] = make_float2(s, q);
  }
  TS_END(STATS ? 3 : 5);
}

#define POLY_NUM 5
__device__ __forceinline__ float ex2_poly(float x, int shl23) {
  const float MAGIC = 12582912.f;
  const float tt = x + MAGIC;
  const float f = x - (tt - MAGIC);
  float p = fmaf(0.0013276472454890609f, f, 0.009675540961325169f);
  p = fmaf(p, f, 0.05550713092088699f);
  p = fmaf(p, f, 0.24022120237350464f);
  p = fmaf(p, f, 0.6931469440460205f);
  p = fmaf(p, f, 1.0000001192092896f);
  return __int_as_float(__float_as_int(tt) * shl23 + __float_as_int(p));
}
constexpr int KV_BYTES = S_LEN * 48;
constexpr int ATT_SMEM = 2 * KV_BYTES + 256;

__global__ void __launch_bounds__(512, 1) attn_kernel(int shl23, const __nv_bfloat16* __restrict__ wg_, const __nv_bfloat16* __restrict__ wu_,
                                                      const __nv_bfloat16* __restrict__ wo_, const __nv_bfloat16* __restrict__ wd_) {
  extern __shared__ __align__(1024) uint8_t smem[];
  if (blockIdx.x >= 128) {
    pdl_launch();
    const int e = blockIdx.x - 128, half = threadIdx.x >> 8;
    if (threadIdx.x == 0) {
      for (int i = 0; i < 13; i++) asm volatile("cp.async.bulk.prefetch.L2.global [%0], %1;" :: "l"((const uint8_t*)wo_ + (e * 13 + i) * 16384 * 0 + (size_t)(e * 13 + i >= 50 ? 0 : (e * 13 + i)) * 16384), "r"(16384));
      for (int i = 0; i < 30; i++) asm volatile("cp.async.bulk.prefetch.L2.global [%0], %1;" :: "l"((const uint8_t*)wd_ + (size_t)(e * 30 + i) * 16384), "r"(16384));
    }
    float (*red)[65] = (float (*)[65])(smem + half * 16384);
    for (int b = e * 12 + half; b < e * 12 + 12; b += 2) {
      if (b < 24) colsum64(wg_, DFF, b * 64, g_cs_g, red, threadIdx.x & 255, 1 + half);
      else colsum64(wu_, DFF, (b - 24) * 64, g_cs_u, red, threadIdx.x & 255, 1 + half);
    }
    return;
  }
  const int h = blockIdx.x >> 2, qb = blockIdx.x & 3;
  const uint32_t sK = smem_u32(smem), sV = sK + KV_BYTES, sBar = sV + KV_BYTES;
  const int tid = threadIdx.x;
  TS_BEGIN(2);
  if (tid == 0) {
    for (int i = 0; i < 8; i++) mbar_init(sBar + 8 * i, 1);
    asm volatile("fence.mbarrier_init.release.cluster;" ::: "memory");
  }
  pdl_launch();
  pdl_wait();
  if (tid == 0) {
    const uint8_t* gk = (const uint8_t*)(g_k + (size_t)h * S_LEN * 24);
    const uint8_t* gv = (const uint8_t*)(g_v + (size_t)h * S_LEN * 24);
    for (int i = 0; i < 8; i++) {
      mbar_expect_tx(sBar + 8 * i, 2 * 12288);
      bulk_g2s(sK + i * 12288, gk + i * 12288, 12288, sBar + 8 * i);
      bulk_g2s(sV + i * 12288, gv + i * 12288, 12288, sBar + 8 * i);
    }
  }
  __syncthreads();
  const int wg = tid >> 7, warp = (tid >> 5) & 3, lane = tid & 31, g = lane >> 2, t = lane & 3;
  float ka = 0.f, kb = 0.f;
#pragma unroll
  for (int i = 0; i < 8; i++) {
    const float2 v = *(const float2*)&g_kn[(i * NH + h) * 2];
    ka = (v.x > ka || v.x != v.x) ? v.x : ka;
    kb = (v.y > kb || v.y != v.y) ? v.y : kb;
  }
  const float kn = sqrtf(ka + kb);
  for (int it = 0; it < 2; it++) {
    const int q0 = qb * 512 + (it * 4 + wg) * 64 + warp * 16;
    uint32_t qa[4], qc[4];
    const uint32_t* qr0 = (const uint32_t*)(g_q + (size_t)(q0 + g) * DM + h * DH);
    const uint32_t* qr1 = (const uint32_t*)(g_q + (size_t)(q0 + g + 8) * DM + h * DH);
    qa[0] = qr0[t]; qa[1] = qr1[t]; qa[2] = qr0[t + 4]; qa[3] = qr1[t + 4];
    qc[0] = (t < 2) ? qr0[t + 8] : 0u; qc[1] = (t < 2) ? qr1[t + 8] : 0u; qc[2] = 0; qc[3] = 0;
    auto sq = [](uint32_t u) { const float a = bf_lo(u), b = bf_hi(u); return a * a + b * b; };
    float n0 = sq(qa[0]) + sq(qa[2]) + sq(qc[0]);
    float n1 = sq(qa[1]) + sq(qa[3]) + sq(qc[1]);
    n0 += __shfl_xor_sync(~0u, n0, 1); n0 += __shfl_xor_sync(~0u, n0, 2);
    n1 += __shfl_xor_sync(~0u, n1, 1); n1 += __shfl_xor_sync(~0u, n1, 2);
    const float m0 = ceilf(sqrtf(n0) * kn * 1.001f) + 1.f, m1 = ceilf(sqrtf(n1) * kn * 1.001f) + 1.f;
    const bool unsafe = !(m0 <= 62.f && m1 <= 62.f);
    uint32_t any_unsafe;
    asm volatile("{\n.reg .pred p, q;\nsetp.ne.u32 p, %1, 0;\nbarrier.cta.red.or.pred q, %2, 128, p;\nselp.u32 %0, 1, 0, q;\n}"
                 : "=r"(any_unsafe) : "r"((uint32_t)unsafe), "r"(1 + wg) : "memory");
    float O[12];
    float S[32];
    if (!__any_sync(~0u, any_unsafe)) {
      if (t == 2) { qc[0] = pack_bf16(-m0, 0.f); qc[1] = pack_bf16(-m1, 0.f); }
      for (int j = 0; j < 32; j++) {
        if (it == 0 && (j & 3) == 0) mbar_wait(sBar + 8 * (j >> 2), 0);
        const uint64_t dk = make_desc(sK + j * 8 * 384, 128, 384, 0);
        wgmma_fence();
        wgmma_rs_n64(S, qa[0], qa[1], qa[2], qa[3], dk, 0);
        wgmma_rs_n64(S, qc[0], qc[1], qc[2], qc[3], dk + (256 >> 4), 1);
        wgmma_commit();
        wgmma_wait<0>();
        uint32_t P[16];
#pragma unroll
        for (int i = 0; i < 16; i++) {
          const bool usepoly = ((i + 1) * POLY_NUM / 16) != (i * POLY_NUM / 16);
          float a, b;
          if (usepoly) { a = ex2_poly(S[2 * i], shl23); b = ex2_poly(S[2 * i + 1], shl23); }
          else { a = ex2_mufu(S[2 * i]); b = ex2_mufu(S[2 * i + 1]); }
          P[i] = pack_bf16(a, b);
        }
        wgmma_fence();
        const uint64_t dv = make_desc(sV + j * 8 * 384, 384, 128, 0);
#pragma unroll
        for (int ks = 0; ks < 4; ks++)
          wgmma_rs_n24_tb(O, P[4 * ks], P[4 * ks + 1], P[4 * ks + 2], P[4 * ks + 3], dv + ((ks * 768) >> 4), (j | ks) != 0);
        wgmma_commit();
      }
    } else {
      float mx0 = -INFINITY, mx1 = -INFINITY;
      for (int j = 0; j < 32; j++) {
        if (it == 0 && (j & 3) == 0) mbar_wait(sBar + 8 * (j >> 2), 0);
        const uint64_t dk = make_desc(sK + j * 8 * 384, 128, 384, 0);
        wgmma_fence();
        wgmma_rs_n64(S, qa[0], qa[1], qa[2], qa[3], dk, 0);
        wgmma_rs_n64(S, qc[0], qc[1], qc[2], qc[3], dk + (256 >> 4), 1);
        wgmma_commit();
        wgmma_wait<0>();
#pragma unroll
        for (int i = 0; i < 8; i++) {
          mx0 = fmaxf(mx0, fmaxf(S[4 * i], S[4 * i + 1]));
          mx1 = fmaxf(mx1, fmaxf(S[4 * i + 2], S[4 * i + 3]));
        }
      }
      mx0 = fmaxf(mx0, __shfl_xor_sync(~0u, mx0, 1)); mx0 = fmaxf(mx0, __shfl_xor_sync(~0u, mx0, 2));
      mx1 = fmaxf(mx1, __shfl_xor_sync(~0u, mx1, 1)); mx1 = fmaxf(mx1, __shfl_xor_sync(~0u, mx1, 2));
      for (int j = 0; j < 32; j++) {
        const uint64_t dk = make_desc(sK + j * 8 * 384, 128, 384, 0);
        wgmma_fence();
        wgmma_rs_n64(S, qa[0], qa[1], qa[2], qa[3], dk, 0);
        wgmma_rs_n64(S, qc[0], qc[1], qc[2], qc[3], dk + (256 >> 4), 1);
        wgmma_commit();
        wgmma_wait<0>();
        uint32_t P[16];
#pragma unroll
        for (int i = 0; i < 8; i++) {
          P[2 * i] = pack_bf16(ex2_mufu(S[4 * i] - mx0), ex2_mufu(S[4 * i + 1] - mx0));
          P[2 * i + 1] = pack_bf16(ex2_mufu(S[4 * i + 2] - mx1), ex2_mufu(S[4 * i + 3] - mx1));
        }
        wgmma_fence();
        const uint64_t dv = make_desc(sV + j * 8 * 384, 384, 128, 0);
#pragma unroll
        for (int ks = 0; ks < 4; ks++)
          wgmma_rs_n24_tb(O, P[4 * ks], P[4 * ks + 1], P[4 * ks + 2], P[4 * ks + 3], dv + ((ks * 768) >> 4), (j | ks) != 0);
        wgmma_commit();
      }
    }
    wgmma_wait<0>();
#pragma unroll
    for (int i = 0; i < 12; i++) asm volatile("" : "+f"(O[i]) :: "memory");
    const float l0 = __shfl_sync(~0u, O[8], (lane & ~3) | 2), l1 = __shfl_sync(~0u, O[10], (lane & ~3) | 2);
    const float r0 = 1.f / l0, r1 = 1.f / l1;
    uint32_t* o0 = (uint32_t*)(g_o + (size_t)(q0 + g) * DM + h * DH);
    uint32_t* o1 = (uint32_t*)(g_o + (size_t)(q0 + g + 8) * DM + h * DH);
    o0[t] = pack_bf16(O[0] * r0, O[1] * r0); o1[t] = pack_bf16(O[2] * r1, O[3] * r1);
    o0[t + 4] = pack_bf16(O[4] * r0, O[5] * r0); o1[t + 4] = pack_bf16(O[6] * r1, O[7] * r1);
    if (t < 2) { o0[t + 8] = pack_bf16(O[8] * r0, O[9] * r0); o1[t + 8] = pack_bf16(O[10] * r1, O[11] * r1); }
  }
  TS_END(2);
}

typedef CUresult (*EncodeFn)(CUtensorMap*, CUtensorMapDataType, cuuint32_t, void*, const cuuint64_t*, const cuuint64_t*, const cuuint32_t*,
                             const cuuint32_t*, CUtensorMapInterleave, CUtensorMapSwizzle, CUtensorMapL2promotion, CUtensorMapFloatOOBfill);
static EncodeFn get_encode() {
  static EncodeFn fn = nullptr;
  if (!fn) {
    void* p = nullptr; cudaDriverEntryPointQueryResult st;
    cudaGetDriverEntryPoint("cuTensorMapEncodeTiled", &p, cudaEnableDefault, &st);
    fn = (EncodeFn)p;
  }
  return fn;
}
static CUtensorMap make_map(const void* ptr, int rows, int cols, int box_rows, int box_cols = 64) {
  CUtensorMap m;
  cuuint64_t dims[2] = {(cuuint64_t)cols, (cuuint64_t)rows};
  cuuint64_t strides[1] = {(cuuint64_t)cols * 2};
  cuuint32_t box[2] = {(cuuint32_t)box_cols, (cuuint32_t)box_rows};
  cuuint32_t es[2] = {1, 1};
  get_encode()(&m, CU_TENSOR_MAP_DATA_TYPE_BFLOAT16, 2, const_cast<void*>(ptr), dims, strides, box, es, CU_TENSOR_MAP_INTERLEAVE_NONE,
               box_cols == 64 ? CU_TENSOR_MAP_SWIZZLE_128B : (box_cols == 32 ? CU_TENSOR_MAP_SWIZZLE_64B : CU_TENSOR_MAP_SWIZZLE_32B), CU_TENSOR_MAP_L2_PROMOTION_L2_128B, CU_TENSOR_MAP_FLOAT_OOB_FILL_NONE);
  return m;
}
static CUtensorMap make_map_w(const void* ptr, int rows, int cols, int bc, int nblk) {
  CUtensorMap m;
  cuuint64_t dims[3] = {(cuuint64_t)bc, (cuuint64_t)rows, (cuuint64_t)(cols / bc)};
  cuuint64_t strides[2] = {(cuuint64_t)cols * 2, (cuuint64_t)bc * 2};
  cuuint32_t box[3] = {(cuuint32_t)bc, 64, (cuuint32_t)nblk};
  cuuint32_t es[3] = {1, 1, 1};
  get_encode()(&m, CU_TENSOR_MAP_DATA_TYPE_BFLOAT16, 3, const_cast<void*>(ptr), dims, strides, box, es, CU_TENSOR_MAP_INTERLEAVE_NONE,
               bc == 64 ? CU_TENSOR_MAP_SWIZZLE_128B : (bc == 32 ? CU_TENSOR_MAP_SWIZZLE_64B : CU_TENSOR_MAP_SWIZZLE_32B),
               CU_TENSOR_MAP_L2_PROMOTION_L2_128B, CU_TENSOR_MAP_FLOAT_OOB_FILL_NONE);
  return m;
}
template <typename... KArgs, typename... Args>
static void launch(void (*kern)(KArgs...), dim3 grid, dim3 block, size_t smem, bool pdl, dim3 cluster, Args... args) {
  cudaLaunchConfig_t cfg = {};
  cfg.gridDim = grid; cfg.blockDim = block; cfg.dynamicSmemBytes = smem; cfg.stream = cudaStreamPerThread;
  cudaLaunchAttribute at[2];
  int na = 0;
  if (pdl) { at[na].id = cudaLaunchAttributeProgrammaticStreamSerialization; at[na].val.programmaticStreamSerializationAllowed = 1; na++; }
  if (cluster.x * cluster.y > 1) { at[na].id = cudaLaunchAttributeClusterDimension; at[na].val.clusterDim.x = cluster.x; at[na].val.clusterDim.y = cluster.y; at[na].val.clusterDim.z = 1; na++; }
  cfg.attrs = at; cfg.numAttrs = na;
  cudaLaunchKernelEx(&cfg, kern, KArgs(args)...);
}

extern "C" void kernel_launch(void* const* d_in, const int* in_sizes, int n_in, void* d_out, int out_size) {
  const __nv_bfloat16* x = (const __nv_bfloat16*)d_in[0];
  const __nv_bfloat16* wqkv = (const __nv_bfloat16*)d_in[1];
  const __nv_bfloat16* wo = (const __nv_bfloat16*)d_in[2];
  const __nv_bfloat16* wgate = (const __nv_bfloat16*)d_in[4];
  const __nv_bfloat16* wup = (const __nv_bfloat16*)d_in[5];
  const __nv_bfloat16* wdown = (const __nv_bfloat16*)d_in[6];
  __nv_bfloat16* out = (__nv_bfloat16*)d_out;
  void *p_o, *p_h, *p_act;
  cudaGetSymbolAddress(&p_o, g_o); cudaGetSymbolAddress(&p_h, g_h); cudaGetSymbolAddress(&p_act, g_act);

#define A_CN 1
#define A_CM 1
#define D_CN 1
#define D_CM 1
  auto kA = gemm_kernel<256, 128, 1, DM, 4, EPI_QKV, 1, A_CN, A_CM>;
  auto kC = gemm_res_kernel<DM, true>;
  auto kD = gemm_kernel<128, 192, 2, DM, 3, EPI_GLU, 1, D_CN, D_CM>;
  auto kE = gemm_res_kernel<DFF, false>;
  constexpr int smA = GemmCfg<256, 128, 1, 4>::SMEM, smC = R_SMEM, smD = GemmCfg<128, 192, 2, 3>::SMEM;
  cudaFuncSetAttribute(kA, cudaFuncAttributeMaxDynamicSharedMemorySize, smA);
  cudaFuncSetAttribute(kC, cudaFuncAttributeMaxDynamicSharedMemorySize, smC);
  cudaFuncSetAttribute(kD, cudaFuncAttributeMaxDynamicSharedMemorySize, smD);
  cudaFuncSetAttribute(kE, cudaFuncAttributeMaxDynamicSharedMemorySize, smC);
  cudaFuncSetAttribute(attn_kernel, cudaFuncAttributeMaxDynamicSharedMemorySize, ATT_SMEM);

  const CUtensorMap tm_x = make_map(x, S_LEN, DM, 256), tm_wqkv = make_map_w(wqkv, DM, 3 * DM, 64, 2);
  const CUtensorMap tm_o = make_map(p_o, S_LEN, DM, 128), tm_wo = make_map_w(wo, DM, DM, 16, 5);
  const CUtensorMap tm_h = make_map(p_h, S_LEN, DM, 128), tm_wg = make_map_w(wgate, DM, DFF, 64, 3), tm_wu = make_map_w(wup, DM, DFF, 64, 3);
  const CUtensorMap tm_act = make_map(p_act, S_LEN, DFF, 128), tm_wd = make_map_w(wdown, DFF, DM, 16, 5);

  launch(pre_kernel, dim3(12), dim3(1024), 0, false, dim3(1, 1), x, wqkv);
  launch(kA, dim3(15, 8), dim3(288), smA, true, dim3(A_CN, A_CM), tm_x, tm_wqkv, tm_wqkv, x, (__nv_bfloat16*)wqkv);
  launch(attn_kernel, dim3(132), dim3(512), ATT_SMEM, true, dim3(1, 1), 0x800000, wgate, wup, wo, wdown);
  launch(kC, dim3(8, 16), dim3(288), smC, true, dim3(1, 1), tm_o, tm_wo, x, (__nv_bfloat16*)p_h);
  launch(kD, dim3(8, 16), dim3(384), smD, true, dim3(D_CN, D_CM), tm_h, tm_wg, tm_wu, (const __nv_bfloat16*)nullptr, (__nv_bfloat16*)p_act);
  launch(kE, dim3(8, 16), dim3(288), smC, true, dim3(1, 1), tm_act, tm_wd, (const __nv_bfloat16*)p_h, out);
}
```

```cpp
#include <cuda_runtime.h>
#include <cuda_bf16.h>
#include <cuda.h>
#include <stdint.h>

constexpr int S_LEN = 2048, DM = 640, NH = 32, DH = 20, DFF = 1536;

__device__ __align__(1024) __nv_bfloat16 g_q[S_LEN * DM];
__device__ __align__(1024) __nv_bfloat16 g_k[NH * S_LEN * 24];
__device__ __align__(1024) __nv_bfloat16 g_v[NH * S_LEN * 24];
__device__ __align__(1024) __nv_bfloat16 g_o[S_LEN * DM];
__device__ __align__(1024) __nv_bfloat16 g_h[S_LEN * DM];
__device__ __align__(1024) __nv_bfloat16 g_act[S_LEN * DFF];
__device__ float g_kn[8 * NH * 2];
__device__ float2 g_stat1[S_LEN];
__device__ float g_cs_qkv[3 * DM];
__device__ float g_cs_g[DFF];
__device__ float g_cs_u[DFF];
__device__ float2 g_part2[S_LEN * 10];

#define TS_BEGIN(k)
#define TS_END(k)
#define TS_MID(k, i)
__device__ __forceinline__ uint32_t smem_u32(const void* p) { return (uint32_t)__cvta_generic_to_shared(p); }
__device__ __forceinline__ void mbar_init(uint32_t bar, uint32_t cnt) { asm volatile("mbarrier.init.shared::cta.b64 [%0], %1;" :: "r"(bar), "r"(cnt)); }
__device__ __forceinline__ void mbar_expect_tx(uint32_t bar, uint32_t bytes) { asm volatile("mbarrier.arrive.expect_tx.shared::cta.b64 _, [%0], %1;" :: "r"(bar), "r"(bytes) : "memory"); }
__device__ __forceinline__ void mbar_arrive(uint32_t bar) { asm volatile("mbarrier.arrive.shared::cta.b64 _, [%0];" :: "r"(bar) : "memory"); }
__device__ __forceinline__ void mbar_wait(uint32_t bar, uint32_t parity) {
  uint32_t done;
  uint32_t spins = 0;
  do {
    asm volatile("{\n.reg .pred P1;\nmbarrier.try_wait.parity.shared::cta.b64 P1, [%1], %2;\nselp.u32 %0, 1, 0, P1;\n}" : "=r"(done) : "r"(bar), "r"(parity) : "memory");
  } while (!done && ++spins < (1u << 24));
}
__device__ __forceinline__ void bulk_g2s(uint32_t dst, const void* src, uint32_t bytes, uint32_t bar) {
  asm volatile("cp.async.bulk.shared::cluster.global.mbarrier::complete_tx::bytes [%0], [%1], %2, [%3];" :: "r"(dst), "l"(src), "r"(bytes), "r"(bar) : "memory");
}
__device__ __forceinline__ void tma_2d(uint32_t dst, const CUtensorMap* tm, int c0, int c1, uint32_t bar) {
  asm volatile("cp.async.bulk.tensor.2d.shared::cluster.global.mbarrier::complete_tx::bytes [%0], [%1, {%3, %4}], [%2];"
               :: "r"(dst), "l"(tm), "r"(bar), "r"(c0), "r"(c1) : "memory");
}
__device__ __forceinline__ void tma_3d(uint32_t dst, const CUtensorMap* tm, int c0, int c1, int c2, uint32_t bar) {
  asm volatile("cp.async.bulk.tensor.3d.shared::cluster.global.mbarrier::complete_tx::bytes [%0], [%1, {%3, %4, %5}], [%2];"
               :: "r"(dst), "l"(tm), "r"(bar), "r"(c0), "r"(c1), "r"(c2) : "memory");
}
__device__ __forceinline__ void tma_2d_mc(uint32_t dst, const CUtensorMap* tm, int c0, int c1, uint32_t bar, uint16_t mask) {
  asm volatile("cp.async.bulk.tensor.2d.shared::cluster.global.mbarrier::complete_tx::bytes.multicast::cluster [%0], [%1, {%3, %4}], [%2], %5;"
               :: "r"(dst), "l"(tm), "r"(bar), "r"(c0), "r"(c1), "h"(mask) : "memory");
}
__device__ __forceinline__ void mbar_arrive_remote(uint32_t bar, uint32_t rank) {
  asm volatile("{\n.reg .b32 ra;\nmapa.shared::cluster.u32 ra, %0, %1;\nmbarrier.arrive.release.cluster.shared::cluster.b64 _, [ra];\n}" :: "r"(bar), "r"(rank) : "memory");
}
__device__ __forceinline__ void cluster_arrive() { asm volatile("barrier.cluster.arrive.release.aligned;" ::: "memory"); }
__device__ __forceinline__ void cluster_wait() { asm volatile("barrier.cluster.wait.acquire.aligned;" ::: "memory"); }
__device__ __forceinline__ void wgmma_fence() { asm volatile("wgmma.fence.sync.aligned;" ::: "memory"); }
__device__ __forceinline__ void wgmma_commit() { asm volatile("wgmma.commit_group.sync.aligned;" ::: "memory"); }
template <int N> __device__ __forceinline__ void wgmma_wait() { asm volatile("wgmma.wait_group.sync.aligned %0;" :: "n"(N) : "memory"); }
__device__ __forceinline__ void pdl_wait() { asm volatile("griddepcontrol.wait;" ::: "memory"); }
__device__ __forceinline__ void pdl_launch() { asm volatile("griddepcontrol.launch_dependents;" ::: "memory"); }
__device__ __forceinline__ void named_bar(int id, int n) { asm volatile("bar.sync %0, %1;" :: "r"(id), "r"(n) : "memory"); }
__device__ __forceinline__ uint64_t make_desc(uint32_t addr, uint32_t lbo, uint32_t sbo, uint32_t swz) {
  return (uint64_t)((addr & 0x3FFFF) >> 4) | ((uint64_t)(lbo >> 4) << 16) | ((uint64_t)(sbo >> 4) << 32) | ((uint64_t)swz << 62);
}
__device__ __forceinline__ void st_g16(void* p, uint4 v) { asm volatile("st.global.v4.b32 [%0], {%1, %2, %3, %4};" :: "l"(p), "r"(v.x), "r"(v.y), "r"(v.z), "r"(v.w) : "memory"); }
__device__ __forceinline__ void st_g8(void* p, uint2 v) { asm volatile("st.global.v2.b32 [%0], {%1, %2};" :: "l"(p), "r"(v.x), "r"(v.y) : "memory"); }
__device__ __forceinline__ uint4 ld_g16(const void* p) { uint4 v; asm volatile("ld.global.v4.b32 {%0, %1, %2, %3}, [%4];" : "=r"(v.x), "=r"(v.y), "=r"(v.z), "=r"(v.w) : "l"(p) : "memory"); return v; }
__device__ __forceinline__ uint32_t pack_bf16(float lo, float hi) { uint32_t r; asm("cvt.rn.bf16x2.f32 %0, %1, %2;" : "=r"(r) : "f"(hi), "f"(lo)); return r; }
__device__ __forceinline__ float bf_lo(uint32_t u) { return __uint_as_float(u << 16); }
__device__ __forceinline__ float bf_hi(uint32_t u) { return __uint_as_float(u & 0xffff0000u); }
__device__ __forceinline__ float bf_round(float x) { return __bfloat162float(__float2bfloat16_rn(x)); }
__device__ __forceinline__ float ex2_mufu(float x) { float y; asm("ex2.approx.ftz.f32 %0, %1;" : "=f"(y) : "f"(x)); return y; }

__device__ __forceinline__ void wgmma_ss_n80(float (&d)[40], uint64_t da, uint64_t db, int scale_d) {
  asm volatile("{\n.reg .pred p;\nsetp.ne.b32 p, %42, 0;\n"
    "wgmma.mma_async.sync.aligned.m64n80k16.f32.bf16.bf16 {%0,%1,%2,%3,%4,%5,%6,%7,%8,%9,%10,%11,%12,%13,%14,%15,%16,%17,%18,%19,%20,%21,%22,%23,%24,%25,%26,%27,%28,%29,%30,%31,%32,%33,%34,%35,%36,%37,%38,%39}, %40, %41, p, 1, 1, 0, 1;\n}\n"
    : "+f"(d[0]),"+f"(d[1]),"+f"(d[2]),"+f"(d[3]),"+f"(d[4]),"+f"(d[5]),"+f"(d[6]),"+f"(d[7]),"+f"(d[8]),"+f"(d[9]),"+f"(d[10]),"+f"(d[11]),"+f"(d[12]),"+f"(d[13]),"+f"(d[14]),"+f"(d[15]),"+f"(d[16]),"+f"(d[17]),"+f"(d[18]),"+f"(d[19]),"+f"(d[20]),"+f"(d[21]),"+f"(d[22]),"+f"(d[23]),"+f"(d[24]),"+f"(d[25]),"+f"(d[26]),"+f"(d[27]),"+f"(d[28]),"+f"(d[29]),"+f"(d[30]),"+f"(d[31]),"+f"(d[32]),"+f"(d[33]),"+f"(d[34]),"+f"(d[35]),"+f"(d[36]),"+f"(d[37]),"+f"(d[38]),"+f"(d[39])
    : "l"(da), "l"(db), "r"(scale_d));
}
__device__ __forceinline__ void wgmma_ss_n128(float (&d)[64], uint64_t da, uint64_t db, int scale_d) {
  asm volatile("{\n.reg .pred p;\nsetp.ne.b32 p, %66, 0;\n"
    "wgmma.mma_async.sync.aligned.m64n128k16.f32.bf16.bf16 {%0,%1,%2,%3,%4,%5,%6,%7,%8,%9,%10,%11,%12,%13,%14,%15,%16,%17,%18,%19,%20,%21,%22,%23,%24,%25,%26,%27,%28,%29,%30,%31,%32,%33,%34,%35,%36,%37,%38,%39,%40,%41,%42,%43,%44,%45,%46,%47,%48,%49,%50,%51,%52,%53,%54,%55,%56,%57,%58,%59,%60,%61,%62,%63}, %64, %65, p, 1, 1, 0, 1;\n}\n"
    : "+f"(d[0]),"+f"(d[1]),"+f"(d[2]),"+f"(d[3]),"+f"(d[4]),"+f"(d[5]),"+f"(d[6]),"+f"(d[7]),"+f"(d[8]),"+f"(d[9]),"+f"(d[10]),"+f"(d[11]),"+f"(d[12]),"+f"(d[13]),"+f"(d[14]),"+f"(d[15]),"+f"(d[16]),"+f"(d[17]),"+f"(d[18]),"+f"(d[19]),"+f"(d[20]),"+f"(d[21]),"+f"(d[22]),"+f"(d[23]),"+f"(d[24]),"+f"(d[25]),"+f"(d[26]),"+f"(d[27]),"+f"(d[28]),"+f"(d[29]),"+f"(d[30]),"+f"(d[31]),"+f"(d[32]),"+f"(d[33]),"+f"(d[34]),"+f"(d[35]),"+f"(d[36]),"+f"(d[37]),"+f"(d[38]),"+f"(d[39]),"+f"(d[40]),"+f"(d[41]),"+f"(d[42]),"+f"(d[43]),"+f"(d[44]),"+f"(d[45]),"+f"(d[46]),"+f"(d[47]),"+f"(d[48]),"+f"(d[49]),"+f"(d[50]),"+f"(d[51]),"+f"(d[52]),"+f"(d[53]),"+f"(d[54]),"+f"(d[55]),"+f"(d[56]),"+f"(d[57]),"+f"(d[58]),"+f"(d[59]),"+f"(d[60]),"+f"(d[61]),"+f"(d[62]),"+f"(d[63])
    : "l"(da), "l"(db), "r"(scale_d));
}
__device__ __forceinline__ void wgmma_ss_n192(float (&d)[96], uint64_t da, uint64_t db, int scale_d) {
  asm volatile("{\n.reg .pred p;\nsetp.ne.b32 p, %98, 0;\n"
    "wgmma.mma_async.sync.aligned.m64n192k16.f32.bf16.bf16 {%0,%1,%2,%3,%4,%5,%6,%7,%8,%9,%10,%11,%12,%13,%14,%15,%16,%17,%18,%19,%20,%21,%22,%23,%24,%25,%26,%27,%28,%29,%30,%31,%32,%33,%34,%35,%36,%37,%38,%39,%40,%41,%42,%43,%44,%45,%46,%47,%48,%49,%50,%51,%52,%53,%54,%55,%56,%57,%58,%59,%60,%61,%62,%63,%64,%65,%66,%67,%68,%69,%70,%71,%72,%73,%74,%75,%76,%77,%78,%79,%80,%81,%82,%83,%84,%85,%86,%87,%88,%89,%90,%91,%92,%93,%94,%95}, %96, %97, p, 1, 1, 0, 1;\n}\n"
    : "+f"(d[0]),"+f"(d[1]),"+f"(d[2]),"+f"(d[3]),"+f"(d[4]),"+f"(d[5]),"+f"(d[6]),"+f"(d[7]),"+f"(d[8]),"+f"(d[9]),"+f"(d[10]),"+f"(d[11]),"+f"(d[12]),"+f"(d[13]),"+f"(d[14]),"+f"(d[15]),"+f"(d[16]),"+f"(d[17]),"+f"(d[18]),"+f"(d[19]),"+f"(d[20]),"+f"(d[21]),"+f"(d[22]),"+f"(d[23]),"+f"(d[24]),"+f"(d[25]),"+f"(d[26]),"+f"(d[27]),"+f"(d[28]),"+f"(d[29]),"+f"(d[30]),"+f"(d[31]),"+f"(d[32]),"+f"(d[33]),"+f"(d[34]),"+f"(d[35]),"+f"(d[36]),"+f"(d[37]),"+f"(d[38]),"+f"(d[39]),"+f"(d[40]),"+f"(d[41]),"+f"(d[42]),"+f"(d[43]),"+f"(d[44]),"+f"(d[45]),"+f"(d[46]),"+f"(d[47]),"+f"(d[48]),"+f"(d[49]),"+f"(d[50]),"+f"(d[51]),"+f"(d[52]),"+f"(d[53]),"+f"(d[54]),"+f"(d[55]),"+f"(d[56]),"+f"(d[57]),"+f"(d[58]),"+f"(d[59]),"+f"(d[60]),"+f"(d[61]),"+f"(d[62]),"+f"(d[63]),"+f"(d[64]),"+f"(d[65]),"+f"(d[66]),"+f"(d[67]),"+f"(d[68]),"+f"(d[69]),"+f"(d[70]),"+f"(d[71]),"+f"(d[72]),"+f"(d[73]),"+f"(d[74]),"+f"(d[75]),"+f"(d[76]),"+f"(d[77]),"+f"(d[78]),"+f"(d[79]),"+f"(d[80]),"+f"(d[81]),"+f"(d[82]),"+f"(d[83]),"+f"(d[84]),"+f"(d[85]),"+f"(d[86]),"+f"(d[87]),"+f"(d[88]),"+f"(d[89]),"+f"(d[90]),"+f"(d[91]),"+f"(d[92]),"+f"(d[93]),"+f"(d[94]),"+f"(d[95])
    : "l"(da), "l"(db), "r"(scale_d));
}
__device__ __forceinline__ void wgmma_rs_n64(float (&d)[32], uint32_t a0, uint32_t a1, uint32_t a2, uint32_t a3, uint64_t db, int scale_d) {
  asm volatile("{\n.reg .pred p;\nsetp.ne.b32 p, %37, 0;\n"
    "wgmma.mma_async.sync.aligned.m64n64k16.f32.bf16.bf16 {%0,%1,%2,%3,%4,%5,%6,%7,%8,%9,%10,%11,%12,%13,%14,%15,%16,%17,%18,%19,%20,%21,%22,%23,%24,%25,%26,%27,%28,%29,%30,%31}, {%32,%33,%34,%35}, %36, p, 1, 1, 0;\n}\n"
    : "+f"(d[0]),"+f"(d[1]),"+f"(d[2]),"+f"(d[3]),"+f"(d[4]),"+f"(d[5]),"+f"(d[6]),"+f"(d[7]),"+f"(d[8]),"+f"(d[9]),"+f"(d[10]),"+f"(d[11]),"+f"(d[12]),"+f"(d[13]),"+f"(d[14]),"+f"(d[15]),"+f"(d[16]),"+f"(d[17]),"+f"(d[18]),"+f"(d[19]),"+f"(d[20]),"+f"(d[21]),"+f"(d[22]),"+f"(d[23]),"+f"(d[24]),"+f"(d[25]),"+f"(d[26]),"+f"(d[27]),"+f"(d[28]),"+f"(d[29]),"+f"(d[30]),"+f"(d[31])
    : "r"(a0), "r"(a1), "r"(a2), "r"(a3), "l"(db), "r"(scale_d));
}
__device__ __forceinline__ void wgmma_rs_n24_tb(float (&d)[12], uint32_t a0, uint32_t a1, uint32_t a2, uint32_t a3, uint64_t db, int scale_d) {
  asm volatile("{\n.reg .pred p;\nsetp.ne.b32 p, %17, 0;\n"
    "wgmma.mma_async.sync.aligned.m64n24k16.f32.bf16.bf16 {%0,%1,%2,%3,%4,%5,%6,%7,%8,%9,%10,%11}, {%12,%13,%14,%15}, %16, p, 1, 1, 1;\n}\n"
    : "+f"(d[0]),"+f"(d[1]),"+f"(d[2]),"+f"(d[3]),"+f"(d[4]),"+f"(d[5]),"+f"(d[6]),"+f"(d[7]),"+f"(d[8]),"+f"(d[9]),"+f"(d[10]),"+f"(d[11])
    : "r"(a0), "r"(a1), "r"(a2), "r"(a3), "l"(db), "r"(scale_d));
}

constexpr int PRE_ROW_BLOCKS = 64;
constexpr int PRE_COL_BLOCKS = 3 * DM / 64;
__device__ __forceinline__ float2 ln_finish(float mean, float var) {
  float mb = bf_round(mean);
  float s = bf_round(sqrtf(bf_round(bf_round(var) + 1e-5f)));
  return make_float2(mb, 1.0f / s);
}
__device__ __forceinline__ void colsum64(const __nv_bfloat16* __restrict__ w, int ld, int c0, float* __restrict__ dst, float (*red)[65], int tid, int bar_id) {
  const int cg = tid & 7, r0 = tid >> 3;
  float acc[8];
#pragma unroll
  for (int i = 0; i < 8; i++) acc[i] = 0.f;
#pragma unroll 10
  for (int r = r0; r < DM; r += 32) {
    uint4 v = __ldg((const uint4*)(w + (size_t)r * ld + c0 + cg * 8));
    acc[0] += bf_lo(v.x); acc[1] += bf_hi(v.x); acc[2] += bf_lo(v.y); acc[3] += bf_hi(v.y);
    acc[4] += bf_lo(v.z); acc[5] += bf_hi(v.z); acc[6] += bf_lo(v.w); acc[7] += bf_hi(v.w);
  }
#pragma unroll
  for (int i = 0; i < 8; i++) red[r0][cg * 8 + i] = acc[i];
  named_bar(bar_id, 256);
  if (tid < 64) {
    float s = 0.f;
#pragma unroll
    for (int r = 0; r < 32; r++) s += red[r][tid];
    dst[c0 + tid] = s;
  }
  named_bar(bar_id, 256);
}
__global__ void __launch_bounds__(1024) pre_kernel(const __nv_bfloat16* __restrict__ x, const __nv_bfloat16* __restrict__ wqkv) {
  TS_BEGIN(0);
  pdl_launch();
  __shared__ float red[51][161];
  const int tid = threadIdx.x, lane = tid & 31, warp = tid >> 5;
  {
    const int ch = tid % 20, rl = tid / 20;
    if (rl < 51) {
      const __nv_bfloat16* w = wqkv + blockIdx.x * 160 + ch * 8;
      uint4 v[13];
#pragma unroll
      for (int i = 0; i < 13; i++) { const int r = rl + i * 51; v[i] = r < DM ? __ldg((const uint4*)(w + (size_t)r * (3 * DM))) : make_uint4(0, 0, 0, 0); }
      float acc[8];
#pragma unroll
      for (int i = 0; i < 8; i++) acc[i] = 0.f;
#pragma unroll
      for (int i = 0; i < 13; i++) {
        acc[0] += bf_lo(v[i].x); acc[1] += bf_hi(v[i].x); acc[2] += bf_lo(v[i].y); acc[3] += bf_hi(v[i].y);
        acc[4] += bf_lo(v[i].z); acc[5] += bf_hi(v[i].z); acc[6] += bf_lo(v[i].w); acc[7] += bf_hi(v[i].w);
      }
#pragma unroll
      for (int i = 0; i < 8; i++) red[rl][ch * 8 + i] = acc[i];
    }
  }
  const int rbeg = blockIdx.x * 171, rend = min(rbeg + 171, S_LEN);
  for (int row0 = rbeg + warp * 2; row0 < rend; row0 += 64) {
    uint4 v[2][3];
#pragma unroll
    for (int k = 0; k < 2; k++) {
      const int row = min(row0 + k, rend - 1);
      const uint4* p = (const uint4*)(x + (size_t)row * DM);
      v[k][0] = __ldg(p + lane); v[k][1] = __ldg(p + 32 + lane);
      v[k][2] = lane < 16 ? __ldg(p + 64 + lane) : make_uint4(0, 0, 0, 0);
    }
#pragma unroll
    for (int k = 0; k < 2; k++) {
      float f[24];
      const uint32_t u[12] = {v[k][0].x, v[k][0].y, v[k][0].z, v[k][0].w, v[k][1].x, v[k][1].y, v[k][1].z, v[k][1].w, v[k][2].x, v[k][2].y, v[k][2].z, v[k][2].w};
#pragma unroll
      for (int j = 0; j < 12; j++) { f[2 * j] = bf_lo(u[j]); f[2 * j + 1] = bf_hi(u[j]); }
      float s = 0.f;
#pragma unroll
      for (int j = 0; j < 24; j++) s += f[j];
#pragma unroll
      for (int o = 16; o; o >>= 1) s += __shfl_xor_sync(~0u, s, o);
      const float mean = s * (1.0f / DM);
      float q = 0.f;
#pragma unroll
      for (int j = 0; j < 16; j++) { const float d = f[j] - mean; q += d * d; }
      if (lane < 16) {
#pragma unroll
        for (int j = 16; j < 24; j++) { const float d = f[j] - mean; q += d * d; }
      }
#pragma unroll
      for (int o = 16; o; o >>= 1) q += __shfl_xor_sync(~0u, q, o);
      if (lane == 0 && row0 + k < rend) g_stat1[row0 + k] = ln_finish(mean, q * (1.0f / DM));
    }
  }
  __syncthreads();
  if (tid < 160) {
    float s = 0.f;
#pragma unroll 17
    for (int r = 0; r < 51; r++) s += red[r][tid];
    g_cs_qkv[blockIdx.x * 160 + tid] = s;
  }
  TS_END(0);
}

enum { EPI_QKV = 0, EPI_WO = 1, EPI_GLU = 2, EPI_DOWN = 3 };
template <int N> struct WG;
template <> struct WG<128> { static __device__ __forceinline__ void mma(float (&d)[64], uint64_t a, uint64_t b, int s) { wgmma_ss_n128(d, a, b, s); } };
template <> struct WG<192> { static __device__ __forceinline__ void mma(float (&d)[96], uint64_t a, uint64_t b, int s) { wgmma_ss_n192(d, a, b, s); } };

template <int BM, int BN, int NB, int STAGES> struct GemmCfg {
  static constexpr int A_BYTES = BM * 128;
  static constexpr int B_BYTES = NB * (BN / 64) * 8192;
  static constexpr int STAGE_BYTES = A_BYTES + B_BYTES;
  static constexpr int SMEM = STAGES * STAGE_BYTES + 1024   + 256   + 4096  ;
};

constexpr float QSCALE = 0.22360679774997896f * 1.4426950408889634f;

template <int BM, int BN, int NB, int KDIM, int STAGES, int EPI, int MINB, int CN, int CM>
__global__ void __launch_bounds__(EPI == EPI_GLU ? 384 : 288, MINB) gemm_kernel(const __grid_constant__ CUtensorMap tmA, const __grid_constant__ CUtensorMap tmB0,
                                                         const __grid_constant__ CUtensorMap tmB1,
                                                         const __nv_bfloat16* resid, __nv_bfloat16* out) {
  using Cfg = GemmCfg<BM, BN, NB, STAGES>;
  constexpr int MB = BM / 128;
  constexpr int KT = KDIM / 64;
  extern __shared__ uint8_t smem_raw[];
  const uint32_t sbase = (smem_u32(smem_raw) + 1023u) & ~1023u;
  uint8_t* sptr = smem_raw + (sbase - smem_u32(smem_raw));
  const uint32_t sbar = sbase + STAGES * Cfg::STAGE_BYTES;
  const int tid = threadIdx.x, warp = tid >> 5, lane = tid & 31;
  const int n0 = blockIdx.x * BN, m0 = blockIdx.y * BM;
  TS_BEGIN(EPI == EPI_QKV ? 1 : EPI + 2);
  TS_MID(EPI == EPI_QKV ? 1 : EPI + 2, 3);
  constexpr int NCL = CN + CM - 1;
  const int cx = blockIdx.x % CN, cy = blockIdx.y % CM;
  if (tid == 0) {
    for (int i = 0; i < STAGES; i++) { mbar_init(sbar + 8 * i, 1); mbar_init(sbar + 8 * (STAGES + i), 2 * NCL); }
    asm volatile("fence.mbarrier_init.release.cluster;" ::: "memory");
  }
  __syncthreads();
  if constexpr (CN * CM > 1) { cluster_arrive(); cluster_wait(); }
  pdl_launch();
  if (warp >= 8) {
    if constexpr (EPI == EPI_GLU) asm volatile("setmaxnreg.dec.sync.aligned.u32 40;");
    if (warp == 8 && lane == 0) {
      auto load_a = [&](int kt, int s) { tma_2d(sbase + s * Cfg::STAGE_BYTES, &tmA, kt * 64, m0, sbar + 8 * s); };
      auto load_b = [&](int kt, int s) {
        const uint32_t sb = sbase + s * Cfg::STAGE_BYTES + Cfg::A_BYTES;
        tma_3d(sb, &tmB0, 0, kt * 64, blockIdx.x * (BN / 64), sbar + 8 * s);
        if constexpr (NB == 2) tma_3d(sb + (BN / 64) * 8192, &tmB1, 0, kt * 64, blockIdx.x * (BN / 64), sbar + 8 * s);
      };
      if constexpr (EPI == EPI_QKV) {
        const int cta = blockIdx.y * gridDim.x + blockIdx.x;
        const uint32_t xb = S_LEN * DM * 2, xs = 21888;
        if (cta * xs < xb) asm volatile("cp.async.bulk.prefetch.L2.global [%0], %1;" :: "l"((const uint8_t*)resid + (size_t)cta * xs), "r"(min(xs, xb - cta * xs)));
        asm volatile("cp.async.bulk.prefetch.L2.global [%0], %1;" :: "l"((const uint8_t*)out + (size_t)cta * 20480), "r"(20480));
      }
      for (int s = 0; s < STAGES; s++) { mbar_expect_tx(sbar + 8 * s, Cfg::STAGE_BYTES); if (EPI != EPI_QKV || s == 0) load_b(s, s); }
      if (EPI != EPI_QKV) pdl_wait();
      for (int s = 0; s < STAGES; s++) { load_a(s, s); if (EPI == EPI_QKV && s > 0) load_b(s, s); }
      for (int kt = STAGES; kt < KT; kt++) {
        const int s = kt % STAGES;
        mbar_wait(sbar + 8 * (STAGES + s), ((kt / STAGES) - 1) & 1);
        mbar_expect_tx(sbar + 8 * s, Cfg::STAGE_BYTES);
        load_a(kt, s);
        load_b(kt, s);
      }
    }
    if constexpr (EPI == EPI_GLU) {
      if (warp > 8) {
        float2* s_st = (float2*)(sptr + STAGES * Cfg::STAGE_BYTES + 256);
        float* s_cs = (float*)(sptr + STAGES * Cfg::STAGE_BYTES + 256 + 1024);
        pdl_wait();
        for (int r = tid - 288; r < BM; r += 96) {
          const float2* pp = &g_part2[(m0 + r) * 8];
          float s = 0.f;
#pragma unroll
          for (int i = 0; i < 8; i++) s += pp[i].x;
          const float mean = s * (1.0f / DM);
          float q = 0.f;
#pragma unroll
          for (int i = 0; i < 8; i++) { const float2 p = pp[i]; const float d = p.x * (1.0f / 80.f) - mean; q += p.y + 80.f * d * d; }
          s_st[r] = ln_finish(mean, q * (1.0f / DM));
        }
        for (int c = tid - 288; c < BN; c += 96) { s_cs[c] = g_cs_g[n0 + c]; s_cs[BN + c] = g_cs_u[n0 + c]; }
        __threadfence_block();
        asm volatile("bar.arrive 2, 352;" ::: "memory");
      }
    }
    if constexpr (CN * CM > 1) { __syncwarp(); cluster_arrive(); cluster_wait(); }
    return;
  }
  if constexpr (EPI == EPI_GLU) asm volatile("setmaxnreg.inc.sync.aligned.u32 232;");
  const int wg = warp >> 2, g = lane >> 2, t = lane & 3;
  float acc[MB][NB][BN / 2];
#pragma unroll
  for (int mb = 0; mb < MB; mb++)
#pragma unroll
    for (int nb = 0; nb < NB; nb++)
#pragma unroll
      for (int i = 0; i < BN / 2; i++) acc[mb][nb][i] = 0.f;
  for (int kt = 0; kt < KT; kt++) {
    const int s = kt % STAGES;
    mbar_wait(sbar + 8 * s, (kt / STAGES) & 1);
    if (kt == 0) TS_MID(EPI == EPI_QKV ? 1 : EPI + 2, 0);
    const uint32_t sa = sbase + s * Cfg::STAGE_BYTES + wg * (MB * 64 * 128);
    const uint32_t sb = sbase + s * Cfg::STAGE_BYTES + Cfg::A_BYTES;
    wgmma_fence();
#pragma unroll
    for (int ks = 0; ks < 4; ks++) {
#pragma unroll
      for (int mb = 0; mb < MB; mb++) {
        const uint64_t da = make_desc(sa + mb * 8192 + ks * 32, 16, 1024, 1);
#pragma unroll
        for (int nb = 0; nb < NB; nb++) {
          const uint64_t db = make_desc(sb + nb * (BN / 64) * 8192 + ks * 2048, 8192, 1024, 1);
          WG<BN>::mma(acc[mb][nb], da, db, 1);
        }
      }
    }
    wgmma_commit();
    wgmma_wait<1>();
    if (kt > 0 && kt - 1 + STAGES < KT && (tid & 127) < NCL) {
      const uint32_t eb = sbar + 8 * (STAGES + (kt - 1) % STAGES);
      if constexpr (CN * CM > 1) {
        const int i = tid & 127;
        const uint32_t rank = i < CN ? cy * CN + i : ((i - CN + (i - CN >= cy ? 1 : 0)) * CN + cx);
        mbar_arrive_remote(eb, rank);
      } else mbar_arrive(eb);
    }
  }
  wgmma_wait<0>();
#pragma unroll
  for (int mb = 0; mb < MB; mb++)
#pragma unroll
    for (int nb = 0; nb < NB; nb++)
#pragma unroll
      for (int i = 0; i < BN / 2; i++) asm volatile("" : "+f"(acc[mb][nb][i]) :: "memory");
  if constexpr (CN * CM > 1) cluster_arrive();
  TS_MID(EPI == EPI_QKV ? 1 : EPI + 2, 1);
  pdl_wait();
  TS_MID(EPI == EPI_QKV ? 1 : EPI + 2, 2);
  named_bar(1, 256);
  constexpr int LDS = BN * 2 + 16;
  const int ctid = tid;

  if constexpr (EPI == EPI_QKV) {
    const int sec = n0 / DM;
    const int lds = sec == 0 ? 272 : 264;
    __shared__ unsigned int s_kn[8];
    if (ctid < 8) s_kn[ctid] = 0u;
    float2 cs[BN / 8];
#pragma unroll
    for (int j = 0; j < BN / 8; j++) cs[j] = *(const float2*)&g_cs_qkv[n0 + j * 8 + 2 * t];
#pragma unroll
    for (int mb = 0; mb < MB; mb++) {
      const int r0 = wg * (MB * 64) + mb * 64 + (warp & 3) * 16 + g;
      const float2 st0 = g_stat1[m0 + r0], st1 = g_stat1[m0 + r0 + 8];
      const float sc0 = sec == 0 ? st0.y * QSCALE : st0.y, sc1 = sec == 0 ? st1.y * QSCALE : st1.y;
#pragma unroll
      for (int j = 0; j < BN / 8; j++) {
        const float* a = &acc[mb][0][4 * j];
        *(uint32_t*)(sptr + r0 * lds + j * 16 + t * 4) = pack_bf16(fmaf(-st0.x, cs[j].x, a[0]) * sc0, fmaf(-st0.x, cs[j].y, a[1]) * sc0);
        *(uint32_t*)(sptr + (r0 + 8) * lds + j * 16 + t * 4) = pack_bf16(fmaf(-st1.x, cs[j].x, a[2]) * sc1, fmaf(-st1.x, cs[j].y, a[3]) * sc1);
      }
    }
    named_bar(1, 256);
    if (sec == 0) {
#pragma unroll
      for (int i = 0; i < BM * (BN / 8) / 256; i++) {
        const int idx = i * 256 + ctid, r = idx / (BN / 8), c = idx % (BN / 8);
        st_g16(g_q + (size_t)(m0 + r) * DM + n0 + c * 8, *(const uint4*)(sptr + r * 272 + c * 16));
      }
    } else {
      const int cbase = n0 - sec * DM;
      const int hfirst = cbase / DH;
      const int j = m0 + ctid;
      uint8_t* dst = (uint8_t*)(sec == 1 ? g_k : g_v) + ((size_t)(j >> 3) * 192 + (j & 7) * 8) * 2;
      const uint8_t* row = sptr + ctid * 264;
#pragma unroll
      for (int i = 0; i < 8; i++) {
        const int hh = hfirst + i;
        const int cr = hh * DH - cbase;
        if (cr < BN) {
          uint2 v[5];
          bool in[5];
          float s = 0.f;
#pragma unroll
          for (int qd = 0; qd < 5; qd++) {
            const int c = cr + 4 * qd;
            in[qd] = c >= 0 && c < BN;
            v[qd] = in[qd] ? *(const uint2*)(row + c * 2) : make_uint2(0u, 0u);
            s += bf_lo(v[qd].x) * bf_lo(v[qd].x) + bf_hi(v[qd].x) * bf_hi(v[qd].x) + bf_lo(v[qd].y) * bf_lo(v[qd].y) + bf_hi(v[qd].y) * bf_hi(v[qd].y);
          }
          uint8_t* p = dst + (size_t)hh * (S_LEN * 48);
          if (in[0] && in[1]) st_g16(p, make_uint4(v[0].x, v[0].y, v[1].x, v[1].y));
          else if (in[0]) st_g8(p, v[0]);
          else if (in[1]) st_g8(p + 8, v[1]);
          if (in[2] && in[3]) st_g16(p + 128, make_uint4(v[2].x, v[2].y, v[3].x, v[3].y));
          else if (in[2]) st_g8(p + 128, v[2]);
          else if (in[3]) st_g8(p + 136, v[3]);
          if (in[4]) st_g16(p + 256, make_uint4(v[4].x, v[4].y, 0x00003f80u, 0u));
          if (sec == 1) {
            const unsigned int mxb = __reduce_max_sync(~0u, __float_as_uint(s) & 0x7fffffffu);
            if (lane == 0) atomicMax(&s_kn[i], mxb);
          }
        }
      }
      if (sec == 1) {
        named_bar(1, 256);
        const int hh = hfirst + ctid;
        if (ctid < 8 && hh * DH < cbase + BN) {
          const bool starts_here = hh * DH >= cbase, ends_here = hh * DH + DH <= cbase + BN;
          const float v = __uint_as_float(s_kn[ctid]);
          float* o = &g_kn[(blockIdx.y * NH + hh) * 2];
          if (starts_here) { o[0] = v; if (ends_here) o[1] = 0.f; }
          else o[1] = v;
        }
      }
    }
  } else if constexpr (EPI == EPI_WO || EPI == EPI_DOWN) {
    const int r0 = wg * 64 + (warp & 3) * 16 + g;
#pragma unroll
    for (int j = 0; j < BN / 8; j++) {
      const float* a = &acc[0][0][4 * j];
      *(uint32_t*)(sptr + r0 * LDS + j * 16 + t * 4) = pack_bf16(a[0], a[1]);
      *(uint32_t*)(sptr + (r0 + 8) * LDS + j * 16 + t * 4) = pack_bf16(a[2], a[3]);
    }
    named_bar(1, 256);
#pragma unroll
    for (int i = 0; i < BM * (BN / 8) / 256; i++) {
      const int idx = i * 256 + ctid, r = idx / (BN / 8), c = idx % (BN / 8);
      const uint4 a = *(const uint4*)(sptr + r * LDS + c * 16);
      const size_t go = (size_t)(m0 + r) * DM + n0 + c * 8;
      const uint4 b = ld_g16(resid + go);
      uint4 o;
      o.x = pack_bf16(bf_lo(a.x) + bf_lo(b.x), bf_hi(a.x) + bf_hi(b.x));
      o.y = pack_bf16(bf_lo(a.y) + bf_lo(b.y), bf_hi(a.y) + bf_hi(b.y));
      o.z = pack_bf16(bf_lo(a.z) + bf_lo(b.z), bf_hi(a.z) + bf_hi(b.z));
      o.w = pack_bf16(bf_lo(a.w) + bf_lo(b.w), bf_hi(a.w) + bf_hi(b.w));
      st_g16(out + go, o);
      if constexpr (EPI == EPI_WO) {
        static_assert(BN == 64, "stats assume 8 lanes per row");
        const float f[8] = {bf_lo(o.x), bf_hi(o.x), bf_lo(o.y), bf_hi(o.y), bf_lo(o.z), bf_hi(o.z), bf_lo(o.w), bf_hi(o.w)};
        float s = 0.f;
#pragma unroll
        for (int k = 0; k < 8; k++) s += f[k];
        s += __shfl_xor_sync(~0u, s, 1); s += __shfl_xor_sync(~0u, s, 2); s += __shfl_xor_sync(~0u, s, 4);
        const float mu = s * (1.0f / 64.f);
        float q = 0.f;
#pragma unroll
        for (int k = 0; k < 8; k++) { const float d = f[k] - mu; q += d * d; }
        q += __shfl_xor_sync(~0u, q, 1); q += __shfl_xor_sync(~0u, q, 2); q += __shfl_xor_sync(~0u, q, 4);
        if (c == 0) g_part2[(m0 + r) * 10 + blockIdx.x] = make_float2(s, q);
      }
    }
  } else {
    const int r0 = wg * 64 + (warp & 3) * 16 + g;
    const float2* s_st = (const float2*)(sptr + STAGES * Cfg::STAGE_BYTES + 256);
    const float* s_cs = (const float*)(sptr + STAGES * Cfg::STAGE_BYTES + 256 + 1024);
    named_bar(2, 352);
    float2 st[2] = {s_st[r0], s_st[r0 + 8]};
#pragma unroll
    for (int j = 0; j < BN / 8; j++) {
      const float2 cg = *(const float2*)&s_cs[j * 8 + 2 * t], cu = *(const float2*)&s_cs[BN + j * 8 + 2 * t];
      const float* a = &acc[0][0][4 * j];
      const float* b = &acc[0][1][4 * j];
#pragma unroll
      for (int e = 0; e < 2; e++) {
        const float2 s_ = st[e];
        const uint32_t gp = pack_bf16(fmaf(-s_.x, cg.x, a[2 * e]) * s_.y, fmaf(-s_.x, cg.y, a[2 * e + 1]) * s_.y);
        const uint32_t up = pack_bf16(fmaf(-s_.x, cu.x, b[2 * e]) * s_.y, fmaf(-s_.x, cu.y, b[2 * e + 1]) * s_.y);
        uint32_t r;
        asm("{\n.reg .b32 z;\nmax.bf16x2 z, %1, %3;\nmul.rn.bf16x2 %0, z, %2;\n}" : "=r"(r) : "r"(gp), "r"(up), "r"(0u));
        *(uint32_t*)(sptr + (r0 + 8 * e) * LDS + j * 16 + t * 4) = r;
      }
    }
    named_bar(1, 256);
#pragma unroll
    for (int i = 0; i < BM * (BN / 8) / 256; i++) {
      const int idx = i * 256 + ctid, r = idx / (BN / 8), c = idx % (BN / 8);
      st_g16(out + (size_t)(m0 + r) * DFF + n0 + c * 8, *(const uint4*)(sptr + r * LDS + c * 16));
    }
  }
  if constexpr (CN * CM > 1) cluster_wait();
  TS_END(EPI == EPI_QKV ? 1 : EPI + 2);
}

constexpr int R_STAGES = 8;
constexpr int R_STAGE_BYTES = 16384 + 5 * 2048;
constexpr int R_BAR_OFF = R_STAGES * R_STAGE_BYTES;
constexpr int R_SMEM = R_BAR_OFF + 256 + 1024;
template <int KDIM, bool STATS>
__global__ void __launch_bounds__(288, 1) gemm_res_kernel(const __grid_constant__ CUtensorMap tmA, const __grid_constant__ CUtensorMap tmB,
                                                          const __nv_bfloat16* resid, __nv_bfloat16* out) {
  constexpr int KT = KDIM / 64;
  extern __shared__ uint8_t smem_raw[];
  const uint32_t sbase = (smem_u32(smem_raw) + 1023u) & ~1023u;
  uint8_t* sptr = smem_raw + (sbase - smem_u32(smem_raw));
  const uint32_t sbar = sbase + R_BAR_OFF;
  const int tid = threadIdx.x, warp = tid >> 5, lane = tid & 31;
  const int n0 = blockIdx.x * 80, m0 = blockIdx.y * 128;
  TS_BEGIN(STATS ? 3 : 5);
  if (tid == 0) {
    for (int i = 0; i < R_STAGES; i++) { mbar_init(sbar + 8 * i, 1); mbar_init(sbar + 8 * (R_STAGES + i), 2); }
    asm volatile("fence.mbarrier_init.release.cluster;" ::: "memory");
  }
  __syncthreads();
  pdl_launch();
  if (warp == 8) {
    if (lane == 0) {
      auto load_b = [&](int kt, int s) { tma_3d(sbase + s * R_STAGE_BYTES + 16384, &tmB, 0, kt * 64, blockIdx.x * 5, sbar + 8 * s); };
      for (int s = 0; s < R_STAGES; s++) { mbar_expect_tx(sbar + 8 * s, R_STAGE_BYTES); if (s < 3) load_b(s, s); }
      pdl_wait();
      for (int s = 0; s < R_STAGES; s++) { tma_2d(sbase + s * R_STAGE_BYTES, &tmA, s * 64, m0, sbar + 8 * s); if (s >= 3) load_b(s, s); }
      for (int kt = R_STAGES; kt < KT; kt++) {
        const int s = kt % R_STAGES;
        mbar_wait(sbar + 8 * (R_STAGES + s), ((kt / R_STAGES) - 1) & 1);
        mbar_expect_tx(sbar + 8 * s, R_STAGE_BYTES);
        tma_2d(sbase + s * R_STAGE_BYTES, &tmA, kt * 64, m0, sbar + 8 * s);
        load_b(kt, s);
      }
    }
    return;
  }
  const int wg = warp >> 2, g = lane >> 2, t = lane & 3;
  pdl_wait();
  uint4 rv[5];
#pragma unroll
  for (int i = 0; i < 5; i++) {
    const int idx = i * 256 + tid, r = idx / 10, c = idx % 10;
    rv[i] = ld_g16(resid + (size_t)(m0 + r) * DM + n0 + c * 8);
  }
  float acc[40];
#pragma unroll
  for (int i = 0; i < 40; i++) acc[i] = 0.f;
  for (int kt = 0; kt < KT; kt++) {
    const int s = kt % R_STAGES;
    mbar_wait(sbar + 8 * s, (kt / R_STAGES) & 1);
    if (kt == 0) TS_MID(STATS ? 3 : 5, 0);
    const uint32_t sa = sbase + s * R_STAGE_BYTES + wg * 8192;
    const uint32_t sb = sbase + s * R_STAGE_BYTES + 16384;
    wgmma_fence();
#pragma unroll
    for (int ks = 0; ks < 4; ks++)
      wgmma_ss_n80(acc, make_desc(sa + ks * 32, 16, 1024, 1), make_desc(sb + ks * 512, 2048, 256, 3), 1);
    wgmma_commit();
    wgmma_wait<1>();
    if (kt > 0 && kt - 1 + R_STAGES < KT && (tid & 127) == 0) mbar_arrive(sbar + 8 * (R_STAGES + (kt - 1) % R_STAGES));
  }
  wgmma_wait<0>();
#pragma unroll
  for (int i = 0; i < 40; i++) asm volatile("" : "+f"(acc[i]) :: "memory");
  TS_MID(STATS ? 3 : 5, 1);
  named_bar(1, 256);
  constexpr int LDS = 176;
  const int r0 = wg * 64 + (warp & 3) * 16 + g;
#pragma unroll
  for (int i = 0; i < 10; i++) {
    *(uint32_t*)(sptr + r0 * LDS + i * 16 + t * 4) = pack_bf16(acc[4 * i], acc[4 * i + 1]);
    *(uint32_t*)(sptr + (r0 + 8) * LDS + i * 16 + t * 4) = pack_bf16(acc[4 * i + 2], acc[4 * i + 3]);
  }
  named_bar(1, 256);
  TS_MID(STATS ? 3 : 5, 2);
#pragma unroll
  for (int i = 0; i < 5; i++) {
    const int idx = i * 256 + tid, r = idx / 10, c = idx % 10;
    const uint4 a = *(const uint4*)(sptr + r * LDS + c * 16);
    const uint4 b = rv[i];
    uint4 o;
    o.x = pack_bf16(bf_lo(a.x) + bf_lo(b.x), bf_hi(a.x) + bf_hi(b.x));
    o.y = pack_bf16(bf_lo(a.y) + bf_lo(b.y), bf_hi(a.y) + bf_hi(b.y));
    o.z = pack_bf16(bf_lo(a.z) + bf_lo(b.z), bf_hi(a.z) + bf_hi(b.z));
    o.w = pack_bf16(bf_lo(a.w) + bf_lo(b.w), bf_hi(a.w) + bf_hi(b.w));
    st_g16(out + (size_t)(m0 + r) * DM + n0 + c * 8, o);
    if constexpr (STATS) *(uint4*)(sptr + r * LDS + c * 16) = o;
  }
  TS_MID(STATS ? 3 : 5, 3);
  if constexpr (STATS) {
    named_bar(1, 256);
    const int r = tid >> 1, hf = tid & 1;
    float f[40];
#pragma unroll
    for (int i = 0; i < 5; i++) {
      const uint4 v = *(const uint4*)(sptr + r * LDS + hf * 80 + i * 16);
      f[8 * i] = bf_lo(v.x); f[8 * i + 1] = bf_hi(v.x); f[8 * i + 2] = bf_lo(v.y); f[8 * i + 3] = bf_hi(v.y);
      f[8 * i + 4] = bf_lo(v.z); f[8 * i + 5] = bf_hi(v.z); f[8 * i + 6] = bf_lo(v.w); f[8 * i + 7] = bf_hi(v.w);
    }
    float s = 0.f;
#pragma unroll
    for (int i = 0; i < 40; i++) s += f[i];
    s += __shfl_xor_sync(~0u, s, 1);
    const float mu = s * (1.0f / 80.f);
    float q = 0.f;
#pragma unroll
    for (int i = 0; i < 40; i++) { const float d = f[i] - mu; q += d * d; }
    q += __shfl_xor_sync(~0u, q, 1);
    if (hf == 0) g_part2[(m0 + r) * 8 + blockIdx.x] = make_float2(s, q);
  }
  TS_END(STATS ? 3 : 5);
}

#define POLY_NUM 5
__device__ __forceinline__ float ex2_poly(float x, int shl23) {
  const float MAGIC = 12582912.f;
  const float tt = x + MAGIC;
  const float f = x - (tt - MAGIC);
  float p = fmaf(0.0013276472454890609f, f, 0.009675540961325169f);
  p = fmaf(p, f, 0.05550713092088699f);
  p = fmaf(p, f, 0.24022120237350464f);
  p = fmaf(p, f, 0.6931469440460205f);
  p = fmaf(p, f, 1.0000001192092896f);
  return __int_as_float(__float_as_int(tt) * shl23 + __float_as_int(p));
}
constexpr int KV_BYTES = S_LEN * 48;
constexpr int ATT_SMEM = 2 * KV_BYTES + 256;

__global__ void __launch_bounds__(512, 1) attn_kernel(int shl23, const __nv_bfloat16* __restrict__ wg_, const __nv_bfloat16* __restrict__ wu_,
                                                      const __nv_bfloat16* __restrict__ wo_, const __nv_bfloat16* __restrict__ wd_) {
  extern __shared__ __align__(1024) uint8_t smem[];
  if (blockIdx.x >= 128) {
    pdl_launch();
    const int e = blockIdx.x - 128, half = threadIdx.x >> 8;
    if (threadIdx.x == 0) {
      for (int i = 0; i < 13; i++) asm volatile("cp.async.bulk.prefetch.L2.global [%0], %1;" :: "l"((const uint8_t*)wo_ + (e * 13 + i) * 16384 * 0 + (size_t)(e * 13 + i >= 50 ? 0 : (e * 13 + i)) * 16384), "r"(16384));
      for (int i = 0; i < 30; i++) asm volatile("cp.async.bulk.prefetch.L2.global [%0], %1;" :: "l"((const uint8_t*)wd_ + (size_t)(e * 30 + i) * 16384), "r"(16384));
    }
    float (*red)[65] = (float (*)[65])(smem + half * 16384);
    for (int b = e * 12 + half; b < e * 12 + 12; b += 2) {
      if (b < 24) colsum64(wg_, DFF, b * 64, g_cs_g, red, threadIdx.x & 255, 1 + half);
      else colsum64(wu_, DFF, (b - 24) * 64, g_cs_u, red, threadIdx.x & 255, 1 + half);
    }
    return;
  }
  const int h = blockIdx.x >> 2, qb = blockIdx.x & 3;
  const uint32_t sK = smem_u32(smem), sV = sK + KV_BYTES, sBar = sV + KV_BYTES;
  const int tid = threadIdx.x;
  TS_BEGIN(2);
  if (tid == 0) {
    for (int i = 0; i < 8; i++) mbar_init(sBar + 8 * i, 1);
    asm volatile("fence.mbarrier_init.release.cluster;" ::: "memory");
  }
  pdl_launch();
  pdl_wait();
  if (tid == 0) {
    const uint8_t* gk = (const uint8_t*)(g_k + (size_t)h * S_LEN * 24);
    const uint8_t* gv = (const uint8_t*)(g_v + (size_t)h * S_LEN * 24);
    for (int i = 0; i < 8; i++) {
      mbar_expect_tx(sBar + 8 * i, 2 * 12288);
      bulk_g2s(sK + i * 12288, gk + i * 12288, 12288, sBar + 8 * i);
      bulk_g2s(sV + i * 12288, gv + i * 12288, 12288, sBar + 8 * i);
    }
  }
  __syncthreads();
  const int wg = tid >> 7, warp = (tid >> 5) & 3, lane = tid & 31, g = lane >> 2, t = lane & 3;
  float ka = 0.f, kb = 0.f;
#pragma unroll
  for (int i = 0; i < 8; i++) {
    const float2 v = *(const float2*)&g_kn[(i * NH + h) * 2];
    ka = (v.x > ka || v.x != v.x) ? v.x : ka;
    kb = (v.y > kb || v.y != v.y) ? v.y : kb;
  }
  const float kn = sqrtf(ka + kb);
  for (int it = 0; it < 2; it++) {
    const int q0 = qb * 512 + (it * 4 + wg) * 64 + warp * 16;
    uint32_t qa[4], qc[4];
    const uint32_t* qr0 = (const uint32_t*)(g_q + (size_t)(q0 + g) * DM + h * DH);
    const uint32_t* qr1 = (const uint32_t*)(g_q + (size_t)(q0 + g + 8) * DM + h * DH);
    qa[0] = qr0[t]; qa[1] = qr1[t]; qa[2] = qr0[t + 4]; qa[3] = qr1[t + 4];
    qc[0] = (t < 2) ? qr0[t + 8] : 0u; qc[1] = (t < 2) ? qr1[t + 8] : 0u; qc[2] = 0; qc[3] = 0;
    auto sq = [](uint32_t u) { const float a = bf_lo(u), b = bf_hi(u); return a * a + b * b; };
    float n0 = sq(qa[0]) + sq(qa[2]) + sq(qc[0]);
    float n1 = sq(qa[1]) + sq(qa[3]) + sq(qc[1]);
    n0 += __shfl_xor_sync(~0u, n0, 1); n0 += __shfl_xor_sync(~0u, n0, 2);
    n1 += __shfl_xor_sync(~0u, n1, 1); n1 += __shfl_xor_sync(~0u, n1, 2);
    const float m0 = ceilf(sqrtf(n0) * kn * 1.001f) + 1.f, m1 = ceilf(sqrtf(n1) * kn * 1.001f) + 1.f;
    const bool unsafe = !(m0 <= 62.f && m1 <= 62.f);
    uint32_t any_unsafe;
    asm volatile("{\n.reg .pred p, q;\nsetp.ne.u32 p, %1, 0;\nbarrier.cta.red.or.pred q, %2, 128, p;\nselp.u32 %0, 1, 0, q;\n}"
                 : "=r"(any_unsafe) : "r"((uint32_t)unsafe), "r"(1 + wg) : "memory");
    float O[12];
    float S[32];
    if (!__any_sync(~0u, any_unsafe)) {
      if (t == 2) { qc[0] = pack_bf16(-m0, 0.f); qc[1] = pack_bf16(-m1, 0.f); }
      for (int j = 0; j < 32; j++) {
        if (it == 0 && (j & 3) == 0) mbar_wait(sBar + 8 * (j >> 2), 0);
        const uint64_t dk = make_desc(sK + j * 8 * 384, 128, 384, 0);
        wgmma_fence();
        wgmma_rs_n64(S, qa[0], qa[1], qa[2], qa[3], dk, 0);
        wgmma_rs_n64(S, qc[0], qc[1], qc[2], qc[3], dk + (256 >> 4), 1);
        wgmma_commit();
        wgmma_wait<0>();
        uint32_t P[16];
#pragma unroll
        for (int i = 0; i < 16; i++) {
          const bool usepoly = ((i + 1) * POLY_NUM / 16) != (i * POLY_NUM / 16);
          float a, b;
          if (usepoly) { a = ex2_poly(S[2 * i], shl23); b = ex2_poly(S[2 * i + 1], shl23); }
          else { a = ex2_mufu(S[2 * i]); b = ex2_mufu(S[2 * i + 1]); }
          P[i] = pack_bf16(a, b);
        }
        wgmma_fence();
        const uint64_t dv = make_desc(sV + j * 8 * 384, 384, 128, 0);
#pragma unroll
        for (int ks = 0; ks < 4; ks++)
          wgmma_rs_n24_tb(O, P[4 * ks], P[4 * ks + 1], P[4 * ks + 2], P[4 * ks + 3], dv + ((ks * 768) >> 4), (j | ks) != 0);
        wgmma_commit();
      }
    } else {
      float mx0 = -INFINITY, mx1 = -INFINITY;
      for (int j = 0; j < 32; j++) {
        if (it == 0 && (j & 3) == 0) mbar_wait(sBar + 8 * (j >> 2), 0);
        const uint64_t dk = make_desc(sK + j * 8 * 384, 128, 384, 0);
        wgmma_fence();
        wgmma_rs_n64(S, qa[0], qa[1], qa[2], qa[3], dk, 0);
        wgmma_rs_n64(S, qc[0], qc[1], qc[2], qc[3], dk + (256 >> 4), 1);
        wgmma_commit();
        wgmma_wait<0>();
#pragma unroll
        for (int i = 0; i < 8; i++) {
          mx0 = fmaxf(mx0, fmaxf(S[4 * i], S[4 * i + 1]));
          mx1 = fmaxf(mx1, fmaxf(S[4 * i + 2], S[4 * i + 3]));
        }
      }
      mx0 = fmaxf(mx0, __shfl_xor_sync(~0u, mx0, 1)); mx0 = fmaxf(mx0, __shfl_xor_sync(~0u, mx0, 2));
      mx1 = fmaxf(mx1, __shfl_xor_sync(~0u, mx1, 1)); mx1 = fmaxf(mx1, __shfl_xor_sync(~0u, mx1, 2));
      for (int j = 0; j < 32; j++) {
        const uint64_t dk = make_desc(sK + j * 8 * 384, 128, 384, 0);
        wgmma_fence();
        wgmma_rs_n64(S, qa[0], qa[1], qa[2], qa[3], dk, 0);
        wgmma_rs_n64(S, qc[0], qc[1], qc[2], qc[3], dk + (256 >> 4), 1);
        wgmma_commit();
        wgmma_wait<0>();
        uint32_t P[16];
#pragma unroll
        for (int i = 0; i < 8; i++) {
          P[2 * i] = pack_bf16(ex2_mufu(S[4 * i] - mx0), ex2_mufu(S[4 * i + 1] - mx0));
          P[2 * i + 1] = pack_bf16(ex2_mufu(S[4 * i + 2] - mx1), ex2_mufu(S[4 * i + 3] - mx1));
        }
        wgmma_fence();
        const uint64_t dv = make_desc(sV + j * 8 * 384, 384, 128, 0);
#pragma unroll
        for (int ks = 0; ks < 4; ks++)
          wgmma_rs_n24_tb(O, P[4 * ks], P[4 * ks + 1], P[4 * ks + 2], P[4 * ks + 3], dv + ((ks * 768) >> 4), (j | ks) != 0);
        wgmma_commit();
      }
    }
    wgmma_wait<0>();
#pragma unroll
    for (int i = 0; i < 12; i++) asm volatile("" : "+f"(O[i]) :: "memory");
    const float l0 = __shfl_sync(~0u, O[8], (lane & ~3) | 2), l1 = __shfl_sync(~0u, O[10], (lane & ~3) | 2);
    const float r0 = 1.f / l0, r1 = 1.f / l1;
    uint32_t* o0 = (uint32_t*)(g_o + (size_t)(q0 + g) * DM + h * DH);
    uint32_t* o1 = (uint32_t*)(g_o + (size_t)(q0 + g + 8) * DM + h * DH);
    o0[t] = pack_bf16(O[0] * r0, O[1] * r0); o1[t] = pack_bf16(O[2] * r1, O[3] * r1);
    o0[t + 4] = pack_bf16(O[4] * r0, O[5] * r0); o1[t + 4] = pack_bf16(O[6] * r1, O[7] * r1);
    if (t < 2) { o0[t + 8] = pack_bf16(O[8] * r0, O[9] * r0); o1[t + 8] = pack_bf16(O[10] * r1, O[11] * r1); }
  }
  TS_END(2);
}

typedef CUresult (*EncodeFn)(CUtensorMap*, CUtensorMapDataType, cuuint32_t, void*, const cuuint64_t*, const cuuint64_t*, const cuuint32_t*,
                             const cuuint32_t*, CUtensorMapInterleave, CUtensorMapSwizzle, CUtensorMapL2promotion, CUtensorMapFloatOOBfill);
static EncodeFn get_encode() {
  static EncodeFn fn = nullptr;
  if (!fn) {
    void* p = nullptr; cudaDriverEntryPointQueryResult st;
    cudaGetDriverEntryPoint("cuTensorMapEncodeTiled", &p, cudaEnableDefault, &st);
    fn = (EncodeFn)p;
  }
  return fn;
}
static CUtensorMap make_map(const void* ptr, int rows, int cols, int box_rows, int box_cols = 64) {
  CUtensorMap m;
  cuuint64_t dims[2] = {(cuuint64_t)cols, (cuuint64_t)rows};
  cuuint64_t strides[1] = {(cuuint64_t)cols * 2};
  cuuint32_t box[2] = {(cuuint32_t)box_cols, (cuuint32_t)box_rows};
  cuuint32_t es[2] = {1, 1};
  get_encode()(&m, CU_TENSOR_MAP_DATA_TYPE_BFLOAT16, 2, const_cast<void*>(ptr), dims, strides, box, es, CU_TENSOR_MAP_INTERLEAVE_NONE,
               box_cols == 64 ? CU_TENSOR_MAP_SWIZZLE_128B : (box_cols == 32 ? CU_TENSOR_MAP_SWIZZLE_64B : CU_TENSOR_MAP_SWIZZLE_32B), CU_TENSOR_MAP_L2_PROMOTION_L2_128B, CU_TENSOR_MAP_FLOAT_OOB_FILL_NONE);
  return m;
}
static CUtensorMap make_map_w(const void* ptr, int rows, int cols, int bc, int nblk) {
  CUtensorMap m;
  cuuint64_t dims[3] = {(cuuint64_t)bc, (cuuint64_t)rows, (cuuint64_t)(cols / bc)};
  cuuint64_t strides[2] = {(cuuint64_t)cols * 2, (cuuint64_t)bc * 2};
  cuuint32_t box[3] = {(cuuint32_t)bc, 64, (cuuint32_t)nblk};
  cuuint32_t es[3] = {1, 1, 1};
  get_encode()(&m, CU_TENSOR_MAP_DATA_TYPE_BFLOAT16, 3, const_cast<void*>(ptr), dims, strides, box, es, CU_TENSOR_MAP_INTERLEAVE_NONE,
               bc == 64 ? CU_TENSOR_MAP_SWIZZLE_128B : (bc == 32 ? CU_TENSOR_MAP_SWIZZLE_64B : CU_TENSOR_MAP_SWIZZLE_32B),
               CU_TENSOR_MAP_L2_PROMOTION_L2_128B, CU_TENSOR_MAP_FLOAT_OOB_FILL_NONE);
  return m;
}
template <typename... KArgs, typename... Args>
static void launch(void (*kern)(KArgs...), dim3 grid, dim3 block, size_t smem, bool pdl, dim3 cluster, Args... args) {
  cudaLaunchConfig_t cfg = {};
  cfg.gridDim = grid; cfg.blockDim = block; cfg.dynamicSmemBytes = smem; cfg.stream = cudaStreamPerThread;
  cudaLaunchAttribute at[2];
  int na = 0;
  if (pdl) { at[na].id = cudaLaunchAttributeProgrammaticStreamSerialization; at[na].val.programmaticStreamSerializationAllowed = 1; na++; }
  if (cluster.x * cluster.y > 1) { at[na].id = cudaLaunchAttributeClusterDimension; at[na].val.clusterDim.x = cluster.x; at[na].val.clusterDim.y = cluster.y; at[na].val.clusterDim.z = 1; na++; }
  cfg.attrs = at; cfg.numAttrs = na;
  cudaLaunchKernelEx(&cfg, kern, KArgs(args)...);
}

extern "C" void kernel_launch(void* const* d_in, const int* in_sizes, int n_in, void* d_out, int out_size) {
  const __nv_bfloat16* x = (const __nv_bfloat16*)d_in[0];
  const __nv_bfloat16* wqkv = (const __nv_bfloat16*)d_in[1];
  const __nv_bfloat16* wo = (const __nv_bfloat16*)d_in[2];
  const __nv_bfloat16* wgate = (const __nv_bfloat16*)d_in[4];
  const __nv_bfloat16* wup = (const __nv_bfloat16*)d_in[5];
  const __nv_bfloat16* wdown = (const __nv_bfloat16*)d_in[6];
  __nv_bfloat16* out = (__nv_bfloat16*)d_out;
  void *p_o, *p_h, *p_act;
  cudaGetSymbolAddress(&p_o, g_o); cudaGetSymbolAddress(&p_h, g_h); cudaGetSymbolAddress(&p_act, g_act);

#define A_CN 1
#define A_CM 1
#define D_CN 1
#define D_CM 1
  auto kA = gemm_kernel<256, 128, 1, DM, 4, EPI_QKV, 1, A_CN, A_CM>;
  auto kC = gemm_res_kernel<DM, true>;
  auto kD = gemm_kernel<128, 192, 2, DM, 3, EPI_GLU, 1, D_CN, D_CM>;
  auto kE = gemm_res_kernel<DFF, false>;
  constexpr int smA = GemmCfg<256, 128, 1, 4>::SMEM, smC = R_SMEM, smD = GemmCfg<128, 192, 2, 3>::SMEM;
  cudaFuncSetAttribute(kA, cudaFuncAttributeMaxDynamicSharedMemorySize, smA);
  cudaFuncSetAttribute(kC, cudaFuncAttributeMaxDynamicSharedMemorySize, smC);
  cudaFuncSetAttribute(kD, cudaFuncAttributeMaxDynamicSharedMemorySize, smD);
  cudaFuncSetAttribute(kE, cudaFuncAttributeMaxDynamicSharedMemorySize, smC);
  cudaFuncSetAttribute(attn_kernel, cudaFuncAttributeMaxDynamicSharedMemorySize, ATT_SMEM);

  const CUtensorMap tm_x = make_map(x, S_LEN, DM, 256), tm_wqkv = make_map_w(wqkv, DM, 3 * DM, 64, 2);
  const CUtensorMap tm_o = make_map(p_o, S_LEN, DM, 128), tm_wo = make_map_w(wo, DM, DM, 16, 5);
  const CUtensorMap tm_h = make_map(p_h, S_LEN, DM, 128), tm_wg = make_map_w(wgate, DM, DFF, 64, 3), tm_wu = make_map_w(wup, DM, DFF, 64, 3);
  const CUtensorMap tm_act = make_map(p_act, S_LEN, DFF, 128), tm_wd = make_map_w(wdown, DFF, DM, 16, 5);

  launch(pre_kernel, dim3(12), dim3(1024), 0, false, dim3(1, 1), x, wqkv);
  launch(kA, dim3(15, 8), dim3(288), smA, true, dim3(A_CN, A_CM), tm_x, tm_wqkv, tm_wqkv, x, (__nv_bfloat16*)wqkv);
  launch(attn_kernel, dim3(132), dim3(512), ATT_SMEM, true, dim3(1, 1), 0x800000, wgate, wup, wo, wdown);
  launch(kC, dim3(8, 16), dim3(288), smC, true, dim3(1, 1), tm_o, tm_wo, x, (__nv_bfloat16*)p_h);
  launch(kD, dim3(8, 16), dim3(384), smD, true, dim3(D_CN, D_CM), tm_h, tm_wg, tm_wu, (const __nv_bfloat16*)nullptr, (__nv_bfloat16*)p_act);
  launch(kE, dim3(8, 16), dim3(288), smC, true, dim3(1, 1), tm_act, tm_wd, (const __nv_bfloat16*)p_h, out);
}
```

```cpp
#include <cuda_runtime.h>
#include <cuda_bf16.h>
#include <cuda.h>
#include <stdint.h>

constexpr int S_LEN = 2048, DM = 640, NH = 32, DH = 20, DFF = 1536;

__device__ __align__(1024) __nv_bfloat16 g_q[S_LEN * DM];
__device__ __align__(1024) __nv_bfloat16 g_k[NH * S_LEN * 24];
__device__ __align__(1024) __nv_bfloat16 g_v[NH * S_LEN * 24];
__device__ __align__(1024) __nv_bfloat16 g_o[S_LEN * DM];
__device__ __align__(1024) __nv_bfloat16 g_h[S_LEN * DM];
__device__ __align__(1024) __nv_bfloat16 g_act[S_LEN * DFF];
__device__ float g_kn[8 * NH * 2];
__device__ float2 g_stat1[S_LEN];
__device__ float g_cs_qkv[3 * DM];
__device__ float g_cs_g[DFF];
__device__ float g_cs_u[DFF];
__device__ float2 g_part2[S_LEN * 10];

#define TS_BEGIN(k)
#define TS_END(k)
#define TS_MID(k, i)
__device__ __forceinline__ uint32_t smem_u32(const void* p) { return (uint32_t)__cvta_generic_to_shared(p); }
__device__ __forceinline__ void mbar_init(uint32_t bar, uint32_t cnt) { asm volatile("mbarrier.init.shared::cta.b64 [%0], %1;" :: "r"(bar), "r"(cnt)); }
__device__ __forceinline__ void mbar_expect_tx(uint32_t bar, uint32_t bytes) { asm volatile("mbarrier.arrive.expect_tx.shared::cta.b64 _, [%0], %1;" :: "r"(bar), "r"(bytes) : "memory"); }
__device__ __forceinline__ void mbar_arrive(uint32_t bar) { asm volatile("mbarrier.arrive.shared::cta.b64 _, [%0];" :: "r"(bar) : "memory"); }
__device__ __forceinline__ void mbar_wait(uint32_t bar, uint32_t parity) {
  uint32_t done;
  uint32_t spins = 0;
  do {
    asm volatile("{\n.reg .pred P1;\nmbarrier.try_wait.parity.shared::cta.b64 P1, [%1], %2;\nselp.u32 %0, 1, 0, P1;\n}" : "=r"(done) : "r"(bar), "r"(parity) : "memory");
  } while (!done && ++spins < (1u << 24));
}
__device__ __forceinline__ void bulk_g2s(uint32_t dst, const void* src, uint32_t bytes, uint32_t bar) {
  asm volatile("cp.async.bulk.shared::cluster.global.mbarrier::complete_tx::bytes [%0], [%1], %2, [%3];" :: "r"(dst), "l"(src), "r"(bytes), "r"(bar) : "memory");
}
__device__ __forceinline__ void tma_2d(uint32_t dst, const CUtensorMap* tm, int c0, int c1, uint32_t bar) {
  asm volatile("cp.async.bulk.tensor.2d.shared::cluster.global.mbarrier::complete_tx::bytes [%0], [%1, {%3, %4}], [%2];"
               :: "r"(dst), "l"(tm), "r"(bar), "r"(c0), "r"(c1) : "memory");
}
__device__ __forceinline__ void tma_3d(uint32_t dst, const CUtensorMap* tm, int c0, int c1, int c2, uint32_t bar) {
  asm volatile("cp.async.bulk.tensor.3d.shared::cluster.global.mbarrier::complete_tx::bytes [%0], [%1, {%3, %4, %5}], [%2];"
               :: "r"(dst), "l"(tm), "r"(bar), "r"(c0), "r"(c1), "r"(c2) : "memory");
}
__device__ __forceinline__ void tma_2d_mc(uint32_t dst, const CUtensorMap* tm, int c0, int c1, uint32_t bar, uint16_t mask) {
  asm volatile("cp.async.bulk.tensor.2d.shared::cluster.global.mbarrier::complete_tx::bytes.multicast::cluster [%0], [%1, {%3, %4}], [%2], %5;"
               :: "r"(dst), "l"(tm), "r"(bar), "r"(c0), "r"(c1), "h"(mask) : "memory");
}
__device__ __forceinline__ void mbar_arrive_remote(uint32_t bar, uint32_t rank) {
  asm volatile("{\n.reg .b32 ra;\nmapa.shared::cluster.u32 ra, %0, %1;\nmbarrier.arrive.release.cluster.shared::cluster.b64 _, [ra];\n}" :: "r"(bar), "r"(rank) : "memory");
}
__device__ __forceinline__ void cluster_arrive() { asm volatile("barrier.cluster.arrive.release.aligned;" ::: "memory"); }
__device__ __forceinline__ void cluster_wait() { asm volatile("barrier.cluster.wait.acquire.aligned;" ::: "memory"); }
__device__ __forceinline__ void wgmma_fence() { asm volatile("wgmma.fence.sync.aligned;" ::: "memory"); }
__device__ __forceinline__ void wgmma_commit() { asm volatile("wgmma.commit_group.sync.aligned;" ::: "memory"); }
template <int N> __device__ __forceinline__ void wgmma_wait() { asm volatile("wgmma.wait_group.sync.aligned %0;" :: "n"(N) : "memory"); }
__device__ __forceinline__ void pdl_wait() { asm volatile("griddepcontrol.wait;" ::: "memory"); }
__device__ __forceinline__ void pdl_launch() { asm volatile("griddepcontrol.launch_dependents;" ::: "memory"); }
__device__ __forceinline__ void named_bar(int id, int n) { asm volatile("bar.sync %0, %1;" :: "r"(id), "r"(n) : "memory"); }
__device__ __forceinline__ uint64_t make_desc(uint32_t addr, uint32_t lbo, uint32_t sbo, uint32_t swz) {
  return (uint64_t)((addr & 0x3FFFF) >> 4) | ((uint64_t)(lbo >> 4) << 16) | ((uint64_t)(sbo >> 4) << 32) | ((uint64_t)swz << 62);
}
__device__ __forceinline__ void st_g16(void* p, uint4 v) { asm volatile("st.global.v4.b32 [%0], {%1, %2, %3, %4};" :: "l"(p), "r"(v.x), "r"(v.y), "r"(v.z), "r"(v.w) : "memory"); }
__device__ __forceinline__ void st_g8(void* p, uint2 v) { asm volatile("st.global.v2.b32 [%0], {%1, %2};" :: "l"(p), "r"(v.x), "r"(v.y) : "memory"); }
__device__ __forceinline__ uint4 ld_g16(const void* p) { uint4 v; asm volatile("ld.global.v4.b32 {%0, %1, %2, %3}, [%4];" : "=r"(v.x), "=r"(v.y), "=r"(v.z), "=r"(v.w) : "l"(p) : "memory"); return v; }
__device__ __forceinline__ uint32_t pack_bf16(float lo, float hi) { uint32_t r; asm("cvt.rn.bf16x2.f32 %0, %1, %2;" : "=r"(r) : "f"(hi), "f"(lo)); return r; }
__device__ __forceinline__ float bf_lo(uint32_t u) { return __uint_as_float(u << 16); }
__device__ __forceinline__ float bf_hi(uint32_t u) { return __uint_as_float(u & 0xffff0000u); }
__device__ __forceinline__ float bf_round(float x) { return __bfloat162float(__float2bfloat16_rn(x)); }
__device__ __forceinline__ float ex2_mufu(float x) { float y; asm("ex2.approx.ftz.f32 %0, %1;" : "=f"(y) : "f"(x)); return y; }

__device__ __forceinline__ void wgmma_ss_n80(float (&d)[40], uint64_t da, uint64_t db, int scale_d) {
  asm volatile("{\n.reg .pred p;\nsetp.ne.b32 p, %42, 0;\n"
    "wgmma.mma_async.sync.aligned.m64n80k16.f32.bf16.bf16 {%0,%1,%2,%3,%4,%5,%6,%7,%8,%9,%10,%11,%12,%13,%14,%15,%16,%17,%18,%19,%20,%21,%22,%23,%24,%25,%26,%27,%28,%29,%30,%31,%32,%33,%34,%35,%36,%37,%38,%39}, %40, %41, p, 1, 1, 0, 1;\n}\n"
    : "+f"(d[0]),"+f"(d[1]),"+f"(d[2]),"+f"(d[3]),"+f"(d[4]),"+f"(d[5]),"+f"(d[6]),"+f"(d[7]),"+f"(d[8]),"+f"(d[9]),"+f"(d[10]),"+f"(d[11]),"+f"(d[12]),"+f"(d[13]),"+f"(d[14]),"+f"(d[15]),"+f"(d[16]),"+f"(d[17]),"+f"(d[18]),"+f"(d[19]),"+f"(d[20]),"+f"(d[21]),"+f"(d[22]),"+f"(d[23]),"+f"(d[24]),"+f"(d[25]),"+f"(d[26]),"+f"(d[27]),"+f"(d[28]),"+f"(d[29]),"+f"(d[30]),"+f"(d[31]),"+f"(d[32]),"+f"(d[33]),"+f"(d[34]),"+f"(d[35]),"+f"(d[36]),"+f"(d[37]),"+f"(d[38]),"+f"(d[39])
    : "l"(da), "l"(db), "r"(scale_d));
}
__device__ __forceinline__ void wgmma_ss_n128(float (&d)[64], uint64_t da, uint64_t db, int scale_d) {
  asm volatile("{\n.reg .pred p;\nsetp.ne.b32 p, %66, 0;\n"
    "wgmma.mma_async.sync.aligned.m64n128k16.f32.bf16.bf16 {%0,%1,%2,%3,%4,%5,%6,%7,%8,%9,%10,%11,%12,%13,%14,%15,%16,%17,%18,%19,%20,%21,%22,%23,%24,%25,%26,%27,%28,%29,%30,%31,%32,%33,%34,%35,%36,%37,%38,%39,%40,%41,%42,%43,%44,%45,%46,%47,%48,%49,%50,%51,%52,%53,%54,%55,%56,%57,%58,%59,%60,%61,%62,%63}, %64, %65, p, 1, 1, 0, 1;\n}\n"
    : "+f"(d[0]),"+f"(d[1]),"+f"(d[2]),"+f"(d[3]),"+f"(d[4]),"+f"(d[5]),"+f"(d[6]),"+f"(d[7]),"+f"(d[8]),"+f"(d[9]),"+f"(d[10]),"+f"(d[11]),"+f"(d[12]),"+f"(d[13]),"+f"(d[14]),"+f"(d[15]),"+f"(d[16]),"+f"(d[17]),"+f"(d[18]),"+f"(d[19]),"+f"(d[20]),"+f"(d[21]),"+f"(d[22]),"+f"(d[23]),"+f"(d[24]),"+f"(d[25]),"+f"(d[26]),"+f"(d[27]),"+f"(d[28]),"+f"(d[29]),"+f"(d[30]),"+f"(d[31]),"+f"(d[32]),"+f"(d[33]),"+f"(d[34]),"+f"(d[35]),"+f"(d[36]),"+f"(d[37]),"+f"(d[38]),"+f"(d[39]),"+f"(d[40]),"+f"(d[41]),"+f"(d[42]),"+f"(d[43]),"+f"(d[44]),"+f"(d[45]),"+f"(d[46]),"+f"(d[47]),"+f"(d[48]),"+f"(d[49]),"+f"(d[50]),"+f"(d[51]),"+f"(d[52]),"+f"(d[53]),"+f"(d[54]),"+f"(d[55]),"+f"(d[56]),"+f"(d[57]),"+f"(d[58]),"+f"(d[59]),"+f"(d[60]),"+f"(d[61]),"+f"(d[62]),"+f"(d[63])
    : "l"(da), "l"(db), "r"(scale_d));
}
__device__ __forceinline__ void wgmma_ss_n192(float (&d)[96], uint64_t da, uint64_t db, int scale_d) {
  asm volatile("{\n.reg .pred p;\nsetp.ne.b32 p, %98, 0;\n"
    "wgmma.mma_async.sync.aligned.m64n192k16.f32.bf16.bf16 {%0,%1,%2,%3,%4,%5,%6,%7,%8,%9,%10,%11,%12,%13,%14,%15,%16,%17,%18,%19,%20,%21,%22,%23,%24,%25,%26,%27,%28,%29,%30,%31,%32,%33,%34,%35,%36,%37,%38,%39,%40,%41,%42,%43,%44,%45,%46,%47,%48,%49,%50,%51,%52,%53,%54,%55,%56,%57,%58,%59,%60,%61,%62,%63,%64,%65,%66,%67,%68,%69,%70,%71,%72,%73,%74,%75,%76,%77,%78,%79,%80,%81,%82,%83,%84,%85,%86,%87,%88,%89,%90,%91,%92,%93,%94,%95}, %96, %97, p, 1, 1, 0, 1;\n}\n"
    : "+f"(d[0]),"+f"(d[1]),"+f"(d[2]),"+f"(d[3]),"+f"(d[4]),"+f"(d[5]),"+f"(d[6]),"+f"(d[7]),"+f"(d[8]),"+f"(d[9]),"+f"(d[10]),"+f"(d[11]),"+f"(d[12]),"+f"(d[13]),"+f"(d[14]),"+f"(d[15]),"+f"(d[16]),"+f"(d[17]),"+f"(d[18]),"+f"(d[19]),"+f"(d[20]),"+f"(d[21]),"+f"(d[22]),"+f"(d[23]),"+f"(d[24]),"+f"(d[25]),"+f"(d[26]),"+f"(d[27]),"+f"(d[28]),"+f"(d[29]),"+f"(d[30]),"+f"(d[31]),"+f"(d[32]),"+f"(d[33]),"+f"(d[34]),"+f"(d[35]),"+f"(d[36]),"+f"(d[37]),"+f"(d[38]),"+f"(d[39]),"+f"(d[40]),"+f"(d[41]),"+f"(d[42]),"+f"(d[43]),"+f"(d[44]),"+f"(d[45]),"+f"(d[46]),"+f"(d[47]),"+f"(d[48]),"+f"(d[49]),"+f"(d[50]),"+f"(d[51]),"+f"(d[52]),"+f"(d[53]),"+f"(d[54]),"+f"(d[55]),"+f"(d[56]),"+f"(d[57]),"+f"(d[58]),"+f"(d[59]),"+f"(d[60]),"+f"(d[61]),"+f"(d[62]),"+f"(d[63]),"+f"(d[64]),"+f"(d[65]),"+f"(d[66]),"+f"(d[67]),"+f"(d[68]),"+f"(d[69]),"+f"(d[70]),"+f"(d[71]),"+f"(d[72]),"+f"(d[73]),"+f"(d[74]),"+f"(d[75]),"+f"(d[76]),"+f"(d[77]),"+f"(d[78]),"+f"(d[79]),"+f"(d[80]),"+f"(d[81]),"+f"(d[82]),"+f"(d[83]),"+f"(d[84]),"+f"(d[85]),"+f"(d[86]),"+f"(d[87]),"+f"(d[88]),"+f"(d[89]),"+f"(d[90]),"+f"(d[91]),"+f"(d[92]),"+f"(d[93]),"+f"(d[94]),"+f"(d[95])
    : "l"(da), "l"(db), "r"(scale_d));
}
__device__ __forceinline__ void wgmma_ss_n64_k(float (&d)[32], uint64_t da, uint64_t db, int scale_d) {
  asm volatile("{\n.reg .pred p;\nsetp.ne.b32 p, %34, 0;\n"
    "wgmma.mma_async.sync.aligned.m64n64k16.f32.bf16.bf16 {%0,%1,%2,%3,%4,%5,%6,%7,%8,%9,%10,%11,%12,%13,%14,%15,%16,%17,%18,%19,%20,%21,%22,%23,%24,%25,%26,%27,%28,%29,%30,%31}, %32, %33, p, 1, 1, 0, 0;\n}\n"
    : "+f"(d[0]),"+f"(d[1]),"+f"(d[2]),"+f"(d[3]),"+f"(d[4]),"+f"(d[5]),"+f"(d[6]),"+f"(d[7]),"+f"(d[8]),"+f"(d[9]),"+f"(d[10]),"+f"(d[11]),"+f"(d[12]),"+f"(d[13]),"+f"(d[14]),"+f"(d[15]),"+f"(d[16]),"+f"(d[17]),"+f"(d[18]),"+f"(d[19]),"+f"(d[20]),"+f"(d[21]),"+f"(d[22]),"+f"(d[23]),"+f"(d[24]),"+f"(d[25]),"+f"(d[26]),"+f"(d[27]),"+f"(d[28]),"+f"(d[29]),"+f"(d[30]),"+f"(d[31])
    : "l"(da), "l"(db), "r"(scale_d));
}
__device__ __forceinline__ void wgmma_rs_n24_tb(float (&d)[12], uint32_t a0, uint32_t a1, uint32_t a2, uint32_t a3, uint64_t db, int scale_d) {
  asm volatile("{\n.reg .pred p;\nsetp.ne.b32 p, %17, 0;\n"
    "wgmma.mma_async.sync.aligned.m64n24k16.f32.bf16.bf16 {%0,%1,%2,%3,%4,%5,%6,%7,%8,%9,%10,%11}, {%12,%13,%14,%15}, %16, p, 1, 1, 1;\n}\n"
    : "+f"(d[0]),"+f"(d[1]),"+f"(d[2]),"+f"(d[3]),"+f"(d[4]),"+f"(d[5]),"+f"(d[6]),"+f"(d[7]),"+f"(d[8]),"+f"(d[9]),"+f"(d[10]),"+f"(d[11])
    : "r"(a0), "r"(a1), "r"(a2), "r"(a3), "l"(db), "r"(scale_d));
}

constexpr int PRE_ROW_BLOCKS = 64;
constexpr int PRE_COL_BLOCKS = 3 * DM / 64;
__device__ __forceinline__ float2 ln_finish(float mean, float var) {
  float mb = bf_round(mean);
  float s = bf_round(sqrtf(bf_round(bf_round(var) + 1e-5f)));
  return make_float2(mb, 1.0f / s);
}
__device__ __forceinline__ void colsum64(const __nv_bfloat16* __restrict__ w, int ld, int c0, float* __restrict__ dst, float (*red)[65], int tid, int bar_id) {
  const int cg = tid & 7, r0 = tid >> 3;
  float acc[8];
#pragma unroll
  for (int i = 0; i < 8; i++) acc[i] = 0.f;
#pragma unroll 10
  for (int r = r0; r < DM; r += 32) {
    uint4 v = __ldg((const uint4*)(w + (size_t)r * ld + c0 + cg * 8));
    acc[0] += bf_lo(v.x); acc[1] += bf_hi(v.x); acc[2] += bf_lo(v.y); acc[3] += bf_hi(v.y);
    acc[4] += bf_lo(v.z); acc[5] += bf_hi(v.z); acc[6] += bf_lo(v.w); acc[7] += bf_hi(v.w);
  }
#pragma unroll
  for (int i = 0; i < 8; i++) red[r0][cg * 8 + i] = acc[i];
  named_bar(bar_id, 256);
  if (tid < 64) {
    float s = 0.f;
#pragma unroll
    for (int r = 0; r < 32; r++) s += red[r][tid];
    dst[c0 + tid] = s;
  }
  named_bar(bar_id, 256);
}
__global__ void __launch_bounds__(1024) pre_kernel(const __nv_bfloat16* __restrict__ x, const __nv_bfloat16* __restrict__ wqkv) {
  TS_BEGIN(0);
  pdl_launch();
  __shared__ float red[51][161];
  const int tid = threadIdx.x, lane = tid & 31, warp = tid >> 5;
  {
    const int ch = tid % 20, rl = tid / 20;
    if (rl < 51) {
      const __nv_bfloat16* w = wqkv + blockIdx.x * 160 + ch * 8;
      uint4 v[13];
#pragma unroll
      for (int i = 0; i < 13; i++) { const int r = rl + i * 51; v[i] = r < DM ? __ldg((const uint4*)(w + (size_t)r * (3 * DM))) : make_uint4(0, 0, 0, 0); }
      float acc[8];
#pragma unroll
      for (int i = 0; i < 8; i++) acc[i] = 0.f;
#pragma unroll
      for (int i = 0; i < 13; i++) {
        acc[0] += bf_lo(v[i].x); acc[1] += bf_hi(v[i].x); acc[2] += bf_lo(v[i].y); acc[3] += bf_hi(v[i].y);
        acc[4] += bf_lo(v[i].z); acc[5] += bf_hi(v[i].z); acc[6] += bf_lo(v[i].w); acc[7] += bf_hi(v[i].w);
      }
#pragma unroll
      for (int i = 0; i < 8; i++) red[rl][ch * 8 + i] = acc[i];
    }
  }
  const int rbeg = blockIdx.x * 171, rend = min(rbeg + 171, S_LEN);
  for (int row0 = rbeg + warp * 2; row0 < rend; row0 += 64) {
    uint4 v[2][3];
#pragma unroll
    for (int k = 0; k < 2; k++) {
      const int row = min(row0 + k, rend - 1);
      const uint4* p = (const uint4*)(x + (size_t)row * DM);
      v[k][0] = __ldg(p + lane); v[k][1] = __ldg(p + 32 + lane);
      v[k][2] = lane < 16 ? __ldg(p + 64 + lane) : make_uint4(0, 0, 0, 0);
    }
#pragma unroll
    for (int k = 0; k < 2; k++) {
      float f[24];
      const uint32_t u[12] = {v[k][0].x, v[k][0].y, v[k][0].z, v[k][0].w, v[k][1].x, v[k][1].y, v[k][1].z, v[k][1].w, v[k][2].x, v[k][2].y, v[k][2].z, v[k][2].w};
#pragma unroll
      for (int j = 0; j < 12; j++) { f[2 * j] = bf_lo(u[j]); f[2 * j + 1] = bf_hi(u[j]); }
      float s = 0.f;
#pragma unroll
      for (int j = 0; j < 24; j++) s += f[j];
#pragma unroll
      for (int o = 16; o; o >>= 1) s += __shfl_xor_sync(~0u, s, o);
      const float mean = s * (1.0f / DM);
      float q = 0.f;
#pragma unroll
      for (int j = 0; j < 16; j++) { const float d = f[j] - mean; q += d * d; }
      if (lane < 16) {
#pragma unroll
        for (int j = 16; j < 24; j++) { const float d = f[j] - mean; q += d * d; }
      }
#pragma unroll
      for (int o = 16; o; o >>= 1) q += __shfl_xor_sync(~0u, q, o);
      if (lane == 0 && row0 + k < rend) g_stat1[row0 + k] = ln_finish(mean, q * (1.0f / DM));
    }
  }
  __syncthreads();
  if (tid < 160) {
    float s = 0.f;
#pragma unroll 17
    for (int r = 0; r < 51; r++) s += red[r][tid];
    g_cs_qkv[blockIdx.x * 160 + tid] = s;
  }
  TS_END(0);
}

enum { EPI_QKV = 0, EPI_WO = 1, EPI_GLU = 2, EPI_DOWN = 3 };
template <int N> struct WG;
template <> struct WG<128> { static __device__ __forceinline__ void mma(float (&d)[64], uint64_t a, uint64_t b, int s) { wgmma_ss_n128(d, a, b, s); } };
template <> struct WG<192> { static __device__ __forceinline__ void mma(float (&d)[96], uint64_t a, uint64_t b, int s) { wgmma_ss_n192(d, a, b, s); } };

template <int BM, int BN, int NB, int STAGES> struct GemmCfg {
  static constexpr int A_BYTES = BM * 128;
  static constexpr int B_BYTES = NB * (BN / 64) * 8192;
  static constexpr int STAGE_BYTES = A_BYTES + B_BYTES;
  static constexpr int SMEM = STAGES * STAGE_BYTES + 1024   + 256   + 4096  ;
};

constexpr float QSCALE = 0.22360679774997896f * 1.4426950408889634f;

template <int BM, int BN, int NB, int KDIM, int STAGES, int EPI, int MINB, int CN, int CM>
__global__ void __launch_bounds__(EPI == EPI_GLU ? 384 : 288, MINB) gemm_kernel(const __grid_constant__ CUtensorMap tmA, const __grid_constant__ CUtensorMap tmB0,
                                                         const __grid_constant__ CUtensorMap tmB1,
                                                         const __nv_bfloat16* resid, __nv_bfloat16* out) {
  using Cfg = GemmCfg<BM, BN, NB, STAGES>;
  constexpr int MB = BM / 128;
  constexpr int KT = KDIM / 64;
  extern __shared__ uint8_t smem_raw[];
  const uint32_t sbase = (smem_u32(smem_raw) + 1023u) & ~1023u;
  uint8_t* sptr = smem_raw + (sbase - smem_u32(smem_raw));
  const uint32_t sbar = sbase + STAGES * Cfg::STAGE_BYTES;
  const int tid = threadIdx.x, warp = tid >> 5, lane = tid & 31;
  const int n0 = blockIdx.x * BN, m0 = blockIdx.y * BM;
  TS_BEGIN(EPI == EPI_QKV ? 1 : EPI + 2);
  TS_MID(EPI == EPI_QKV ? 1 : EPI + 2, 3);
  constexpr int NCL = CN + CM - 1;
  const int cx = blockIdx.x % CN, cy = blockIdx.y % CM;
  if (tid == 0) {
    for (int i = 0; i < STAGES; i++) { mbar_init(sbar + 8 * i, 1); mbar_init(sbar + 8 * (STAGES + i), 2 * NCL); }
    asm volatile("fence.mbarrier_init.release.cluster;" ::: "memory");
  }
  __syncthreads();
  if constexpr (CN * CM > 1) { cluster_arrive(); cluster_wait(); }
  pdl_launch();
  if (warp >= 8) {
    if constexpr (EPI == EPI_GLU) asm volatile("setmaxnreg.dec.sync.aligned.u32 40;");
    if (warp == 8 && lane == 0) {
      auto load_a = [&](int kt, int s) { tma_2d(sbase + s * Cfg::STAGE_BYTES, &tmA, kt * 64, m0, sbar + 8 * s); };
      auto load_b = [&](int kt, int s) {
        const uint32_t sb = sbase + s * Cfg::STAGE_BYTES + Cfg::A_BYTES;
        tma_3d(sb, &tmB0, 0, kt * 64, blockIdx.x * (BN / 64), sbar + 8 * s);
        if constexpr (NB == 2) tma_3d(sb + (BN / 64) * 8192, &tmB1, 0, kt * 64, blockIdx.x * (BN / 64), sbar + 8 * s);
      };
      if constexpr (EPI == EPI_QKV) {
        const int cta = blockIdx.y * gridDim.x + blockIdx.x;
        const uint32_t xb = S_LEN * DM * 2, xs = 21888;
        if (cta * xs < xb) asm volatile("cp.async.bulk.prefetch.L2.global [%0], %1;" :: "l"((const uint8_t*)resid + (size_t)cta * xs), "r"(min(xs, xb - cta * xs)));
        asm volatile("cp.async.bulk.prefetch.L2.global [%0], %1;" :: "l"((const uint8_t*)out + (size_t)cta * 20480), "r"(20480));
      }
      for (int s = 0; s < STAGES; s++) { mbar_expect_tx(sbar + 8 * s, Cfg::STAGE_BYTES); if (EPI != EPI_QKV || s == 0) load_b(s, s); }
      if (EPI != EPI_QKV) pdl_wait();
      for (int s = 0; s < STAGES; s++) { load_a(s, s); if (EPI == EPI_QKV && s > 0) load_b(s, s); }
      for (int kt = STAGES; kt < KT; kt++) {
        const int s = kt % STAGES;
        mbar_wait(sbar + 8 * (STAGES + s), ((kt / STAGES) - 1) & 1);
        mbar_expect_tx(sbar + 8 * s, Cfg::STAGE_BYTES);
        load_a(kt, s);
        load_b(kt, s);
      }
    }
    if constexpr (EPI == EPI_GLU) {
      if (warp > 8) {
        float2* s_st = (float2*)(sptr + STAGES * Cfg::STAGE_BYTES + 256);
        float* s_cs = (float*)(sptr + STAGES * Cfg::STAGE_BYTES + 256 + 1024);
        pdl_wait();
        for (int r = tid - 288; r < BM; r += 96) {
          const float2* pp = &g_part2[(m0 + r) * 8];
          float s = 0.f;
#pragma unroll
          for (int i = 0; i < 8; i++) s += pp[i].x;
          const float mean = s * (1.0f / DM);
          float q = 0.f;
#pragma unroll
          for (int i = 0; i < 8; i++) { const float2 p = pp[i]; const float d = p.x * (1.0f / 80.f) - mean; q += p.y + 80.f * d * d; }
          s_st[r] = ln_finish(mean, q * (1.0f / DM));
        }
        for (int c = tid - 288; c < BN; c += 96) { s_cs[c] = g_cs_g[n0 + c]; s_cs[BN + c] = g_cs_u[n0 + c]; }
        __threadfence_block();
        asm volatile("bar.arrive 2, 352;" ::: "memory");
      }
    }
    if constexpr (CN * CM > 1) { __syncwarp(); cluster_arrive(); cluster_wait(); }
    return;
  }
  if constexpr (EPI == EPI_GLU) asm volatile("setmaxnreg.inc.sync.aligned.u32 232;");
  const int wg = warp >> 2, g = lane >> 2, t = lane & 3;
  float acc[MB][NB][BN / 2];
#pragma unroll
  for (int mb = 0; mb < MB; mb++)
#pragma unroll
    for (int nb = 0; nb < NB; nb++)
#pragma unroll
      for (int i = 0; i < BN / 2; i++) acc[mb][nb][i] = 0.f;
  for (int kt = 0; kt < KT; kt++) {
    const int s = kt % STAGES;
    mbar_wait(sbar + 8 * s, (kt / STAGES) & 1);
    if (kt == 0) TS_MID(EPI == EPI_QKV ? 1 : EPI + 2, 0);
    const uint32_t sa = sbase + s * Cfg::STAGE_BYTES + wg * (MB * 64 * 128);
    const uint32_t sb = sbase + s * Cfg::STAGE_BYTES + Cfg::A_BYTES;
    wgmma_fence();
#pragma unroll
    for (int ks = 0; ks < 4; ks++) {
#pragma unroll
      for (int mb = 0; mb < MB; mb++) {
        const uint64_t da = make_desc(sa + mb * 8192 + ks * 32, 16, 1024, 1);
#pragma unroll
        for (int nb = 0; nb < NB; nb++) {
          const uint64_t db = make_desc(sb + nb * (BN / 64) * 8192 + ks * 2048, 8192, 1024, 1);
          WG<BN>::mma(acc[mb][nb], da, db, 1);
        }
      }
    }
    wgmma_commit();
    wgmma_wait<1>();
    if (kt > 0 && kt - 1 + STAGES < KT && (tid & 127) < NCL) {
      const uint32_t eb = sbar + 8 * (STAGES + (kt - 1) % STAGES);
      if constexpr (CN * CM > 1) {
        const int i = tid & 127;
        const uint32_t rank = i < CN ? cy * CN + i : ((i - CN + (i - CN >= cy ? 1 : 0)) * CN + cx);
        mbar_arrive_remote(eb, rank);
      } else mbar_arrive(eb);
    }
  }
  wgmma_wait<0>();
#pragma unroll
  for (int mb = 0; mb < MB; mb++)
#pragma unroll
    for (int nb = 0; nb < NB; nb++)
#pragma unroll
      for (int i = 0; i < BN / 2; i++) asm volatile("" : "+f"(acc[mb][nb][i]) :: "memory");
  if constexpr (CN * CM > 1) cluster_arrive();
  TS_MID(EPI == EPI_QKV ? 1 : EPI + 2, 1);
  pdl_wait();
  TS_MID(EPI == EPI_QKV ? 1 : EPI + 2, 2);
  named_bar(1, 256);
  constexpr int LDS = BN * 2 + 16;
  const int ctid = tid;

  if constexpr (EPI == EPI_QKV) {
    const int sec = n0 / DM;
    const int lds = sec == 0 ? 272 : 264;
    __shared__ unsigned int s_kn[8];
    if (ctid < 8) s_kn[ctid] = 0u;
    float2 cs[BN / 8];
#pragma unroll
    for (int j = 0; j < BN / 8; j++) cs[j] = *(const float2*)&g_cs_qkv[n0 + j * 8 + 2 * t];
#pragma unroll
    for (int mb = 0; mb < MB; mb++) {
      const int r0 = wg * (MB * 64) + mb * 64 + (warp & 3) * 16 + g;
      const float2 st0 = g_stat1[m0 + r0], st1 = g_stat1[m0 + r0 + 8];
      const float sc0 = sec == 0 ? st0.y * QSCALE : st0.y, sc1 = sec == 0 ? st1.y * QSCALE : st1.y;
#pragma unroll
      for (int j = 0; j < BN / 8; j++) {
        const float* a = &acc[mb][0][4 * j];
        *(uint32_t*)(sptr + r0 * lds + j * 16 + t * 4) = pack_bf16(fmaf(-st0.x, cs[j].x, a[0]) * sc0, fmaf(-st0.x, cs[j].y, a[1]) * sc0);
        *(uint32_t*)(sptr + (r0 + 8) * lds + j * 16 + t * 4) = pack_bf16(fmaf(-st1.x, cs[j].x, a[2]) * sc1, fmaf(-st1.x, cs[j].y, a[3]) * sc1);
      }
    }
    named_bar(1, 256);
    if (sec == 0) {
#pragma unroll
      for (int i = 0; i < BM * (BN / 8) / 256; i++) {
        const int idx = i * 256 + ctid, r = idx / (BN / 8), c = idx % (BN / 8);
        st_g16(g_q + (size_t)(m0 + r) * DM + n0 + c * 8, *(const uint4*)(sptr + r * 272 + c * 16));
      }
    } else {
      const int cbase = n0 - sec * DM;
      const int hfirst = cbase / DH;
      const int j = m0 + ctid;
      uint8_t* dst = (uint8_t*)(sec == 1 ? g_k : g_v) + ((size_t)(j >> 3) * 192 + (j & 7) * 8) * 2;
      const uint8_t* row = sptr + ctid * 264;
#pragma unroll
      for (int i = 0; i < 8; i++) {
        const int hh = hfirst + i;
        const int cr = hh * DH - cbase;
        if (cr < BN) {
          uint2 v[5];
          bool in[5];
          float s = 0.f;
#pragma unroll
          for (int qd = 0; qd < 5; qd++) {
            const int c = cr + 4 * qd;
            in[qd] = c >= 0 && c < BN;
            v[qd] = in[qd] ? *(const uint2*)(row + c * 2) : make_uint2(0u, 0u);
            s += bf_lo(v[qd].x) * bf_lo(v[qd].x) + bf_hi(v[qd].x) * bf_hi(v[qd].x) + bf_lo(v[qd].y) * bf_lo(v[qd].y) + bf_hi(v[qd].y) * bf_hi(v[qd].y);
          }
          uint8_t* p = dst + (size_t)hh * (S_LEN * 48);
          if (in[0] && in[1]) st_g16(p, make_uint4(v[0].x, v[0].y, v[1].x, v[1].y));
          else if (in[0]) st_g8(p, v[0]);
          else if (in[1]) st_g8(p + 8, v[1]);
          if (in[2] && in[3]) st_g16(p + 128, make_uint4(v[2].x, v[2].y, v[3].x, v[3].y));
          else if (in[2]) st_g8(p + 128, v[2]);
          else if (in[3]) st_g8(p + 136, v[3]);
          if (in[4]) st_g16(p + 256, make_uint4(v[4].x, v[4].y, 0x00003f80u, 0u));
          if (sec == 1) {
            const unsigned int mxb = __reduce_max_sync(~0u, __float_as_uint(s) & 0x7fffffffu);
            if (lane == 0) atomicMax(&s_kn[i], mxb);
          }
        }
      }
      if (sec == 1) {
        named_bar(1, 256);
        const int hh = hfirst + ctid;
        if (ctid < 8 && hh * DH < cbase + BN) {
          const bool starts_here = hh * DH >= cbase, ends_here = hh * DH + DH <= cbase + BN;
          const float v = __uint_as_float(s_kn[ctid]);
          float* o = &g_kn[(blockIdx.y * NH + hh) * 2];
          if (starts_here) { o[0] = v; if (ends_here) o[1] = 0.f; }
          else o[1] = v;
        }
      }
    }
  } else if constexpr (EPI == EPI_WO || EPI == EPI_DOWN) {
    const int r0 = wg * 64 + (warp & 3) * 16 + g;
#pragma unroll
    for (int j = 0; j < BN / 8; j++) {
      const float* a = &acc[0][0][4 * j];
      *(uint32_t*)(sptr + r0 * LDS + j * 16 + t * 4) = pack_bf16(a[0], a[1]);
      *(uint32_t*)(sptr + (r0 + 8) * LDS + j * 16 + t * 4) = pack_bf16(a[2], a[3]);
    }
    named_bar(1, 256);
#pragma unroll
    for (int i = 0; i < BM * (BN / 8) / 256; i++) {
      const int idx = i * 256 + ctid, r = idx / (BN / 8), c = idx % (BN / 8);
      const uint4 a = *(const uint4*)(sptr + r * LDS + c * 16);
      const size_t go = (size_t)(m0 + r) * DM + n0 + c * 8;
      const uint4 b = ld_g16(resid + go);
      uint4 o;
      o.x = pack_bf16(bf_lo(a.x) + bf_lo(b.x), bf_hi(a.x) + bf_hi(b.x));
      o.y = pack_bf16(bf_lo(a.y) + bf_lo(b.y), bf_hi(a.y) + bf_hi(b.y));
      o.z = pack_bf16(bf_lo(a.z) + bf_lo(b.z), bf_hi(a.z) + bf_hi(b.z));
      o.w = pack_bf16(bf_lo(a.w) + bf_lo(b.w), bf_hi(a.w) + bf_hi(b.w));
      st_g16(out + go, o);
      if constexpr (EPI == EPI_WO) {
        static_assert(BN == 64, "stats assume 8 lanes per row");
        const float f[8] = {bf_lo(o.x), bf_hi(o.x), bf_lo(o.y), bf_hi(o.y), bf_lo(o.z), bf_hi(o.z), bf_lo(o.w), bf_hi(o.w)};
        float s = 0.f;
#pragma unroll
        for (int k = 0; k < 8; k++) s += f[k];
        s += __shfl_xor_sync(~0u, s, 1); s += __shfl_xor_sync(~0u, s, 2); s += __shfl_xor_sync(~0u, s, 4);
        const float mu = s * (1.0f / 64.f);
        float q = 0.f;
#pragma unroll
        for (int k = 0; k < 8; k++) { const float d = f[k] - mu; q += d * d; }
        q += __shfl_xor_sync(~0u, q, 1); q += __shfl_xor_sync(~0u, q, 2); q += __shfl_xor_sync(~0u, q, 4);
        if (c == 0) g_part2[(m0 + r) * 10 + blockIdx.x] = make_float2(s, q);
      }
    }
  } else {
    const int r0 = wg * 64 + (warp & 3) * 16 + g;
    const float2* s_st = (const float2*)(sptr + STAGES * Cfg::STAGE_BYTES + 256);
    const float* s_cs = (const float*)(sptr + STAGES * Cfg::STAGE_BYTES + 256 + 1024);
    named_bar(2, 352);
    float2 st[2] = {s_st[r0], s_st[r0 + 8]};
#pragma unroll
    for (int j = 0; j < BN / 8; j++) {
      const float2 cg = *(const float2*)&s_cs[j * 8 + 2 * t], cu = *(const float2*)&s_cs[BN + j * 8 + 2 * t];
      const float* a = &acc[0][0][4 * j];
      const float* b = &acc[0][1][4 * j];
#pragma unroll
      for (int e = 0; e < 2; e++) {
        const float2 s_ = st[e];
        const uint32_t gp = pack_bf16(fmaf(-s_.x, cg.x, a[2 * e]) * s_.y, fmaf(-s_.x, cg.y, a[2 * e + 1]) * s_.y);
        const uint32_t up = pack_bf16(fmaf(-s_.x, cu.x, b[2 * e]) * s_.y, fmaf(-s_.x, cu.y, b[2 * e + 1]) * s_.y);
        uint32_t r;
        asm("{\n.reg .b32 z;\nmax.bf16x2 z, %1, %3;\nmul.rn.bf16x2 %0, z, %2;\n}" : "=r"(r) : "r"(gp), "r"(up), "r"(0u));
        *(uint32_t*)(sptr + (r0 + 8 * e) * LDS + j * 16 + t * 4) = r;
      }
    }
    named_bar(1, 256);
#pragma unroll
    for (int i = 0; i < BM * (BN / 8) / 256; i++) {
      const int idx = i * 256 + ctid, r = idx / (BN / 8), c = idx % (BN / 8);
      st_g16(out + (size_t)(m0 + r) * DFF + n0 + c * 8, *(const uint4*)(sptr + r * LDS + c * 16));
    }
  }
  if constexpr (CN * CM > 1) cluster_wait();
  TS_END(EPI == EPI_QKV ? 1 : EPI + 2);
}

constexpr int R_STAGES = 8;
constexpr int R_STAGE_BYTES = 16384 + 5 * 2048;
constexpr int R_BAR_OFF = R_STAGES * R_STAGE_BYTES;
constexpr int R_SMEM = R_BAR_OFF + 256 + 1024;
template <int KDIM, bool STATS>
__global__ void __launch_bounds__(288, 1) gemm_res_kernel(const __grid_constant__ CUtensorMap tmA, const __grid_constant__ CUtensorMap tmB,
                                                          const __nv_bfloat16* resid, __nv_bfloat16* out) {
  constexpr int KT = KDIM / 64;
  extern __shared__ uint8_t smem_raw[];
  const uint32_t sbase = (smem_u32(smem_raw) + 1023u) & ~1023u;
  uint8_t* sptr = smem_raw + (sbase - smem_u32(smem_raw));
  const uint32_t sbar = sbase + R_BAR_OFF;
  const int tid = threadIdx.x, warp = tid >> 5, lane = tid & 31;
  const int n0 = blockIdx.x * 80, m0 = blockIdx.y * 128;
  TS_BEGIN(STATS ? 3 : 5);
  if (tid == 0) {
    for (int i = 0; i < R_STAGES; i++) { mbar_init(sbar + 8 * i, 1); mbar_init(sbar + 8 * (R_STAGES + i), 2); }
    asm volatile("fence.mbarrier_init.release.cluster;" ::: "memory");
  }
  __syncthreads();
  pdl_launch();
  if (warp == 8) {
    if (lane == 0) {
      auto load_b = [&](int kt, int s) { tma_3d(sbase + s * R_STAGE_BYTES + 16384, &tmB, 0, kt * 64, blockIdx.x * 5, sbar + 8 * s); };
      for (int s = 0; s < R_STAGES; s++) { mbar_expect_tx(sbar + 8 * s, R_STAGE_BYTES); if (s < 3) load_b(s, s); }
      pdl_wait();
      for (int s = 0; s < R_STAGES; s++) { tma_2d(sbase + s * R_STAGE_BYTES, &tmA, s * 64, m0, sbar + 8 * s); if (s >= 3) load_b(s, s); }
      for (int kt = R_STAGES; kt < KT; kt++) {
        const int s = kt % R_STAGES;
        mbar_wait(sbar + 8 * (R_STAGES + s), ((kt / R_STAGES) - 1) & 1);
        mbar_expect_tx(sbar + 8 * s, R_STAGE_BYTES);
        tma_2d(sbase + s * R_STAGE_BYTES, &tmA, kt * 64, m0, sbar + 8 * s);
        load_b(kt, s);
      }
    }
    return;
  }
  const int wg = warp >> 2, g = lane >> 2, t = lane & 3;
  pdl_wait();
  uint4 rv[5];
#pragma unroll
  for (int i = 0; i < 5; i++) {
    const int idx = i * 256 + tid, r = idx / 10, c = idx % 10;
    rv[i] = ld_g16(resid + (size_t)(m0 + r) * DM + n0 + c * 8);
  }
  float acc[40];
#pragma unroll
  for (int i = 0; i < 40; i++) acc[i] = 0.f;
  for (int kt = 0; kt < KT; kt++) {
    const int s = kt % R_STAGES;
    mbar_wait(sbar + 8 * s, (kt / R_STAGES) & 1);
    if (kt == 0) TS_MID(STATS ? 3 : 5, 0);
    const uint32_t sa = sbase + s * R_STAGE_BYTES + wg * 8192;
    const uint32_t sb = sbase + s * R_STAGE_BYTES + 16384;
    wgmma_fence();
#pragma unroll
    for (int ks = 0; ks < 4; ks++)
      wgmma_ss_n80(acc, make_desc(sa + ks * 32, 16, 1024, 1), make_desc(sb + ks * 512, 2048, 256, 3), 1);
    wgmma_commit();
    wgmma_wait<1>();
    if (kt > 0 && kt - 1 + R_STAGES < KT && (tid & 127) == 0) mbar_arrive(sbar + 8 * (R_STAGES + (kt - 1) % R_STAGES));
  }
  wgmma_wait<0>();
#pragma unroll
  for (int i = 0; i < 40; i++) asm volatile("" : "+f"(acc[i]) :: "memory");
  TS_MID(STATS ? 3 : 5, 1);
  named_bar(1, 256);
  constexpr int LDS = 176;
  const int r0 = wg * 64 + (warp & 3) * 16 + g;
#pragma unroll
  for (int i = 0; i < 10; i++) {
    *(uint32_t*)(sptr + r0 * LDS + i * 16 + t * 4) = pack_bf16(acc[4 * i], acc[4 * i + 1]);
    *(uint32_t*)(sptr + (r0 + 8) * LDS + i * 16 + t * 4) = pack_bf16(acc[4 * i + 2], acc[4 * i + 3]);
  }
  named_bar(1, 256);
  TS_MID(STATS ? 3 : 5, 2);
#pragma unroll
  for (int i = 0; i < 5; i++) {
    const int idx = i * 256 + tid, r = idx / 10, c = idx % 10;
    const uint4 a = *(const uint4*)(sptr + r * LDS + c * 16);
    const uint4 b = rv[i];
    uint4 o;
    o.x = pack_bf16(bf_lo(a.x) + bf_lo(b.x), bf_hi(a.x) + bf_hi(b.x));
    o.y = pack_bf16(bf_lo(a.y) + bf_lo(b.y), bf_hi(a.y) + bf_hi(b.y));
    o.z = pack_bf16(bf_lo(a.z) + bf_lo(b.z), bf_hi(a.z) + bf_hi(b.z));
    o.w = pack_bf16(bf_lo(a.w) + bf_lo(b.w), bf_hi(a.w) + bf_hi(b.w));
    st_g16(out + (size_t)(m0 + r) * DM + n0 + c * 8, o);
    if constexpr (STATS) *(uint4*)(sptr + r * LDS + c * 16) = o;
  }
  TS_MID(STATS ? 3 : 5, 3);
  if constexpr (STATS) {
    named_bar(1, 256);
    const int r = tid >> 1, hf = tid & 1;
    float f[40];
#pragma unroll
    for (int i = 0; i < 5; i++) {
      const uint4 v = *(const uint4*)(sptr + r * LDS + hf * 80 + i * 16);
      f[8 * i] = bf_lo(v.x); f[8 * i + 1] = bf_hi(v.x); f[8 * i + 2] = bf_lo(v.y); f[8 * i + 3] = bf_hi(v.y);
      f[8 * i + 4] = bf_lo(v.z); f[8 * i + 5] = bf_hi(v.z); f[8 * i + 6] = bf_lo(v.w); f[8 * i + 7] = bf_hi(v.w);
    }
    float s = 0.f;
#pragma unroll
    for (int i = 0; i < 40; i++) s += f[i];
    s += __shfl_xor_sync(~0u, s, 1);
    const float mu = s * (1.0f / 80.f);
    float q = 0.f;
#pragma unroll
    for (int i = 0; i < 40; i++) { const float d = f[i] - mu; q += d * d; }
    q += __shfl_xor_sync(~0u, q, 1);
    if (hf == 0) g_part2[(m0 + r) * 8 + blockIdx.x] = make_float2(s, q);
  }
  TS_END(STATS ? 3 : 5);
}

#define POLY_NUM 5
__device__ __forceinline__ float ex2_poly(float x, int shl23) {
  const float MAGIC = 12582912.f;
  const float tt = x + MAGIC;
  const float f = x - (tt - MAGIC);
  float p = fmaf(0.0013276472454890609f, f, 0.009675540961325169f);
  p = fmaf(p, f, 0.05550713092088699f);
  p = fmaf(p, f, 0.24022120237350464f);
  p = fmaf(p, f, 0.6931469440460205f);
  p = fmaf(p, f, 1.0000001192092896f);
  return __int_as_float(__float_as_int(tt) * shl23 + __float_as_int(p));
}
constexpr int KV_BYTES = S_LEN * 48;
constexpr int ATT_SMEM = 2 * KV_BYTES + 256 + 16384;
constexpr int ATT_BODY = 8;

__global__ void __launch_bounds__(512, 1) attn_kernel(int shl23, const __nv_bfloat16* __restrict__ wg_, const __nv_bfloat16* __restrict__ wu_,
                                                      const __nv_bfloat16* __restrict__ wo_, const __nv_bfloat16* __restrict__ wd_) {
  extern __shared__ __align__(1024) uint8_t smem[];
  if (blockIdx.x >= 128) {
    pdl_launch();
    const int e = blockIdx.x - 128, half = threadIdx.x >> 8;
    if (threadIdx.x == 0) {
      for (int i = 0; i < 13; i++) asm volatile("cp.async.bulk.prefetch.L2.global [%0], %1;" :: "l"((const uint8_t*)wo_ + (e * 13 + i) * 16384 * 0 + (size_t)(e * 13 + i >= 50 ? 0 : (e * 13 + i)) * 16384), "r"(16384));
      for (int i = 0; i < 30; i++) asm volatile("cp.async.bulk.prefetch.L2.global [%0], %1;" :: "l"((const uint8_t*)wd_ + (size_t)(e * 30 + i) * 16384), "r"(16384));
    }
    float (*red)[65] = (float (*)[65])(smem + half * 16384);
    for (int b = e * 12 + half; b < e * 12 + 12; b += 2) {
      if (b < 24) colsum64(wg_, DFF, b * 64, g_cs_g, red, threadIdx.x & 255, 1 + half);
      else colsum64(wu_, DFF, (b - 24) * 64, g_cs_u, red, threadIdx.x & 255, 1 + half);
    }
    return;
  }
  const int h = blockIdx.x >> 2, qb = blockIdx.x & 3;
  const uint32_t sK = smem_u32(smem), sV = sK + KV_BYTES, sBar = sV + KV_BYTES;
  const int tid = threadIdx.x;
  TS_BEGIN(2);
  if (tid == 0) {
    for (int i = 0; i < 8; i++) mbar_init(sBar + 8 * i, 1);
    asm volatile("fence.mbarrier_init.release.cluster;" ::: "memory");
  }
  pdl_launch();
  pdl_wait();
  if (tid == 0) {
    const uint8_t* gk = (const uint8_t*)(g_k + (size_t)h * S_LEN * 24);
    const uint8_t* gv = (const uint8_t*)(g_v + (size_t)h * S_LEN * 24);
    for (int i = 0; i < 8; i++) {
      mbar_expect_tx(sBar + 8 * i, 2 * 12288);
      bulk_g2s(sK + i * 12288, gk + i * 12288, 12288, sBar + 8 * i);
      bulk_g2s(sV + i * 12288, gv + i * 12288, 12288, sBar + 8 * i);
    }
  }
  __syncthreads();
  const int wg = tid >> 7, warp = (tid >> 5) & 3, lane = tid & 31, g = lane >> 2, t = lane & 3;
  float ka = 0.f, kb = 0.f;
#pragma unroll
  for (int i = 0; i < 8; i++) {
    const float2 v = *(const float2*)&g_kn[(i * NH + h) * 2];
    ka = (v.x > ka || v.x != v.x) ? v.x : ka;
    kb = (v.y > kb || v.y != v.y) ? v.y : kb;
  }
  const float kn = sqrtf(ka + kb);
  for (int it = 0; it < 2; it++) {
    const int q0 = qb * 512 + (it * 4 + wg) * 64 + warp * 16;
    uint32_t qa[4], qc[4];
    const uint32_t* qr0 = (const uint32_t*)(g_q + (size_t)(q0 + g) * DM + h * DH);
    const uint32_t* qr1 = (const uint32_t*)(g_q + (size_t)(q0 + g + 8) * DM + h * DH);
    qa[0] = qr0[t]; qa[1] = qr1[t]; qa[2] = qr0[t + 4]; qa[3] = qr1[t + 4];
    qc[0] = (t < 2) ? qr0[t + 8] : 0u; qc[1] = (t < 2) ? qr1[t + 8] : 0u; qc[2] = 0; qc[3] = 0;
    auto sq = [](uint32_t u) { const float a = bf_lo(u), b = bf_hi(u); return a * a + b * b; };
    float n0 = sq(qa[0]) + sq(qa[2]) + sq(qc[0]);
    float n1 = sq(qa[1]) + sq(qa[3]) + sq(qc[1]);
    n0 += __shfl_xor_sync(~0u, n0, 1); n0 += __shfl_xor_sync(~0u, n0, 2);
    n1 += __shfl_xor_sync(~0u, n1, 1); n1 += __shfl_xor_sync(~0u, n1, 2);
    const float m0 = ceilf(sqrtf(n0) * kn * 1.001f) + 1.f, m1 = ceilf(sqrtf(n1) * kn * 1.001f) + 1.f;
    const bool unsafe = !(m0 <= 62.f && m1 <= 62.f);
    uint32_t any_unsafe;
    asm volatile("{\n.reg .pred p, q;\nsetp.ne.u32 p, %1, 0;\nbarrier.cta.red.or.pred q, %2, 128, p;\nselp.u32 %0, 1, 0, q;\n}"
                 : "=r"(any_unsafe) : "r"((uint32_t)unsafe), "r"(1 + wg) : "memory");
    const bool fast = !__any_sync(~0u, any_unsafe);
    if (fast && t == 2) { qc[0] = pack_bf16(-m0, 0.f); qc[1] = pack_bf16(-m1, 0.f); }
    {
      uint8_t* qs = smem + 2 * KV_BYTES + 256 + wg * 4096 + warp * 1024 + g * 16 + t * 4;
      *(uint32_t*)(qs) = qa[0]; *(uint32_t*)(qs + 512) = qa[1]; *(uint32_t*)(qs + 128) = qa[2]; *(uint32_t*)(qs + 512 + 128) = qa[3];
      *(uint32_t*)(qs + 256) = qc[0]; *(uint32_t*)(qs + 512 + 256) = qc[1]; *(uint32_t*)(qs + 384) = 0u; *(uint32_t*)(qs + 512 + 384) = 0u;
      asm volatile("fence.proxy.async.shared::cta;" ::: "memory");
      named_bar(1 + wg, 128);
    }
    const uint64_t dq = make_desc(sBar + 256 + wg * 4096, 128, 512, 0);
    float O[12];
#pragma unroll
    for (int i = 0; i < 12; i++) { O[i] = 0.f; asm volatile("" : "+f"(O[i]) :: "memory"); }
    if (fast) {
      float S[2][32];
      uint32_t P[16];
#pragma unroll 1
      for (int jb = 0; jb < 32 / ATT_BODY; jb++) {
        if (it == 0) { for (int c = 0; c < ATT_BODY / 4; c++) mbar_wait(sBar + 8 * (jb * (ATT_BODY / 4) + c), 0); }
        const uint64_t dk0 = make_desc(sK + jb * ATT_BODY * 8 * 384, 128, 384, 0);
        const uint64_t dv0 = make_desc(sV + jb * ATT_BODY * 8 * 384, 384, 128, 0);
        wgmma_fence();
        wgmma_ss_n64_k(S[0], dq, dk0, 0);
        wgmma_ss_n64_k(S[0], dq + (256 >> 4), dk0 + (256 >> 4), 1);
        wgmma_commit();
#pragma unroll
        for (int u = 0; u < ATT_BODY; u++) {
          if (u + 1 < ATT_BODY) {
            const uint64_t dk = dk0 + (((u + 1) * 8 * 384) >> 4);
            wgmma_fence();
            wgmma_ss_n64_k(S[(u + 1) & 1], dq, dk, 0);
            wgmma_ss_n64_k(S[(u + 1) & 1], dq + (256 >> 4), dk + (256 >> 4), 1);
            wgmma_commit();
          }
          if (u == 0 || u == ATT_BODY - 1) wgmma_wait<1>(); else wgmma_wait<2>();
#pragma unroll
          for (int i = 0; i < 32; i++) asm volatile("" : "+f"(S[u & 1][i]) :: "memory");
          const uint64_t dv = dv0 + ((u * 8 * 384) >> 4);
#pragma unroll
          for (int hf = 0; hf < 2; hf++) {
            if (hf == 1 && u > 0) { if (u == ATT_BODY - 1) wgmma_wait<1>(); else wgmma_wait<2>(); }
#pragma unroll
            for (int i = hf * 8; i < hf * 8 + 8; i++) {
              const bool usepoly = ((i + 1) * POLY_NUM / 16) != (i * POLY_NUM / 16);
              float a, b;
              if (usepoly) { a = ex2_poly(S[u & 1][2 * i], shl23); b = ex2_poly(S[u & 1][2 * i + 1], shl23); }
              else { a = ex2_mufu(S[u & 1][2 * i]); b = ex2_mufu(S[u & 1][2 * i + 1]); }
              P[i] = pack_bf16(a, b);
            }
            wgmma_fence();
#pragma unroll
            for (int ks = hf * 2; ks < hf * 2 + 2; ks++)
              wgmma_rs_n24_tb(O, P[4 * ks], P[4 * ks + 1], P[4 * ks + 2], P[4 * ks + 3], dv + ((ks * 768) >> 4), 1);
            wgmma_commit();
          }
        }
        wgmma_wait<0>();
      }
    } else {
      float S[32];
      float mx0 = -INFINITY, mx1 = -INFINITY;
      for (int j = 0; j < 32; j++) {
        if (it == 0 && (j & 3) == 0) mbar_wait(sBar + 8 * (j >> 2), 0);
        const uint64_t dk = make_desc(sK + j * 8 * 384, 128, 384, 0);
        wgmma_fence();
        wgmma_ss_n64_k(S, dq, dk, 0);
        wgmma_ss_n64_k(S, dq + (256 >> 4), dk + (256 >> 4), 1);
        wgmma_commit();
        wgmma_wait<0>();
#pragma unroll
        for (int i = 0; i < 8; i++) {
          mx0 = fmaxf(mx0, fmaxf(S[4 * i], S[4 * i + 1]));
          mx1 = fmaxf(mx1, fmaxf(S[4 * i + 2], S[4 * i + 3]));
        }
      }
      mx0 = fmaxf(mx0, __shfl_xor_sync(~0u, mx0, 1)); mx0 = fmaxf(mx0, __shfl_xor_sync(~0u, mx0, 2));
      mx1 = fmaxf(mx1, __shfl_xor_sync(~0u, mx1, 1)); mx1 = fmaxf(mx1, __shfl_xor_sync(~0u, mx1, 2));
      for (int j = 0; j < 32; j++) {
        const uint64_t dk = make_desc(sK + j * 8 * 384, 128, 384, 0);
        wgmma_fence();
        wgmma_ss_n64_k(S, dq, dk, 0);
        wgmma_ss_n64_k(S, dq + (256 >> 4), dk + (256 >> 4), 1);
        wgmma_commit();
        wgmma_wait<0>();
        uint32_t P[16];
#pragma unroll
        for (int i = 0; i < 8; i++) {
          P[2 * i] = pack_bf16(ex2_mufu(S[4 * i] - mx0), ex2_mufu(S[4 * i + 1] - mx0));
          P[2 * i + 1] = pack_bf16(ex2_mufu(S[4 * i + 2] - mx1), ex2_mufu(S[4 * i + 3] - mx1));
        }
        wgmma_fence();
        const uint64_t dv = make_desc(sV + j * 8 * 384, 384, 128, 0);
#pragma unroll
        for (int ks = 0; ks < 4; ks++)
          wgmma_rs_n24_tb(O, P[4 * ks], P[4 * ks + 1], P[4 * ks + 2], P[4 * ks + 3], dv + ((ks * 768) >> 4), 1);
        wgmma_commit();
      }
    }
    wgmma_wait<0>();
#pragma unroll
    for (int i = 0; i < 12; i++) asm volatile("" : "+f"(O[i]) :: "memory");
    const float l0 = __shfl_sync(~0u, O[8], (lane & ~3) | 2), l1 = __shfl_sync(~0u, O[10], (lane & ~3) | 2);
    const float r0 = 1.f / l0, r1 = 1.f / l1;
    uint32_t* o0 = (uint32_t*)(g_o + (size_t)(q0 + g) * DM + h * DH);
    uint32_t* o1 = (uint32_t*)(g_o + (size_t)(q0 + g + 8) * DM + h * DH);
    o0[t] = pack_bf16(O[0] * r0, O[1] * r0); o1[t] = pack_bf16(O[2] * r1, O[3] * r1);
    o0[t + 4] = pack_bf16(O[4] * r0, O[5] * r0); o1[t + 4] = pack_bf16(O[6] * r1, O[7] * r1);
    if (t < 2) { o0[t + 8] = pack_bf16(O[8] * r0, O[9] * r0); o1[t + 8] = pack_bf16(O[10] * r1, O[11] * r1); }
  }
  TS_END(2);
}

typedef CUresult (*EncodeFn)(CUtensorMap*, CUtensorMapDataType, cuuint32_t, void*, const cuuint64_t*, const cuuint64_t*, const cuuint32_t*,
                             const cuuint32_t*, CUtensorMapInterleave, CUtensorMapSwizzle, CUtensorMapL2promotion, CUtensorMapFloatOOBfill);
static EncodeFn get_encode() {
  static EncodeFn fn = nullptr;
  if (!fn) {
    void* p = nullptr; cudaDriverEntryPointQueryResult st;
    cudaGetDriverEntryPoint("cuTensorMapEncodeTiled", &p, cudaEnableDefault, &st);
    fn = (EncodeFn)p;
  }
  return fn;
}
static CUtensorMap make_map(const void* ptr, int rows, int cols, int box_rows, int box_cols = 64) {
  CUtensorMap m;
  cuuint64_t dims[2] = {(cuuint64_t)cols, (cuuint64_t)rows};
  cuuint64_t strides[1] = {(cuuint64_t)cols * 2};
  cuuint32_t box[2] = {(cuuint32_t)box_cols, (cuuint32_t)box_rows};
  cuuint32_t es[2] = {1, 1};
  get_encode()(&m, CU_TENSOR_MAP_DATA_TYPE_BFLOAT16, 2, const_cast<void*>(ptr), dims, strides, box, es, CU_TENSOR_MAP_INTERLEAVE_NONE,
               box_cols == 64 ? CU_TENSOR_MAP_SWIZZLE_128B : (box_cols == 32 ? CU_TENSOR_MAP_SWIZZLE_64B : CU_TENSOR_MAP_SWIZZLE_32B), CU_TENSOR_MAP_L2_PROMOTION_L2_128B, CU_TENSOR_MAP_FLOAT_OOB_FILL_NONE);
  return m;
}
static CUtensorMap make_map_w(const void* ptr, int rows, int cols, int bc, int nblk) {
  CUtensorMap m;
  cuuint64_t dims[3] = {(cuuint64_t)bc, (cuuint64_t)rows, (cuuint64_t)(cols / bc)};
  cuuint64_t strides[2] = {(cuuint64_t)cols * 2, (cuuint64_t)bc * 2};
  cuuint32_t box[3] = {(cuuint32_t)bc, 64, (cuuint32_t)nblk};
  cuuint32_t es[3] = {1, 1, 1};
  get_encode()(&m, CU_TENSOR_MAP_DATA_TYPE_BFLOAT16, 3, const_cast<void*>(ptr), dims, strides, box, es, CU_TENSOR_MAP_INTERLEAVE_NONE,
               bc == 64 ? CU_TENSOR_MAP_SWIZZLE_128B : (bc == 32 ? CU_TENSOR_MAP_SWIZZLE_64B : CU_TENSOR_MAP_SWIZZLE_32B),
               CU_TENSOR_MAP_L2_PROMOTION_L2_128B, CU_TENSOR_MAP_FLOAT_OOB_FILL_NONE);
  return m;
}
template <typename... KArgs, typename... Args>
static void launch(void (*kern)(KArgs...), dim3 grid, dim3 block, size_t smem, bool pdl, dim3 cluster, Args... args) {
  cudaLaunchConfig_t cfg = {};
  cfg.gridDim = grid; cfg.blockDim = block; cfg.dynamicSmemBytes = smem; cfg.stream = cudaStreamPerThread;
  cudaLaunchAttribute at[2];
  int na = 0;
  if (pdl) { at[na].id = cudaLaunchAttributeProgrammaticStreamSerialization; at[na].val.programmaticStreamSerializationAllowed = 1; na++; }
  if (cluster.x * cluster.y > 1) { at[na].id = cudaLaunchAttributeClusterDimension; at[na].val.clusterDim.x = cluster.x; at[na].val.clusterDim.y = cluster.y; at[na].val.clusterDim.z = 1; na++; }
  cfg.attrs = at; cfg.numAttrs = na;
  cudaLaunchKernelEx(&cfg, kern, KArgs(args)...);
}

extern "C" void kernel_launch(void* const* d_in, const int* in_sizes, int n_in, void* d_out, int out_size) {
  const __nv_bfloat16* x = (const __nv_bfloat16*)d_in[0];
  const __nv_bfloat16* wqkv = (const __nv_bfloat16*)d_in[1];
  const __nv_bfloat16* wo = (const __nv_bfloat16*)d_in[2];
  const __nv_bfloat16* wgate = (const __nv_bfloat16*)d_in[4];
  const __nv_bfloat16* wup = (const __nv_bfloat16*)d_in[5];
  const __nv_bfloat16* wdown = (const __nv_bfloat16*)d_in[6];
  __nv_bfloat16* out = (__nv_bfloat16*)d_out;
  void *p_o, *p_h, *p_act;
  cudaGetSymbolAddress(&p_o, g_o); cudaGetSymbolAddress(&p_h, g_h); cudaGetSymbolAddress(&p_act, g_act);

#define A_CN 1
#define A_CM 1
#define D_CN 1
#define D_CM 1
  auto kA = gemm_kernel<256, 128, 1, DM, 4, EPI_QKV, 1, A_CN, A_CM>;
  auto kC = gemm_res_kernel<DM, true>;
  auto kD = gemm_kernel<128, 192, 2, DM, 3, EPI_GLU, 1, D_CN, D_CM>;
  auto kE = gemm_res_kernel<DFF, false>;
  constexpr int smA = GemmCfg<256, 128, 1, 4>::SMEM, smC = R_SMEM, smD = GemmCfg<128, 192, 2, 3>::SMEM;
  cudaFuncSetAttribute(kA, cudaFuncAttributeMaxDynamicSharedMemorySize, smA);
  cudaFuncSetAttribute(kC, cudaFuncAttributeMaxDynamicSharedMemorySize, smC);
  cudaFuncSetAttribute(kD, cudaFuncAttributeMaxDynamicSharedMemorySize, smD);
  cudaFuncSetAttribute(kE, cudaFuncAttributeMaxDynamicSharedMemorySize, smC);
  cudaFuncSetAttribute(attn_kernel, cudaFuncAttributeMaxDynamicSharedMemorySize, ATT_SMEM);

  const CUtensorMap tm_x = make_map(x, S_LEN, DM, 256), tm_wqkv = make_map_w(wqkv, DM, 3 * DM, 64, 2);
  const CUtensorMap tm_o = make_map(p_o, S_LEN, DM, 128), tm_wo = make_map_w(wo, DM, DM, 16, 5);
  const CUtensorMap tm_h = make_map(p_h, S_LEN, DM, 128), tm_wg = make_map_w(wgate, DM, DFF, 64, 3), tm_wu = make_map_w(wup, DM, DFF, 64, 3);
  const CUtensorMap tm_act = make_map(p_act, S_LEN, DFF, 128), tm_wd = make_map_w(wdown, DFF, DM, 16, 5);

  launch(pre_kernel, dim3(12), dim3(1024), 0, false, dim3(1, 1), x, wqkv);
  launch(kA, dim3(15, 8), dim3(288), smA, true, dim3(A_CN, A_CM), tm_x, tm_wqkv, tm_wqkv, x, (__nv_bfloat16*)wqkv);
  launch(attn_kernel, dim3(132), dim3(512), ATT_SMEM, true, dim3(1, 1), 0x800000, wgate, wup, wo, wdown);
  launch(kC, dim3(8, 16), dim3(288), smC, true, dim3(1, 1), tm_o, tm_wo, x, (__nv_bfloat16*)p_h);
  launch(kD, dim3(8, 16), dim3(384), smD, true, dim3(D_CN, D_CM), tm_h, tm_wg, tm_wu, (const __nv_bfloat16*)nullptr, (__nv_bfloat16*)p_act);
  launch(kE, dim3(8, 16), dim3(288), smC, true, dim3(1, 1), tm_act, tm_wd, (const __nv_bfloat16*)p_h, out);
}
```

```cpp
#include <cuda_runtime.h>
#include <cuda_bf16.h>
#include <cuda.h>
#include <stdint.h>

constexpr int S_LEN = 2048, DM = 640, NH = 32, DH = 20, DFF = 1536;

__device__ __align__(1024) __nv_bfloat16 g_q[S_LEN * DM];
__device__ __align__(1024) __nv_bfloat16 g_k[NH * S_LEN * 24];
__device__ __align__(1024) __nv_bfloat16 g_v[NH * S_LEN * 24];
__device__ __align__(1024) __nv_bfloat16 g_o[S_LEN * DM];
__device__ __align__(1024) __nv_bfloat16 g_h[S_LEN * DM];
__device__ __align__(1024) __nv_bfloat16 g_act[S_LEN * DFF];
__device__ float g_kn[8 * NH * 2];
__device__ float2 g_stat1[S_LEN];
__device__ float g_cs_qkv[3 * DM];
__device__ float g_cs_g[DFF];
__device__ float g_cs_u[DFF];
__device__ float2 g_part2[S_LEN * 10];

#define TS_BEGIN(k)
#define TS_END(k)
#define TS_MID(k, i)
__device__ __forceinline__ uint32_t smem_u32(const void* p) { return (uint32_t)__cvta_generic_to_shared(p); }
__device__ __forceinline__ void mbar_init(uint32_t bar, uint32_t cnt) { asm volatile("mbarrier.init.shared::cta.b64 [%0], %1;" :: "r"(bar), "r"(cnt)); }
__device__ __forceinline__ void mbar_expect_tx(uint32_t bar, uint32_t bytes) { asm volatile("mbarrier.arrive.expect_tx.shared::cta.b64 _, [%0], %1;" :: "r"(bar), "r"(bytes) : "memory"); }
__device__ __forceinline__ void mbar_arrive(uint32_t bar) { asm volatile("mbarrier.arrive.shared::cta.b64 _, [%0];" :: "r"(bar) : "memory"); }
__device__ __forceinline__ void mbar_wait(uint32_t bar, uint32_t parity) {
  uint32_t done;
  uint32_t spins = 0;
  do {
    asm volatile("{\n.reg .pred P1;\nmbarrier.try_wait.parity.shared::cta.b64 P1, [%1], %2;\nselp.u32 %0, 1, 0, P1;\n}" : "=r"(done) : "r"(bar), "r"(parity) : "memory");
  } while (!done && ++spins < (1u << 24));
}
__device__ __forceinline__ void bulk_g2s(uint32_t dst, const void* src, uint32_t bytes, uint32_t bar) {
  asm volatile("cp.async.bulk.shared::cluster.global.mbarrier::complete_tx::bytes [%0], [%1], %2, [%3];" :: "r"(dst), "l"(src), "r"(bytes), "r"(bar) : "memory");
}
__device__ __forceinline__ void tma_2d(uint32_t dst, const CUtensorMap* tm, int c0, int c1, uint32_t bar) {
  asm volatile("cp.async.bulk.tensor.2d.shared::cluster.global.mbarrier::complete_tx::bytes [%0], [%1, {%3, %4}], [%2];"
               :: "r"(dst), "l"(tm), "r"(bar), "r"(c0), "r"(c1) : "memory");
}
__device__ __forceinline__ void tma_3d(uint32_t dst, const CUtensorMap* tm, int c0, int c1, int c2, uint32_t bar) {
  asm volatile("cp.async.bulk.tensor.3d.shared::cluster.global.mbarrier::complete_tx::bytes [%0], [%1, {%3, %4, %5}], [%2];"
               :: "r"(dst), "l"(tm), "r"(bar), "r"(c0), "r"(c1), "r"(c2) : "memory");
}
__device__ __forceinline__ void tma_2d_mc(uint32_t dst, const CUtensorMap* tm, int c0, int c1, uint32_t bar, uint16_t mask) {
  asm volatile("cp.async.bulk.tensor.2d.shared::cluster.global.mbarrier::complete_tx::bytes.multicast::cluster [%0], [%1, {%3, %4}], [%2], %5;"
               :: "r"(dst), "l"(tm), "r"(bar), "r"(c0), "r"(c1), "h"(mask) : "memory");
}
__device__ __forceinline__ void mbar_arrive_remote(uint32_t bar, uint32_t rank) {
  asm volatile("{\n.reg .b32 ra;\nmapa.shared::cluster.u32 ra, %0, %1;\nmbarrier.arrive.release.cluster.shared::cluster.b64 _, [ra];\n}" :: "r"(bar), "r"(rank) : "memory");
}
__device__ __forceinline__ void cluster_arrive() { asm volatile("barrier.cluster.arrive.release.aligned;" ::: "memory"); }
__device__ __forceinline__ void cluster_wait() { asm volatile("barrier.cluster.wait.acquire.aligned;" ::: "memory"); }
__device__ __forceinline__ void wgmma_fence() { asm volatile("wgmma.fence.sync.aligned;" ::: "memory"); }
__device__ __forceinline__ void wgmma_commit() { asm volatile("wgmma.commit_group.sync.aligned;" ::: "memory"); }
template <int N> __device__ __forceinline__ void wgmma_wait() { asm volatile("wgmma.wait_group.sync.aligned %0;" :: "n"(N) : "memory"); }
__device__ __forceinline__ void pdl_wait() { asm volatile("griddepcontrol.wait;" ::: "memory"); }
__device__ __forceinline__ void pdl_launch() { asm volatile("griddepcontrol.launch_dependents;" ::: "memory"); }
__device__ __forceinline__ void named_bar(int id, int n) { asm volatile("bar.sync %0, %1;" :: "r"(id), "r"(n) : "memory"); }
__device__ __forceinline__ uint64_t make_desc(uint32_t addr, uint32_t lbo, uint32_t sbo, uint32_t swz) {
  return (uint64_t)((addr & 0x3FFFF) >> 4) | ((uint64_t)(lbo >> 4) << 16) | ((uint64_t)(sbo >> 4) << 32) | ((uint64_t)swz << 62);
}
__device__ __forceinline__ void st_g16(void* p, uint4 v) { asm volatile("st.global.v4.b32 [%0], {%1, %2, %3, %4};" :: "l"(p), "r"(v.x), "r"(v.y), "r"(v.z), "r"(v.w) : "memory"); }
__device__ __forceinline__ void st_g8(void* p, uint2 v) { asm volatile("st.global.v2.b32 [%0], {%1, %2};" :: "l"(p), "r"(v.x), "r"(v.y) : "memory"); }
__device__ __forceinline__ uint4 ld_g16(const void* p) { uint4 v; asm volatile("ld.global.v4.b32 {%0, %1, %2, %3}, [%4];" : "=r"(v.x), "=r"(v.y), "=r"(v.z), "=r"(v.w) : "l"(p) : "memory"); return v; }
__device__ __forceinline__ uint32_t pack_bf16(float lo, float hi) { uint32_t r; asm("cvt.rn.bf16x2.f32 %0, %1, %2;" : "=r"(r) : "f"(hi), "f"(lo)); return r; }
__device__ __forceinline__ float bf_lo(uint32_t u) { return __uint_as_float(u << 16); }
__device__ __forceinline__ float bf_hi(uint32_t u) { return __uint_as_float(u & 0xffff0000u); }
__device__ __forceinline__ float bf_round(float x) { return __bfloat162float(__float2bfloat16_rn(x)); }
__device__ __forceinline__ float ex2_mufu(float x) { float y; asm("ex2.approx.ftz.f32 %0, %1;" : "=f"(y) : "f"(x)); return y; }

__device__ __forceinline__ void wgmma_ss_n80(float (&d)[40], uint64_t da, uint64_t db, int scale_d) {
  asm volatile("{\n.reg .pred p;\nsetp.ne.b32 p, %42, 0;\n"
    "wgmma.mma_async.sync.aligned.m64n80k16.f32.bf16.bf16 {%0,%1,%2,%3,%4,%5,%6,%7,%8,%9,%10,%11,%12,%13,%14,%15,%16,%17,%18,%19,%20,%21,%22,%23,%24,%25,%26,%27,%28,%29,%30,%31,%32,%33,%34,%35,%36,%37,%38,%39}, %40, %41, p, 1, 1, 0, 1;\n}\n"
    : "+f"(d[0]),"+f"(d[1]),"+f"(d[2]),"+f"(d[3]),"+f"(d[4]),"+f"(d[5]),"+f"(d[6]),"+f"(d[7]),"+f"(d[8]),"+f"(d[9]),"+f"(d[10]),"+f"(d[11]),"+f"(d[12]),"+f"(d[13]),"+f"(d[14]),"+f"(d[15]),"+f"(d[16]),"+f"(d[17]),"+f"(d[18]),"+f"(d[19]),"+f"(d[20]),"+f"(d[21]),"+f"(d[22]),"+f"(d[23]),"+f"(d[24]),"+f"(d[25]),"+f"(d[26]),"+f"(d[27]),"+f"(d[28]),"+f"(d[29]),"+f"(d[30]),"+f"(d[31]),"+f"(d[32]),"+f"(d[33]),"+f"(d[34]),"+f"(d[35]),"+f"(d[36]),"+f"(d[37]),"+f"(d[38]),"+f"(d[39])
    : "l"(da), "l"(db), "r"(scale_d));
}
__device__ __forceinline__ void wgmma_ss_n128(float (&d)[64], uint64_t da, uint64_t db, int scale_d) {
  asm volatile("{\n.reg .pred p;\nsetp.ne.b32 p, %66, 0;\n"
    "wgmma.mma_async.sync.aligned.m64n128k16.f32.bf16.bf16 {%0,%1,%2,%3,%4,%5,%6,%7,%8,%9,%10,%11,%12,%13,%14,%15,%16,%17,%18,%19,%20,%21,%22,%23,%24,%25,%26,%27,%28,%29,%30,%31,%32,%33,%34,%35,%36,%37,%38,%39,%40,%41,%42,%43,%44,%45,%46,%47,%48,%49,%50,%51,%52,%53,%54,%55,%56,%57,%58,%59,%60,%61,%62,%63}, %64, %65, p, 1, 1, 0, 1;\n}\n"
    : "+f"(d[0]),"+f"(d[1]),"+f"(d[2]),"+f"(d[3]),"+f"(d[4]),"+f"(d[5]),"+f"(d[6]),"+f"(d[7]),"+f"(d[8]),"+f"(d[9]),"+f"(d[10]),"+f"(d[11]),"+f"(d[12]),"+f"(d[13]),"+f"(d[14]),"+f"(d[15]),"+f"(d[16]),"+f"(d[17]),"+f"(d[18]),"+f"(d[19]),"+f"(d[20]),"+f"(d[21]),"+f"(d[22]),"+f"(d[23]),"+f"(d[24]),"+f"(d[25]),"+f"(d[26]),"+f"(d[27]),"+f"(d[28]),"+f"(d[29]),"+f"(d[30]),"+f"(d[31]),"+f"(d[32]),"+f"(d[33]),"+f"(d[34]),"+f"(d[35]),"+f"(d[36]),"+f"(d[37]),"+f"(d[38]),"+f"(d[39]),"+f"(d[40]),"+f"(d[41]),"+f"(d[42]),"+f"(d[43]),"+f"(d[44]),"+f"(d[45]),"+f"(d[46]),"+f"(d[47]),"+f"(d[48]),"+f"(d[49]),"+f"(d[50]),"+f"(d[51]),"+f"(d[52]),"+f"(d[53]),"+f"(d[54]),"+f"(d[55]),"+f"(d[56]),"+f"(d[57]),"+f"(d[58]),"+f"(d[59]),"+f"(d[60]),"+f"(d[61]),"+f"(d[62]),"+f"(d[63])
    : "l"(da), "l"(db), "r"(scale_d));
}
__device__ __forceinline__ void wgmma_ss_n192(float (&d)[96], uint64_t da, uint64_t db, int scale_d) {
  asm volatile("{\n.reg .pred p;\nsetp.ne.b32 p, %98, 0;\n"
    "wgmma.mma_async.sync.aligned.m64n192k16.f32.bf16.bf16 {%0,%1,%2,%3,%4,%5,%6,%7,%8,%9,%10,%11,%12,%13,%14,%15,%16,%17,%18,%19,%20,%21,%22,%23,%24,%25,%26,%27,%28,%29,%30,%31,%32,%33,%34,%35,%36,%37,%38,%39,%40,%41,%42,%43,%44,%45,%46,%47,%48,%49,%50,%51,%52,%53,%54,%55,%56,%57,%58,%59,%60,%61,%62,%63,%64,%65,%66,%67,%68,%69,%70,%71,%72,%73,%74,%75,%76,%77,%78,%79,%80,%81,%82,%83,%84,%85,%86,%87,%88,%89,%90,%91,%92,%93,%94,%95}, %96, %97, p, 1, 1, 0, 1;\n}\n"
    : "+f"(d[0]),"+f"(d[1]),"+f"(d[2]),"+f"(d[3]),"+f"(d[4]),"+f"(d[5]),"+f"(d[6]),"+f"(d[7]),"+f"(d[8]),"+f"(d[9]),"+f"(d[10]),"+f"(d[11]),"+f"(d[12]),"+f"(d[13]),"+f"(d[14]),"+f"(d[15]),"+f"(d[16]),"+f"(d[17]),"+f"(d[18]),"+f"(d[19]),"+f"(d[20]),"+f"(d[21]),"+f"(d[22]),"+f"(d[23]),"+f"(d[24]),"+f"(d[25]),"+f"(d[26]),"+f"(d[27]),"+f"(d[28]),"+f"(d[29]),"+f"(d[30]),"+f"(d[31]),"+f"(d[32]),"+f"(d[33]),"+f"(d[34]),"+f"(d[35]),"+f"(d[36]),"+f"(d[37]),"+f"(d[38]),"+f"(d[39]),"+f"(d[40]),"+f"(d[41]),"+f"(d[42]),"+f"(d[43]),"+f"(d[44]),"+f"(d[45]),"+f"(d[46]),"+f"(d[47]),"+f"(d[48]),"+f"(d[49]),"+f"(d[50]),"+f"(d[51]),"+f"(d[52]),"+f"(d[53]),"+f"(d[54]),"+f"(d[55]),"+f"(d[56]),"+f"(d[57]),"+f"(d[58]),"+f"(d[59]),"+f"(d[60]),"+f"(d[61]),"+f"(d[62]),"+f"(d[63]),"+f"(d[64]),"+f"(d[65]),"+f"(d[66]),"+f"(d[67]),"+f"(d[68]),"+f"(d[69]),"+f"(d[70]),"+f"(d[71]),"+f"(d[72]),"+f"(d[73]),"+f"(d[74]),"+f"(d[75]),"+f"(d[76]),"+f"(d[77]),"+f"(d[78]),"+f"(d[79]),"+f"(d[80]),"+f"(d[81]),"+f"(d[82]),"+f"(d[83]),"+f"(d[84]),"+f"(d[85]),"+f"(d[86]),"+f"(d[87]),"+f"(d[88]),"+f"(d[89]),"+f"(d[90]),"+f"(d[91]),"+f"(d[92]),"+f"(d[93]),"+f"(d[94]),"+f"(d[95])
    : "l"(da), "l"(db), "r"(scale_d));
}
__device__ __forceinline__ void wgmma_ss_n64_k(float (&d)[32], uint64_t da, uint64_t db, int scale_d) {
  asm volatile("{\n.reg .pred p;\nsetp.ne.b32 p, %34, 0;\n"
    "wgmma.mma_async.sync.aligned.m64n64k16.f32.bf16.bf16 {%0,%1,%2,%3,%4,%5,%6,%7,%8,%9,%10,%11,%12,%13,%14,%15,%16,%17,%18,%19,%20,%21,%22,%23,%24,%25,%26,%27,%28,%29,%30,%31}, %32, %33, p, 1, 1, 0, 0;\n}\n"
    : "+f"(d[0]),"+f"(d[1]),"+f"(d[2]),"+f"(d[3]),"+f"(d[4]),"+f"(d[5]),"+f"(d[6]),"+f"(d[7]),"+f"(d[8]),"+f"(d[9]),"+f"(d[10]),"+f"(d[11]),"+f"(d[12]),"+f"(d[13]),"+f"(d[14]),"+f"(d[15]),"+f"(d[16]),"+f"(d[17]),"+f"(d[18]),"+f"(d[19]),"+f"(d[20]),"+f"(d[21]),"+f"(d[22]),"+f"(d[23]),"+f"(d[24]),"+f"(d[25]),"+f"(d[26]),"+f"(d[27]),"+f"(d[28]),"+f"(d[29]),"+f"(d[30]),"+f"(d[31])
    : "l"(da), "l"(db), "r"(scale_d));
}
__device__ __forceinline__ void wgmma_rs_n24_tb(float (&d)[12], uint32_t a0, uint32_t a1, uint32_t a2, uint32_t a3, uint64_t db, int scale_d) {
  asm volatile("{\n.reg .pred p;\nsetp.ne.b32 p, %17, 0;\n"
    "wgmma.mma_async.sync.aligned.m64n24k16.f32.bf16.bf16 {%0,%1,%2,%3,%4,%5,%6,%7,%8,%9,%10,%11}, {%12,%13,%14,%15}, %16, p, 1, 1, 1;\n}\n"
    : "+f"(d[0]),"+f"(d[1]),"+f"(d[2]),"+f"(d[3]),"+f"(d[4]),"+f"(d[5]),"+f"(d[6]),"+f"(d[7]),"+f"(d[8]),"+f"(d[9]),"+f"(d[10]),"+f"(d[11])
    : "r"(a0), "r"(a1), "r"(a2), "r"(a3), "l"(db), "r"(scale_d));
}

constexpr int PRE_ROW_BLOCKS = 64;
constexpr int PRE_COL_BLOCKS = 3 * DM / 64;
__device__ __forceinline__ float2 ln_finish(float mean, float var) {
  float mb = bf_round(mean);
  float s = bf_round(sqrtf(bf_round(bf_round(var) + 1e-5f)));
  return make_float2(mb, 1.0f / s);
}
__device__ __forceinline__ void colsum64(const __nv_bfloat16* __restrict__ w, int ld, int c0, float* __restrict__ dst, float (*red)[65], int tid, int bar_id) {
  const int cg = tid & 7, r0 = tid >> 3;
  float acc[8];
#pragma unroll
  for (int i = 0; i < 8; i++) acc[i] = 0.f;
#pragma unroll 10
  for (int r = r0; r < DM; r += 32) {
    uint4 v = __ldg((const uint4*)(w + (size_t)r * ld + c0 + cg * 8));
    acc[0] += bf_lo(v.x); acc[1] += bf_hi(v.x); acc[2] += bf_lo(v.y); acc[3] += bf_hi(v.y);
    acc[4] += bf_lo(v.z); acc[5] += bf_hi(v.z); acc[6] += bf_lo(v.w); acc[7] += bf_hi(v.w);
  }
#pragma unroll
  for (int i = 0; i < 8; i++) red[r0][cg * 8 + i] = acc[i];
  named_bar(bar_id, 256);
  if (tid < 64) {
    float s = 0.f;
#pragma unroll
    for (int r = 0; r < 32; r++) s += red[r][tid];
    dst[c0 + tid] = s;
  }
  named_bar(bar_id, 256);
}
__global__ void __launch_bounds__(1024) pre_kernel(const __nv_bfloat16* __restrict__ x, const __nv_bfloat16* __restrict__ wqkv) {
  TS_BEGIN(0);
  pdl_launch();
  __shared__ float red[51][161];
  const int tid = threadIdx.x, lane = tid & 31, warp = tid >> 5;
  {
    const int ch = tid % 20, rl = tid / 20;
    if (rl < 51) {
      const __nv_bfloat16* w = wqkv + blockIdx.x * 160 + ch * 8;
      uint4 v[13];
#pragma unroll
      for (int i = 0; i < 13; i++) { const int r = rl + i * 51; v[i] = r < DM ? __ldg((const uint4*)(w + (size_t)r * (3 * DM))) : make_uint4(0, 0, 0, 0); }
      float acc[8];
#pragma unroll
      for (int i = 0; i < 8; i++) acc[i] = 0.f;
#pragma unroll
      for (int i = 0; i < 13; i++) {
        acc[0] += bf_lo(v[i].x); acc[1] += bf_hi(v[i].x); acc[2] += bf_lo(v[i].y); acc[3] += bf_hi(v[i].y);
        acc[4] += bf_lo(v[i].z); acc[5] += bf_hi(v[i].z); acc[6] += bf_lo(v[i].w); acc[7] += bf_hi(v[i].w);
      }
#pragma unroll
      for (int i = 0; i < 8; i++) red[rl][ch * 8 + i] = acc[i];
    }
  }
  const int rbeg = blockIdx.x * 171, rend = min(rbeg + 171, S_LEN);
  for (int row0 = rbeg + warp * 2; row0 < rend; row0 += 64) {
    uint4 v[2][3];
#pragma unroll
    for (int k = 0; k < 2; k++) {
      const int row = min(row0 + k, rend - 1);
      const uint4* p = (const uint4*)(x + (size_t)row * DM);
      v[k][0] = __ldg(p + lane); v[k][1] = __ldg(p + 32 + lane);
      v[k][2] = lane < 16 ? __ldg(p + 64 + lane) : make_uint4(0, 0, 0, 0);
    }
#pragma unroll
    for (int k = 0; k < 2; k++) {
      float f[24];
      const uint32_t u[12] = {v[k][0].x, v[k][0].y, v[k][0].z, v[k][0].w, v[k][1].x, v[k][1].y, v[k][1].z, v[k][1].w, v[k][2].x, v[k][2].y, v[k][2].z, v[k][2].w};
#pragma unroll
      for (int j = 0; j < 12; j++) { f[2 * j] = bf_lo(u[j]); f[2 * j + 1] = bf_hi(u[j]); }
      float s = 0.f;
#pragma unroll
      for (int j = 0; j < 24; j++) s += f[j];
#pragma unroll
      for (int o = 16; o; o >>= 1) s += __shfl_xor_sync(~0u, s, o);
      const float mean = s * (1.0f / DM);
      float q = 0.f;
#pragma unroll
      for (int j = 0; j < 16; j++) { const float d = f[j] - mean; q += d * d; }
      if (lane < 16) {
#pragma unroll
        for (int j = 16; j < 24; j++) { const float d = f[j] - mean; q += d * d; }
      }
#pragma unroll
      for (int o = 16; o; o >>= 1) q += __shfl_xor_sync(~0u, q, o);
      if (lane == 0 && row0 + k < rend) g_stat1[row0 + k] = ln_finish(mean, q * (1.0f / DM));
    }
  }
  __syncthreads();
  if (tid < 160) {
    float s = 0.f;
#pragma unroll 17
    for (int r = 0; r < 51; r++) s += red[r][tid];
    g_cs_qkv[blockIdx.x * 160 + tid] = s;
  }
  TS_END(0);
}

enum { EPI_QKV = 0, EPI_WO = 1, EPI_GLU = 2, EPI_DOWN = 3 };
template <int N> struct WG;
template <> struct WG<128> { static __device__ __forceinline__ void mma(float (&d)[64], uint64_t a, uint64_t b, int s) { wgmma_ss_n128(d, a, b, s); } };
template <> struct WG<192> { static __device__ __forceinline__ void mma(float (&d)[96], uint64_t a, uint64_t b, int s) { wgmma_ss_n192(d, a, b, s); } };

template <int BM, int BN, int NB, int STAGES> struct GemmCfg {
  static constexpr int A_BYTES = BM * 128;
  static constexpr int B_BYTES = NB * (BN / 64) * 8192;
  static constexpr int STAGE_BYTES = A_BYTES + B_BYTES;
  static constexpr int SMEM = STAGES * STAGE_BYTES + 1024   + 256   + 4096  ;
};

constexpr float QSCALE = 0.22360679774997896f * 1.4426950408889634f;

template <int BM, int BN, int NB, int KDIM, int STAGES, int EPI, int MINB, int CN, int CM>
__global__ void __launch_bounds__(EPI == EPI_GLU ? 384 : 288, MINB) gemm_kernel(const __grid_constant__ CUtensorMap tmA, const __grid_constant__ CUtensorMap tmB0,
                                                         const __grid_constant__ CUtensorMap tmB1,
                                                         const __nv_bfloat16* resid, __nv_bfloat16* out) {
  using Cfg = GemmCfg<BM, BN, NB, STAGES>;
  constexpr int MB = BM / 128;
  constexpr int KT = KDIM / 64;
  extern __shared__ uint8_t smem_raw[];
  const uint32_t sbase = (smem_u32(smem_raw) + 1023u) & ~1023u;
  uint8_t* sptr = smem_raw + (sbase - smem_u32(smem_raw));
  const uint32_t sbar = sbase + STAGES * Cfg::STAGE_BYTES;
  const int tid = threadIdx.x, warp = tid >> 5, lane = tid & 31;
  const int n0 = blockIdx.x * BN, m0 = blockIdx.y * BM;
  TS_BEGIN(EPI == EPI_QKV ? 1 : EPI + 2);
  TS_MID(EPI == EPI_QKV ? 1 : EPI + 2, 3);
  constexpr int NCL = CN + CM - 1;
  const int cx = blockIdx.x % CN, cy = blockIdx.y % CM;
  if (tid == 0) {
    for (int i = 0; i < STAGES; i++) { mbar_init(sbar + 8 * i, 1); mbar_init(sbar + 8 * (STAGES + i), 2 * NCL); }
    asm volatile("fence.mbarrier_init.release.cluster;" ::: "memory");
  }
  __syncthreads();
  if constexpr (CN * CM > 1) { cluster_arrive(); cluster_wait(); }
  pdl_launch();
  if (warp >= 8) {
    if constexpr (EPI == EPI_GLU) asm volatile("setmaxnreg.dec.sync.aligned.u32 40;");
    if (warp == 8 && lane == 0) {
      auto load_a = [&](int kt, int s) { tma_2d(sbase + s * Cfg::STAGE_BYTES, &tmA, kt * 64, m0, sbar + 8 * s); };
      auto load_b = [&](int kt, int s) {
        const uint32_t sb = sbase + s * Cfg::STAGE_BYTES + Cfg::A_BYTES;
        tma_3d(sb, &tmB0, 0, kt * 64, blockIdx.x * (BN / 64), sbar + 8 * s);
        if constexpr (NB == 2) tma_3d(sb + (BN / 64) * 8192, &tmB1, 0, kt * 64, blockIdx.x * (BN / 64), sbar + 8 * s);
      };
      if constexpr (EPI == EPI_QKV) {
        const int cta = blockIdx.y * gridDim.x + blockIdx.x;
        const uint32_t xb = S_LEN * DM * 2, xs = 21888;
        if (cta * xs < xb) asm volatile("cp.async.bulk.prefetch.L2.global [%0], %1;" :: "l"((const uint8_t*)resid + (size_t)cta * xs), "r"(min(xs, xb - cta * xs)));
        asm volatile("cp.async.bulk.prefetch.L2.global [%0], %1;" :: "l"((const uint8_t*)out + (size_t)cta * 20480), "r"(20480));
      }
      for (int s = 0; s < STAGES; s++) { mbar_expect_tx(sbar + 8 * s, Cfg::STAGE_BYTES); if (EPI != EPI_QKV || s == 0) load_b(s, s); }
      if (EPI != EPI_QKV) pdl_wait();
      for (int s = 0; s < STAGES; s++) { load_a(s, s); if (EPI == EPI_QKV && s > 0) load_b(s, s); }
      for (int kt = STAGES; kt < KT; kt++) {
        const int s = kt % STAGES;
        mbar_wait(sbar + 8 * (STAGES + s), ((kt / STAGES) - 1) & 1);
        mbar_expect_tx(sbar + 8 * s, Cfg::STAGE_BYTES);
        load_a(kt, s);
        load_b(kt, s);
      }
    }
    if constexpr (EPI == EPI_GLU) {
      if (warp > 8) {
        float2* s_st = (float2*)(sptr + STAGES * Cfg::STAGE_BYTES + 256);
        float* s_cs = (float*)(sptr + STAGES * Cfg::STAGE_BYTES + 256 + 1024);
        pdl_wait();
        for (int r = tid - 288; r < BM; r += 96) {
          const float2* pp = &g_part2[(m0 + r) * 8];
          float s = 0.f;
#pragma unroll
          for (int i = 0; i < 8; i++) s += pp[i].x;
          const float mean = s * (1.0f / DM);
          float q = 0.f;
#pragma unroll
          for (int i = 0; i < 8; i++) { const float2 p = pp[i]; const float d = p.x * (1.0f / 80.f) - mean; q += p.y + 80.f * d * d; }
          s_st[r] = ln_finish(mean, q * (1.0f / DM));
        }
        for (int c = tid - 288; c < BN; c += 96) { s_cs[c] = g_cs_g[n0 + c]; s_cs[BN + c] = g_cs_u[n0 + c]; }
        __threadfence_block();
        asm volatile("bar.arrive 2, 352;" ::: "memory");
      }
    }
    if constexpr (CN * CM > 1) { __syncwarp(); cluster_arrive(); cluster_wait(); }
    return;
  }
  if constexpr (EPI == EPI_GLU) asm volatile("setmaxnreg.inc.sync.aligned.u32 232;");
  const int wg = warp >> 2, g = lane >> 2, t = lane & 3;
  float acc[MB][NB][BN / 2];
#pragma unroll
  for (int mb = 0; mb < MB; mb++)
#pragma unroll
    for (int nb = 0; nb < NB; nb++)
#pragma unroll
      for (int i = 0; i < BN / 2; i++) acc[mb][nb][i] = 0.f;
  for (int kt = 0; kt < KT; kt++) {
    const int s = kt % STAGES;
    mbar_wait(sbar + 8 * s, (kt / STAGES) & 1);
    if (kt == 0) TS_MID(EPI == EPI_QKV ? 1 : EPI + 2, 0);
    const uint32_t sa = sbase + s * Cfg::STAGE_BYTES + wg * (MB * 64 * 128);
    const uint32_t sb = sbase + s * Cfg::STAGE_BYTES + Cfg::A_BYTES;
    wgmma_fence();
#pragma unroll
    for (int ks = 0; ks < 4; ks++) {
#pragma unroll
      for (int mb = 0; mb < MB; mb++) {
        const uint64_t da = make_desc(sa + mb * 8192 + ks * 32, 16, 1024, 1);
#pragma unroll
        for (int nb = 0; nb < NB; nb++) {
          const uint64_t db = make_desc(sb + nb * (BN / 64) * 8192 + ks * 2048, 8192, 1024, 1);
          WG<BN>::mma(acc[mb][nb], da, db, 1);
        }
      }
    }
    wgmma_commit();
    wgmma_wait<1>();
    if (kt > 0 && kt - 1 + STAGES < KT && (tid & 127) < NCL) {
      const uint32_t eb = sbar + 8 * (STAGES + (kt - 1) % STAGES);
      if constexpr (CN * CM > 1) {
        const int i = tid & 127;
        const uint32_t rank = i < CN ? cy * CN + i : ((i - CN + (i - CN >= cy ? 1 : 0)) * CN + cx);
        mbar_arrive_remote(eb, rank);
      } else mbar_arrive(eb);
    }
  }
  wgmma_wait<0>();
#pragma unroll
  for (int mb = 0; mb < MB; mb++)
#pragma unroll
    for (int nb = 0; nb < NB; nb++)
#pragma unroll
      for (int i = 0; i < BN / 2; i++) asm volatile("" : "+f"(acc[mb][nb][i]) :: "memory");
  if constexpr (CN * CM > 1) cluster_arrive();
  TS_MID(EPI == EPI_QKV ? 1 : EPI + 2, 1);
  pdl_wait();
  TS_MID(EPI == EPI_QKV ? 1 : EPI + 2, 2);
  named_bar(1, 256);
  constexpr int LDS = BN * 2 + 16;
  const int ctid = tid;

  if constexpr (EPI == EPI_QKV) {
    const int sec = n0 / DM;
    const int lds = sec == 0 ? 272 : 264;
    __shared__ unsigned int s_kn[8];
    if (ctid < 8) s_kn[ctid] = 0u;
    float2 cs[BN / 8];
#pragma unroll
    for (int j = 0; j < BN / 8; j++) cs[j] = *(const float2*)&g_cs_qkv[n0 + j * 8 + 2 * t];
#pragma unroll
    for (int mb = 0; mb < MB; mb++) {
      const int r0 = wg * (MB * 64) + mb * 64 + (warp & 3) * 16 + g;
      const float2 st0 = g_stat1[m0 + r0], st1 = g_stat1[m0 + r0 + 8];
      const float sc0 = sec == 0 ? st0.y * QSCALE : st0.y, sc1 = sec == 0 ? st1.y * QSCALE : st1.y;
#pragma unroll
      for (int j = 0; j < BN / 8; j++) {
        const float* a = &acc[mb][0][4 * j];
        *(uint32_t*)(sptr + r0 * lds + j * 16 + t * 4) = pack_bf16(fmaf(-st0.x, cs[j].x, a[0]) * sc0, fmaf(-st0.x, cs[j].y, a[1]) * sc0);
        *(uint32_t*)(sptr + (r0 + 8) * lds + j * 16 + t * 4) = pack_bf16(fmaf(-st1.x, cs[j].x, a[2]) * sc1, fmaf(-st1.x, cs[j].y, a[3]) * sc1);
      }
    }
    named_bar(1, 256);
    if (sec == 0) {
#pragma unroll
      for (int i = 0; i < BM * (BN / 8) / 256; i++) {
        const int idx = i * 256 + ctid, r = idx / (BN / 8), c = idx % (BN / 8);
        st_g16(g_q + (size_t)(m0 + r) * DM + n0 + c * 8, *(const uint4*)(sptr + r * 272 + c * 16));
      }
    } else {
      const int cbase = n0 - sec * DM;
      const int hfirst = cbase / DH;
      const int j = m0 + ctid;
      uint8_t* dst = (uint8_t*)(sec == 1 ? g_k : g_v) + ((size_t)(j >> 3) * 192 + (j & 7) * 8) * 2;
      const uint8_t* row = sptr + ctid * 264;
#pragma unroll
      for (int i = 0; i < 8; i++) {
        const int hh = hfirst + i;
        const int cr = hh * DH - cbase;
        if (cr < BN) {
          uint2 v[5];
          bool in[5];
          float s = 0.f;
#pragma unroll
          for (int qd = 0; qd < 5; qd++) {
            const int c = cr + 4 * qd;
            in[qd] = c >= 0 && c < BN;
            v[qd] = in[qd] ? *(const uint2*)(row + c * 2) : make_uint2(0u, 0u);
            s += bf_lo(v[qd].x) * bf_lo(v[qd].x) + bf_hi(v[qd].x) * bf_hi(v[qd].x) + bf_lo(v[qd].y) * bf_lo(v[qd].y) + bf_hi(v[qd].y) * bf_hi(v[qd].y);
          }
          uint8_t* p = dst + (size_t)hh * (S_LEN * 48);
          if (in[0] && in[1]) st_g16(p, make_uint4(v[0].x, v[0].y, v[1].x, v[1].y));
          else if (in[0]) st_g8(p, v[0]);
          else if (in[1]) st_g8(p + 8, v[1]);
          if (in[2] && in[3]) st_g16(p + 128, make_uint4(v[2].x, v[2].y, v[3].x, v[3].y));
          else if (in[2]) st_g8(p + 128, v[2]);
          else if (in[3]) st_g8(p + 136, v[3]);
          if (in[4]) st_g16(p + 256, make_uint4(v[4].x, v[4].y, 0x00003f80u, 0u));
          if (sec == 1) {
            const unsigned int mxb = __reduce_max_sync(~0u, __float_as_uint(s) & 0x7fffffffu);
            if (lane == 0) atomicMax(&s_kn[i], mxb);
          }
        }
      }
      if (sec == 1) {
        named_bar(1, 256);
        const int hh = hfirst + ctid;
        if (ctid < 8 && hh * DH < cbase + BN) {
          const bool starts_here = hh * DH >= cbase, ends_here = hh * DH + DH <= cbase + BN;
          const float v = __uint_as_float(s_kn[ctid]);
          float* o = &g_kn[(blockIdx.y * NH + hh) * 2];
          if (starts_here) { o[0] = v; if (ends_here) o[1] = 0.f; }
          else o[1] = v;
        }
      }
    }
  } else if constexpr (EPI == EPI_WO || EPI == EPI_DOWN) {
    const int r0 = wg * 64 + (warp & 3) * 16 + g;
#pragma unroll
    for (int j = 0; j < BN / 8; j++) {
      const float* a = &acc[0][0][4 * j];
      *(uint32_t*)(sptr + r0 * LDS + j * 16 + t * 4) = pack_bf16(a[0], a[1]);
      *(uint32_t*)(sptr + (r0 + 8) * LDS + j * 16 + t * 4) = pack_bf16(a[2], a[3]);
    }
    named_bar(1, 256);
#pragma unroll
    for (int i = 0; i < BM * (BN / 8) / 256; i++) {
      const int idx = i * 256 + ctid, r = idx / (BN / 8), c = idx % (BN / 8);
      const uint4 a = *(const uint4*)(sptr + r * LDS + c * 16);
      const size_t go = (size_t)(m0 + r) * DM + n0 + c * 8;
      const uint4 b = ld_g16(resid + go);
      uint4 o;
      o.x = pack_bf16(bf_lo(a.x) + bf_lo(b.x), bf_hi(a.x) + bf_hi(b.x));
      o.y = pack_bf16(bf_lo(a.y) + bf_lo(b.y), bf_hi(a.y) + bf_hi(b.y));
      o.z = pack_bf16(bf_lo(a.z) + bf_lo(b.z), bf_hi(a.z) + bf_hi(b.z));
      o.w = pack_bf16(bf_lo(a.w) + bf_lo(b.w), bf_hi(a.w) + bf_hi(b.w));
      st_g16(out + go, o);
      if constexpr (EPI == EPI_WO) {
        static_assert(BN == 64, "stats assume 8 lanes per row");
        const float f[8] = {bf_lo(o.x), bf_hi(o.x), bf_lo(o.y), bf_hi(o.y), bf_lo(o.z), bf_hi(o.z), bf_lo(o.w), bf_hi(o.w)};
        float s = 0.f;
#pragma unroll
        for (int k = 0; k < 8; k++) s += f[k];
        s += __shfl_xor_sync(~0u, s, 1); s += __shfl_xor_sync(~0u, s, 2); s += __shfl_xor_sync(~0u, s, 4);
        const float mu = s * (1.0f / 64.f);
        float q = 0.f;
#pragma unroll
        for (int k = 0; k < 8; k++) { const float d = f[k] - mu; q += d * d; }
        q += __shfl_xor_sync(~0u, q, 1); q += __shfl_xor_sync(~0u, q, 2); q += __shfl_xor_sync(~0u, q, 4);
        if (c == 0) g_part2[(m0 + r) * 10 + blockIdx.x] = make_float2(s, q);
      }
    }
  } else {
    const int r0 = wg * 64 + (warp & 3) * 16 + g;
    const float2* s_st = (const float2*)(sptr + STAGES * Cfg::STAGE_BYTES + 256);
    const float* s_cs = (const float*)(sptr + STAGES * Cfg::STAGE_BYTES + 256 + 1024);
    named_bar(2, 352);
    float2 st[2] = {s_st[r0], s_st[r0 + 8]};
#pragma unroll
    for (int j = 0; j < BN / 8; j++) {
      const float2 cg = *(const float2*)&s_cs[j * 8 + 2 * t], cu = *(const float2*)&s_cs[BN + j * 8 + 2 * t];
      const float* a = &acc[0][0][4 * j];
      const float* b = &acc[0][1][4 * j];
#pragma unroll
      for (int e = 0; e < 2; e++) {
        const float2 s_ = st[e];
        const uint32_t gp = pack_bf16(fmaf(-s_.x, cg.x, a[2 * e]) * s_.y, fmaf(-s_.x, cg.y, a[2 * e + 1]) * s_.y);
        const uint32_t up = pack_bf16(fmaf(-s_.x, cu.x, b[2 * e]) * s_.y, fmaf(-s_.x, cu.y, b[2 * e + 1]) * s_.y);
        uint32_t r;
        asm("{\n.reg .b32 z;\nmax.bf16x2 z, %1, %3;\nmul.rn.bf16x2 %0, z, %2;\n}" : "=r"(r) : "r"(gp), "r"(up), "r"(0u));
        *(uint32_t*)(sptr + (r0 + 8 * e) * LDS + j * 16 + t * 4) = r;
      }
    }
    named_bar(1, 256);
#pragma unroll
    for (int i = 0; i < BM * (BN / 8) / 256; i++) {
      const int idx = i * 256 + ctid, r = idx / (BN / 8), c = idx % (BN / 8);
      st_g16(out + (size_t)(m0 + r) * DFF + n0 + c * 8, *(const uint4*)(sptr + r * LDS + c * 16));
    }
  }
  if constexpr (CN * CM > 1) cluster_wait();
  TS_END(EPI == EPI_QKV ? 1 : EPI + 2);
}

constexpr int R_STAGES = 8;
constexpr int R_STAGE_BYTES = 16384 + 5 * 2048;
constexpr int R_BAR_OFF = R_STAGES * R_STAGE_BYTES;
constexpr int R_SMEM = R_BAR_OFF + 256 + 1024;
template <int KDIM, bool STATS>
__global__ void __launch_bounds__(288, 1) gemm_res_kernel(const __grid_constant__ CUtensorMap tmA, const __grid_constant__ CUtensorMap tmB,
                                                          const __nv_bfloat16* resid, __nv_bfloat16* out) {
  constexpr int KT = KDIM / 64;
  extern __shared__ uint8_t smem_raw[];
  const uint32_t sbase = (smem_u32(smem_raw) + 1023u) & ~1023u;
  uint8_t* sptr = smem_raw + (sbase - smem_u32(smem_raw));
  const uint32_t sbar = sbase + R_BAR_OFF;
  const int tid = threadIdx.x, warp = tid >> 5, lane = tid & 31;
  const int n0 = blockIdx.x * 80, m0 = blockIdx.y * 128;
  TS_BEGIN(STATS ? 3 : 5);
  if (tid == 0) {
    for (int i = 0; i < R_STAGES; i++) { mbar_init(sbar + 8 * i, 1); mbar_init(sbar + 8 * (R_STAGES + i), 2); }
    asm volatile("fence.mbarrier_init.release.cluster;" ::: "memory");
  }
  __syncthreads();
  pdl_launch();
  if (warp == 8) {
    if (lane == 0) {
      auto load_b = [&](int kt, int s) { tma_3d(sbase + s * R_STAGE_BYTES + 16384, &tmB, 0, kt * 64, blockIdx.x * 5, sbar + 8 * s); };
      for (int s = 0; s < R_STAGES; s++) { mbar_expect_tx(sbar + 8 * s, R_STAGE_BYTES); if (s < 3) load_b(s, s); }
      pdl_wait();
      for (int s = 0; s < R_STAGES; s++) { tma_2d(sbase + s * R_STAGE_BYTES, &tmA, s * 64, m0, sbar + 8 * s); if (s >= 3) load_b(s, s); }
      for (int kt = R_STAGES; kt < KT; kt++) {
        const int s = kt % R_STAGES;
        mbar_wait(sbar + 8 * (R_STAGES + s), ((kt / R_STAGES) - 1) & 1);
        mbar_expect_tx(sbar + 8 * s, R_STAGE_BYTES);
        tma_2d(sbase + s * R_STAGE_BYTES, &tmA, kt * 64, m0, sbar + 8 * s);
        load_b(kt, s);
      }
    }
    return;
  }
  const int wg = warp >> 2, g = lane >> 2, t = lane & 3;
  pdl_wait();
  uint4 rv[5];
#pragma unroll
  for (int i = 0; i < 5; i++) {
    const int idx = i * 256 + tid, r = idx / 10, c = idx % 10;
    rv[i] = ld_g16(resid + (size_t)(m0 + r) * DM + n0 + c * 8);
  }
  float acc[40];
#pragma unroll
  for (int i = 0; i < 40; i++) acc[i] = 0.f;
  for (int kt = 0; kt < KT; kt++) {
    const int s = kt % R_STAGES;
    mbar_wait(sbar + 8 * s, (kt / R_STAGES) & 1);
    if (kt == 0) TS_MID(STATS ? 3 : 5, 0);
    const uint32_t sa = sbase + s * R_STAGE_BYTES + wg * 8192;
    const uint32_t sb = sbase + s * R_STAGE_BYTES + 16384;
    wgmma_fence();
#pragma unroll
    for (int ks = 0; ks < 4; ks++)
      wgmma_ss_n80(acc, make_desc(sa + ks * 32, 16, 1024, 1), make_desc(sb + ks * 512, 2048, 256, 3), 1);
    wgmma_commit();
    wgmma_wait<1>();
    if (kt > 0 && kt - 1 + R_STAGES < KT && (tid & 127) == 0) mbar_arrive(sbar + 8 * (R_STAGES + (kt - 1) % R_STAGES));
  }
  wgmma_wait<0>();
#pragma unroll
  for (int i = 0; i < 40; i++) asm volatile("" : "+f"(acc[i]) :: "memory");
  TS_MID(STATS ? 3 : 5, 1);
  named_bar(1, 256);
  constexpr int LDS = 176;
  const int r0 = wg * 64 + (warp & 3) * 16 + g;
#pragma unroll
  for (int i = 0; i < 10; i++) {
    *(uint32_t*)(sptr + r0 * LDS + i * 16 + t * 4) = pack_bf16(acc[4 * i], acc[4 * i + 1]);
    *(uint32_t*)(sptr + (r0 + 8) * LDS + i * 16 + t * 4) = pack_bf16(acc[4 * i + 2], acc[4 * i + 3]);
  }
  named_bar(1, 256);
  TS_MID(STATS ? 3 : 5, 2);
#pragma unroll
  for (int i = 0; i < 5; i++) {
    const int idx = i * 256 + tid, r = idx / 10, c = idx % 10;
    const uint4 a = *(const uint4*)(sptr + r * LDS + c * 16);
    const uint4 b = rv[i];
    uint4 o;
    o.x = pack_bf16(bf_lo(a.x) + bf_lo(b.x), bf_hi(a.x) + bf_hi(b.x));
    o.y = pack_bf16(bf_lo(a.y) + bf_lo(b.y), bf_hi(a.y) + bf_hi(b.y));
    o.z = pack_bf16(bf_lo(a.z) + bf_lo(b.z), bf_hi(a.z) + bf_hi(b.z));
    o.w = pack_bf16(bf_lo(a.w) + bf_lo(b.w), bf_hi(a.w) + bf_hi(b.w));
    st_g16(out + (size_t)(m0 + r) * DM + n0 + c * 8, o);
    if constexpr (STATS) *(uint4*)(sptr + r * LDS + c * 16) = o;
  }
  TS_MID(STATS ? 3 : 5, 3);
  if constexpr (STATS) {
    named_bar(1, 256);
    const int r = tid >> 1, hf = tid & 1;
    float f[40];
#pragma unroll
    for (int i = 0; i < 5; i++) {
      const uint4 v = *(const uint4*)(sptr + r * LDS + hf * 80 + i * 16);
      f[8 * i] = bf_lo(v.x); f[8 * i + 1] = bf_hi(v.x); f[8 * i + 2] = bf_lo(v.y); f[8 * i + 3] = bf_hi(v.y);
      f[8 * i + 4] = bf_lo(v.z); f[8 * i + 5] = bf_hi(v.z); f[8 * i + 6] = bf_lo(v.w); f[8 * i + 7] = bf_hi(v.w);
    }
    float s = 0.f;
#pragma unroll
    for (int i = 0; i < 40; i++) s += f[i];
    s += __shfl_xor_sync(~0u, s, 1);
    const float mu = s * (1.0f / 80.f);
    float q = 0.f;
#pragma unroll
    for (int i = 0; i < 40; i++) { const float d = f[i] - mu; q += d * d; }
    q += __shfl_xor_sync(~0u, q, 1);
    if (hf == 0) g_part2[(m0 + r) * 8 + blockIdx.x] = make_float2(s, q);
  }
  TS_END(STATS ? 3 : 5);
}

#define POLY_NUM 5
__device__ __forceinline__ float ex2_poly(float x, int shl23) {
  const float MAGIC = 12582912.f;
  const float tt = x + MAGIC;
  const float f = x - (tt - MAGIC);
  float p = fmaf(0.0013276472454890609f, f, 0.009675540961325169f);
  p = fmaf(p, f, 0.05550713092088699f);
  p = fmaf(p, f, 0.24022120237350464f);
  p = fmaf(p, f, 0.6931469440460205f);
  p = fmaf(p, f, 1.0000001192092896f);
  return __int_as_float(__float_as_int(tt) * shl23 + __float_as_int(p));
}
constexpr int KV_BYTES = S_LEN * 48;
constexpr int ATT_SMEM = 2 * KV_BYTES + 256 + 32768;
constexpr int ATT_BODY = 8;

__global__ void __launch_bounds__(512, 1) attn_kernel(int shl23, const __nv_bfloat16* __restrict__ wg_, const __nv_bfloat16* __restrict__ wu_,
                                                      const __nv_bfloat16* __restrict__ wo_, const __nv_bfloat16* __restrict__ wd_) {
  extern __shared__ __align__(1024) uint8_t smem[];
  if (blockIdx.x >= 128) {
    pdl_launch();
    const int e = blockIdx.x - 128, half = threadIdx.x >> 8;
    if (threadIdx.x == 0) {
      for (int i = 0; i < 13; i++) asm volatile("cp.async.bulk.prefetch.L2.global [%0], %1;" :: "l"((const uint8_t*)wo_ + (e * 13 + i) * 16384 * 0 + (size_t)(e * 13 + i >= 50 ? 0 : (e * 13 + i)) * 16384), "r"(16384));
      for (int i = 0; i < 30; i++) asm volatile("cp.async.bulk.prefetch.L2.global [%0], %1;" :: "l"((const uint8_t*)wd_ + (size_t)(e * 30 + i) * 16384), "r"(16384));
    }
    float (*red)[65] = (float (*)[65])(smem + half * 16384);
    for (int b = e * 12 + half; b < e * 12 + 12; b += 2) {
      if (b < 24) colsum64(wg_, DFF, b * 64, g_cs_g, red, threadIdx.x & 255, 1 + half);
      else colsum64(wu_, DFF, (b - 24) * 64, g_cs_u, red, threadIdx.x & 255, 1 + half);
    }
    return;
  }
  const int h = blockIdx.x >> 2, qb = blockIdx.x & 3;
  const uint32_t sK = smem_u32(smem), sV = sK + KV_BYTES, sBar = sV + KV_BYTES;
  const int tid = threadIdx.x;
  TS_BEGIN(2);
  if (tid == 0) {
    for (int i = 0; i < 8; i++) mbar_init(sBar + 8 * i, 1);
    asm volatile("fence.mbarrier_init.release.cluster;" ::: "memory");
  }
  pdl_launch();
  pdl_wait();
  if (tid == 0) {
    const uint8_t* gk = (const uint8_t*)(g_k + (size_t)h * S_LEN * 24);
    const uint8_t* gv = (const uint8_t*)(g_v + (size_t)h * S_LEN * 24);
    for (int i = 0; i < 8; i++) {
      mbar_expect_tx(sBar + 8 * i, 2 * 12288);
      bulk_g2s(sK + i * 12288, gk + i * 12288, 12288, sBar + 8 * i);
      bulk_g2s(sV + i * 12288, gv + i * 12288, 12288, sBar + 8 * i);
    }
  }
  float ka = 0.f, kb = 0.f;
#pragma unroll
  for (int i = 0; i < 8; i++) {
    const float2 v = *(const float2*)&g_kn[(i * NH + h) * 2];
    ka = (v.x > ka || v.x != v.x) ? v.x : ka;
    kb = (v.y > kb || v.y != v.y) ? v.y : kb;
  }
  bool fast;
  {
    const float kn = sqrtf(ka + kb);
    const int wg = tid >> 7, warp = (tid >> 5) & 3, lane = tid & 31, g = lane >> 2, t = lane & 3;
    uint32_t qa[2][6];
    float m[2][2];
    bool unsafe = false;
#pragma unroll
    for (int it = 0; it < 2; it++) {
      const int q0 = qb * 512 + (it * 4 + wg) * 64 + warp * 16;
      const uint32_t* qr0 = (const uint32_t*)(g_q + (size_t)(q0 + g) * DM + h * DH);
      const uint32_t* qr1 = qr0 + 8 * DM / 2;
      qa[it][0] = qr0[t]; qa[it][1] = qr1[t]; qa[it][2] = qr0[t + 4]; qa[it][3] = qr1[t + 4];
      qa[it][4] = (t < 2) ? qr0[t + 8] : 0u; qa[it][5] = (t < 2) ? qr1[t + 8] : 0u;
    }
#pragma unroll
    for (int it = 0; it < 2; it++) {
      auto sq = [](uint32_t u) { const float a = bf_lo(u), b = bf_hi(u); return a * a + b * b; };
      float n0 = sq(qa[it][0]) + sq(qa[it][2]) + sq(qa[it][4]);
      float n1 = sq(qa[it][1]) + sq(qa[it][3]) + sq(qa[it][5]);
      n0 += __shfl_xor_sync(~0u, n0, 1); n0 += __shfl_xor_sync(~0u, n0, 2);
      n1 += __shfl_xor_sync(~0u, n1, 1); n1 += __shfl_xor_sync(~0u, n1, 2);
      m[it][0] = ceilf(sqrtf(n0) * kn * 1.001f) + 1.f; m[it][1] = ceilf(sqrtf(n1) * kn * 1.001f) + 1.f;
      unsafe |= !(m[it][0] <= 62.f && m[it][1] <= 62.f);
    }
    fast = __syncthreads_or(unsafe) == 0;
#pragma unroll
    for (int it = 0; it < 2; it++) {
      if (fast && t == 2) { qa[it][4] = pack_bf16(-m[it][0], 0.f); qa[it][5] = pack_bf16(-m[it][1], 0.f); }
      uint8_t* qs = smem + 2 * KV_BYTES + 256 + (it * 4 + wg) * 4096 + warp * 1024 + g * 16 + t * 4;
      *(uint32_t*)(qs) = qa[it][0]; *(uint32_t*)(qs + 512) = qa[it][1]; *(uint32_t*)(qs + 128) = qa[it][2]; *(uint32_t*)(qs + 512 + 128) = qa[it][3];
      *(uint32_t*)(qs + 256) = qa[it][4]; *(uint32_t*)(qs + 512 + 256) = qa[it][5]; *(uint32_t*)(qs + 384) = 0u; *(uint32_t*)(qs + 512 + 384) = 0u;
    }
    asm volatile("fence.proxy.async.shared::cta;" ::: "memory");
    __syncthreads();
  }
  auto write_out = [&](float (&O)[12], int it) {
    uint32_t tid2;
    asm volatile("mov.u32 %0, %%tid.x;" : "=r"(tid2));
    const int lane2 = tid2 & 31, t2 = lane2 & 3;
    const int qq = (blockIdx.x & 3) * 512 + (it * 4 + (tid2 >> 7)) * 64 + ((tid2 >> 5) & 3) * 16 + (lane2 >> 2);
    const float l0 = __shfl_sync(~0u, O[8], (lane2 & ~3) | 2), l1 = __shfl_sync(~0u, O[10], (lane2 & ~3) | 2);
    const float r0 = 1.f / l0, r1 = 1.f / l1;
    uint32_t* o0 = (uint32_t*)(g_o + (size_t)qq * DM + (blockIdx.x >> 2) * DH);
    uint32_t* o1 = o0 + 8 * DM / 2;
    o0[t2] = pack_bf16(O[0] * r0, O[1] * r0); o1[t2] = pack_bf16(O[2] * r1, O[3] * r1);
    o0[t2 + 4] = pack_bf16(O[4] * r0, O[5] * r0); o1[t2 + 4] = pack_bf16(O[6] * r1, O[7] * r1);
    if (t2 < 2) { o0[t2 + 8] = pack_bf16(O[8] * r0, O[9] * r0); o1[t2 + 8] = pack_bf16(O[10] * r1, O[11] * r1); }
  };
  if (fast) {
#pragma unroll 1
    for (int it = 0; it < 2; it++) {
      const uint64_t dq = make_desc(sBar + 256 + (it * 4 + (tid >> 7)) * 4096, 128, 512, 0);
      float O[12];
#pragma unroll
      for (int i = 0; i < 12; i++) { O[i] = 0.f; asm volatile("" : "+f"(O[i]) :: "memory"); }
      float S[2][32];
      uint32_t P[16];
#pragma unroll 1
      for (int jb = 0; jb < 32 / ATT_BODY; jb++) {
        if (it == 0) { for (int c = 0; c < ATT_BODY / 4; c++) mbar_wait(sBar + 8 * (jb * (ATT_BODY / 4) + c), 0); }
        const uint64_t dk0 = make_desc(sK + jb * ATT_BODY * 8 * 384, 128, 384, 0);
        const uint64_t dv0 = make_desc(sV + jb * ATT_BODY * 8 * 384, 384, 128, 0);
        wgmma_fence();
        wgmma_ss_n64_k(S[0], dq, dk0, 0);
        wgmma_ss_n64_k(S[0], dq + (256 >> 4), dk0 + (256 >> 4), 1);
        wgmma_commit();
#pragma unroll
        for (int u = 0; u < ATT_BODY; u++) {
          if (u + 1 < ATT_BODY) {
            const uint64_t dk = dk0 + (((u + 1) * 8 * 384) >> 4);
            wgmma_fence();
            wgmma_ss_n64_k(S[(u + 1) & 1], dq, dk, 0);
            wgmma_ss_n64_k(S[(u + 1) & 1], dq + (256 >> 4), dk + (256 >> 4), 1);
            wgmma_commit();
          }
          if (u == 0 || u == ATT_BODY - 1) wgmma_wait<1>(); else wgmma_wait<2>();
#pragma unroll
          for (int i = 0; i < 32; i++) asm volatile("" : "+f"(S[u & 1][i]) :: "memory");
          const uint64_t dv = dv0 + ((u * 8 * 384) >> 4);
#pragma unroll
          for (int hf = 0; hf < 2; hf++) {
            if (hf == 1 && u > 0) { if (u == ATT_BODY - 1) wgmma_wait<1>(); else wgmma_wait<2>(); }
#pragma unroll
            for (int i = hf * 8; i < hf * 8 + 8; i++) {
              const bool usepoly = ((i + 1) * POLY_NUM / 16) != (i * POLY_NUM / 16);
              float a, b;
              if (usepoly) { a = ex2_poly(S[u & 1][2 * i], shl23); b = ex2_poly(S[u & 1][2 * i + 1], shl23); }
              else { a = ex2_mufu(S[u & 1][2 * i]); b = ex2_mufu(S[u & 1][2 * i + 1]); }
              P[i] = pack_bf16(a, b);
            }
            wgmma_fence();
#pragma unroll
            for (int ks = hf * 2; ks < hf * 2 + 2; ks++)
              wgmma_rs_n24_tb(O, P[4 * ks], P[4 * ks + 1], P[4 * ks + 2], P[4 * ks + 3], dv + ((ks * 768) >> 4), 1);
            wgmma_commit();
          }
        }
        wgmma_wait<0>();
      }
#pragma unroll
      for (int i = 0; i < 12; i++) asm volatile("" : "+f"(O[i]) :: "memory");
      write_out(O, it);
    }
  } else {
#pragma unroll 1
    for (int it = 0; it < 2; it++) {
      const uint64_t dq = make_desc(sBar + 256 + (it * 4 + (tid >> 7)) * 4096, 128, 512, 0);
      float O[12];
#pragma unroll
      for (int i = 0; i < 12; i++) { O[i] = 0.f; asm volatile("" : "+f"(O[i]) :: "memory"); }
      float S[32];
      float mx0 = -INFINITY, mx1 = -INFINITY;
#pragma unroll 1
      for (int j = 0; j < 32; j++) {
        if (it == 0 && (j & 3) == 0) mbar_wait(sBar + 8 * (j >> 2), 0);
        const uint64_t dk = make_desc(sK + j * 8 * 384, 128, 384, 0);
        wgmma_fence();
        wgmma_ss_n64_k(S, dq, dk, 0);
        wgmma_ss_n64_k(S, dq + (256 >> 4), dk + (256 >> 4), 1);
        wgmma_commit();
        wgmma_wait<0>();
#pragma unroll
        for (int i = 0; i < 8; i++) {
          mx0 = fmaxf(mx0, fmaxf(S[4 * i], S[4 * i + 1]));
          mx1 = fmaxf(mx1, fmaxf(S[4 * i + 2], S[4 * i + 3]));
        }
      }
      mx0 = fmaxf(mx0, __shfl_xor_sync(~0u, mx0, 1)); mx0 = fmaxf(mx0, __shfl_xor_sync(~0u, mx0, 2));
      mx1 = fmaxf(mx1, __shfl_xor_sync(~0u, mx1, 1)); mx1 = fmaxf(mx1, __shfl_xor_sync(~0u, mx1, 2));
#pragma unroll 1
      for (int j = 0; j < 32; j++) {
        const uint64_t dk = make_desc(sK + j * 8 * 384, 128, 384, 0);
        wgmma_fence();
        wgmma_ss_n64_k(S, dq, dk, 0);
        wgmma_ss_n64_k(S, dq + (256 >> 4), dk + (256 >> 4), 1);
        wgmma_commit();
        wgmma_wait<0>();
        uint32_t P[16];
#pragma unroll
        for (int i = 0; i < 8; i++) {
          P[2 * i] = pack_bf16(ex2_mufu(S[4 * i] - mx0), ex2_mufu(S[4 * i + 1] - mx0));
          P[2 * i + 1] = pack_bf16(ex2_mufu(S[4 * i + 2] - mx1), ex2_mufu(S[4 * i + 3] - mx1));
        }
        wgmma_fence();
        const uint64_t dv = make_desc(sV + j * 8 * 384, 384, 128, 0);
#pragma unroll
        for (int ks = 0; ks < 4; ks++)
          wgmma_rs_n24_tb(O, P[4 * ks], P[4 * ks + 1], P[4 * ks + 2], P[4 * ks + 3], dv + ((ks * 768) >> 4), 1);
        wgmma_commit();
        wgmma_wait<0>();
      }
#pragma unroll
      for (int i = 0; i < 12; i++) asm volatile("" : "+f"(O[i]) :: "memory");
      write_out(O, it);
    }
  }
  TS_END(2);
}

typedef CUresult (*EncodeFn)(CUtensorMap*, CUtensorMapDataType, cuuint32_t, void*, const cuuint64_t*, const cuuint64_t*, const cuuint32_t*,
                             const cuuint32_t*, CUtensorMapInterleave, CUtensorMapSwizzle, CUtensorMapL2promotion, CUtensorMapFloatOOBfill);
static EncodeFn get_encode() {
  static EncodeFn fn = nullptr;
  if (!fn) {
    void* p = nullptr; cudaDriverEntryPointQueryResult st;
    cudaGetDriverEntryPoint("cuTensorMapEncodeTiled", &p, cudaEnableDefault, &st);
    fn = (EncodeFn)p;
  }
  return fn;
}
static CUtensorMap make_map(const void* ptr, int rows, int cols, int box_rows, int box_cols = 64) {
  CUtensorMap m;
  cuuint64_t dims[2] = {(cuuint64_t)cols, (cuuint64_t)rows};
  cuuint64_t strides[1] = {(cuuint64_t)cols * 2};
  cuuint32_t box[2] = {(cuuint32_t)box_cols, (cuuint32_t)box_rows};
  cuuint32_t es[2] = {1, 1};
  get_encode()(&m, CU_TENSOR_MAP_DATA_TYPE_BFLOAT16, 2, const_cast<void*>(ptr), dims, strides, box, es, CU_TENSOR_MAP_INTERLEAVE_NONE,
               box_cols == 64 ? CU_TENSOR_MAP_SWIZZLE_128B : (box_cols == 32 ? CU_TENSOR_MAP_SWIZZLE_64B : CU_TENSOR_MAP_SWIZZLE_32B), CU_TENSOR_MAP_L2_PROMOTION_L2_128B, CU_TENSOR_MAP_FLOAT_OOB_FILL_NONE);
  return m;
}
static CUtensorMap make_map_w(const void* ptr, int rows, int cols, int bc, int nblk) {
  CUtensorMap m;
  cuuint64_t dims[3] = {(cuuint64_t)bc, (cuuint64_t)rows, (cuuint64_t)(cols / bc)};
  cuuint64_t strides[2] = {(cuuint64_t)cols * 2, (cuuint64_t)bc * 2};
  cuuint32_t box[3] = {(cuuint32_t)bc, 64, (cuuint32_t)nblk};
  cuuint32_t es[3] = {1, 1, 1};
  get_encode()(&m, CU_TENSOR_MAP_DATA_TYPE_BFLOAT16, 3, const_cast<void*>(ptr), dims, strides, box, es, CU_TENSOR_MAP_INTERLEAVE_NONE,
               bc == 64 ? CU_TENSOR_MAP_SWIZZLE_128B : (bc == 32 ? CU_TENSOR_MAP_SWIZZLE_64B : CU_TENSOR_MAP_SWIZZLE_32B),
               CU_TENSOR_MAP_L2_PROMOTION_L2_128B, CU_TENSOR_MAP_FLOAT_OOB_FILL_NONE);
  return m;
}
template <typename... KArgs, typename... Args>
static void launch(void (*kern)(KArgs...), dim3 grid, dim3 block, size_t smem, bool pdl, dim3 cluster, Args... args) {
  cudaLaunchConfig_t cfg = {};
  cfg.gridDim = grid; cfg.blockDim = block; cfg.dynamicSmemBytes = smem; cfg.stream = cudaStreamPerThread;
  cudaLaunchAttribute at[2];
  int na = 0;
  if (pdl) { at[na].id = cudaLaunchAttributeProgrammaticStreamSerialization; at[na].val.programmaticStreamSerializationAllowed = 1; na++; }
  if (cluster.x * cluster.y > 1) { at[na].id = cudaLaunchAttributeClusterDimension; at[na].val.clusterDim.x = cluster.x; at[na].val.clusterDim.y = cluster.y; at[na].val.clusterDim.z = 1; na++; }
  cfg.attrs = at; cfg.numAttrs = na;
  cudaLaunchKernelEx(&cfg, kern, KArgs(args)...);
}

extern "C" void kernel_launch(void* const* d_in, const int* in_sizes, int n_in, void* d_out, int out_size) {
  const __nv_bfloat16* x = (const __nv_bfloat16*)d_in[0];
  const __nv_bfloat16* wqkv = (const __nv_bfloat16*)d_in[1];
  const __nv_bfloat16* wo = (const __nv_bfloat16*)d_in[2];
  const __nv_bfloat16* wgate = (const __nv_bfloat16*)d_in[4];
  const __nv_bfloat16* wup = (const __nv_bfloat16*)d_in[5];
  const __nv_bfloat16* wdown = (const __nv_bfloat16*)d_in[6];
  __nv_bfloat16* out = (__nv_bfloat16*)d_out;
  void *p_o, *p_h, *p_act;
  cudaGetSymbolAddress(&p_o, g_o); cudaGetSymbolAddress(&p_h, g_h); cudaGetSymbolAddress(&p_act, g_act);

#define A_CN 1
#define A_CM 1
#define D_CN 1
#define D_CM 1
  auto kA = gemm_kernel<256, 128, 1, DM, 4, EPI_QKV, 1, A_CN, A_CM>;
  auto kC = gemm_res_kernel<DM, true>;
  auto kD = gemm_kernel<128, 192, 2, DM, 3, EPI_GLU, 1, D_CN, D_CM>;
  auto kE = gemm_res_kernel<DFF, false>;
  constexpr int smA = GemmCfg<256, 128, 1, 4>::SMEM, smC = R_SMEM, smD = GemmCfg<128, 192, 2, 3>::SMEM;
  cudaFuncSetAttribute(kA, cudaFuncAttributeMaxDynamicSharedMemorySize, smA);
  cudaFuncSetAttribute(kC, cudaFuncAttributeMaxDynamicSharedMemorySize, smC);
  cudaFuncSetAttribute(kD, cudaFuncAttributeMaxDynamicSharedMemorySize, smD);
  cudaFuncSetAttribute(kE, cudaFuncAttributeMaxDynamicSharedMemorySize, smC);
  cudaFuncSetAttribute(attn_kernel, cudaFuncAttributeMaxDynamicSharedMemorySize, ATT_SMEM);

  const CUtensorMap tm_x = make_map(x, S_LEN, DM, 256), tm_wqkv = make_map_w(wqkv, DM, 3 * DM, 64, 2);
  const CUtensorMap tm_o = make_map(p_o, S_LEN, DM, 128), tm_wo = make_map_w(wo, DM, DM, 16, 5);
  const CUtensorMap tm_h = make_map(p_h, S_LEN, DM, 128), tm_wg = make_map_w(wgate, DM, DFF, 64, 3), tm_wu = make_map_w(wup, DM, DFF, 64, 3);
  const CUtensorMap tm_act = make_map(p_act, S_LEN, DFF, 128), tm_wd = make_map_w(wdown, DFF, DM, 16, 5);

  launch(pre_kernel, dim3(12), dim3(1024), 0, false, dim3(1, 1), x, wqkv);
  launch(kA, dim3(15, 8), dim3(288), smA, true, dim3(A_CN, A_CM), tm_x, tm_wqkv, tm_wqkv, x, (__nv_bfloat16*)wqkv);
  launch(attn_kernel, dim3(132), dim3(512), ATT_SMEM, true, dim3(1, 1), 0x800000, wgate, wup, wo, wdown);
  launch(kC, dim3(8, 16), dim3(288), smC, true, dim3(1, 1), tm_o, tm_wo, x, (__nv_bfloat16*)p_h);
  launch(kD, dim3(8, 16), dim3(384), smD, true, dim3(D_CN, D_CM), tm_h, tm_wg, tm_wu, (const __nv_bfloat16*)nullptr, (__nv_bfloat16*)p_act);
  launch(kE, dim3(8, 16), dim3(288), smC, true, dim3(1, 1), tm_act, tm_wd, (const __nv_bfloat16*)p_h, out);
}
```

```cpp
#include <cuda_runtime.h>
#include <cuda_bf16.h>
#include <cuda.h>
#include <stdint.h>

constexpr int S_LEN = 2048, DM = 640, NH = 32, DH = 20, DFF = 1536;

__device__ __align__(1024) __nv_bfloat16 g_q[NH * S_LEN * 32];
__device__ __align__(1024) __nv_bfloat16 g_k[NH * S_LEN * 24];
__device__ __align__(1024) __nv_bfloat16 g_v[NH * S_LEN * 24];
__device__ __align__(1024) __nv_bfloat16 g_o[S_LEN * DM];
__device__ __align__(1024) __nv_bfloat16 g_h[S_LEN * DM];
__device__ __align__(1024) __nv_bfloat16 g_act[S_LEN * DFF];
__device__ float g_kn[8 * NH * 2];
__device__ float2 g_stat1[S_LEN];
__device__ float g_cs_qkv[3 * DM];
__device__ float g_cs_g[DFF];
__device__ float g_cs_u[DFF];
__device__ float2 g_part2[S_LEN * 10];

#define TS_BEGIN(k)
#define TS_END(k)
#define TS_MID(k, i)
__device__ __forceinline__ uint32_t smem_u32(const void* p) { return (uint32_t)__cvta_generic_to_shared(p); }
__device__ __forceinline__ void mbar_init(uint32_t bar, uint32_t cnt) { asm volatile("mbarrier.init.shared::cta.b64 [%0], %1;" :: "r"(bar), "r"(cnt)); }
__device__ __forceinline__ void mbar_expect_tx(uint32_t bar, uint32_t bytes) { asm volatile("mbarrier.arrive.expect_tx.shared::cta.b64 _, [%0], %1;" :: "r"(bar), "r"(bytes) : "memory"); }
__device__ __forceinline__ void mbar_arrive(uint32_t bar) { asm volatile("mbarrier.arrive.shared::cta.b64 _, [%0];" :: "r"(bar) : "memory"); }
__device__ __forceinline__ void mbar_wait(uint32_t bar, uint32_t parity) {
  uint32_t done;
  uint32_t spins = 0;
  do {
    asm volatile("{\n.reg .pred P1;\nmbarrier.try_wait.parity.shared::cta.b64 P1, [%1], %2;\nselp.u32 %0, 1, 0, P1;\n}" : "=r"(done) : "r"(bar), "r"(parity) : "memory");
  } while (!done && ++spins < (1u << 24));
}
__device__ __forceinline__ void bulk_g2s(uint32_t dst, const void* src, uint32_t bytes, uint32_t bar) {
  asm volatile("cp.async.bulk.shared::cluster.global.mbarrier::complete_tx::bytes [%0], [%1], %2, [%3];" :: "r"(dst), "l"(src), "r"(bytes), "r"(bar) : "memory");
}
__device__ __forceinline__ void tma_2d(uint32_t dst, const CUtensorMap* tm, int c0, int c1, uint32_t bar) {
  asm volatile("cp.async.bulk.tensor.2d.shared::cluster.global.mbarrier::complete_tx::bytes [%0], [%1, {%3, %4}], [%2];"
               :: "r"(dst), "l"(tm), "r"(bar), "r"(c0), "r"(c1) : "memory");
}
__device__ __forceinline__ void tma_3d(uint32_t dst, const CUtensorMap* tm, int c0, int c1, int c2, uint32_t bar) {
  asm volatile("cp.async.bulk.tensor.3d.shared::cluster.global.mbarrier::complete_tx::bytes [%0], [%1, {%3, %4, %5}], [%2];"
               :: "r"(dst), "l"(tm), "r"(bar), "r"(c0), "r"(c1), "r"(c2) : "memory");
}
__device__ __forceinline__ void tma_2d_mc(uint32_t dst, const CUtensorMap* tm, int c0, int c1, uint32_t bar, uint16_t mask) {
  asm volatile("cp.async.bulk.tensor.2d.shared::cluster.global.mbarrier::complete_tx::bytes.multicast::cluster [%0], [%1, {%3, %4}], [%2], %5;"
               :: "r"(dst), "l"(tm), "r"(bar), "r"(c0), "r"(c1), "h"(mask) : "memory");
}
__device__ __forceinline__ void mbar_arrive_remote(uint32_t bar, uint32_t rank) {
  asm volatile("{\n.reg .b32 ra;\nmapa.shared::cluster.u32 ra, %0, %1;\nmbarrier.arrive.release.cluster.shared::cluster.b64 _, [ra];\n}" :: "r"(bar), "r"(rank) : "memory");
}
__device__ __forceinline__ void cluster_arrive() { asm volatile("barrier.cluster.arrive.release.aligned;" ::: "memory"); }
__device__ __forceinline__ void cluster_wait() { asm volatile("barrier.cluster.wait.acquire.aligned;" ::: "memory"); }
__device__ __forceinline__ void wgmma_fence() { asm volatile("wgmma.fence.sync.aligned;" ::: "memory"); }
__device__ __forceinline__ void wgmma_commit() { asm volatile("wgmma.commit_group.sync.aligned;" ::: "memory"); }
template <int N> __device__ __forceinline__ void wgmma_wait() { asm volatile("wgmma.wait_group.sync.aligned %0;" :: "n"(N) : "memory"); }
__device__ __forceinline__ void pdl_wait() { asm volatile("griddepcontrol.wait;" ::: "memory"); }
__device__ __forceinline__ void pdl_launch() { asm volatile("griddepcontrol.launch_dependents;" ::: "memory"); }
__device__ __forceinline__ void named_bar(int id, int n) { asm volatile("bar.sync %0, %1;" :: "r"(id), "r"(n) : "memory"); }
__device__ __forceinline__ uint64_t make_desc(uint32_t addr, uint32_t lbo, uint32_t sbo, uint32_t swz) {
  return (uint64_t)((addr & 0x3FFFF) >> 4) | ((uint64_t)(lbo >> 4) << 16) | ((uint64_t)(sbo >> 4) << 32) | ((uint64_t)swz << 62);
}
__device__ __forceinline__ void st_g16(void* p, uint4 v) { asm volatile("st.global.v4.b32 [%0], {%1, %2, %3, %4};" :: "l"(p), "r"(v.x), "r"(v.y), "r"(v.z), "r"(v.w) : "memory"); }
__device__ __forceinline__ void st_g8(void* p, uint2 v) { asm volatile("st.global.v2.b32 [%0], {%1, %2};" :: "l"(p), "r"(v.x), "r"(v.y) : "memory"); }
__device__ __forceinline__ uint4 ld_g16(const void* p) { uint4 v; asm volatile("ld.global.v4.b32 {%0, %1, %2, %3}, [%4];" : "=r"(v.x), "=r"(v.y), "=r"(v.z), "=r"(v.w) : "l"(p) : "memory"); return v; }
__device__ __forceinline__ uint32_t pack_bf16(float lo, float hi) { uint32_t r; asm("cvt.rn.bf16x2.f32 %0, %1, %2;" : "=r"(r) : "f"(hi), "f"(lo)); return r; }
__device__ __forceinline__ float bf_lo(uint32_t u) { return __uint_as_float(u << 16); }
__device__ __forceinline__ float bf_hi(uint32_t u) { return __uint_as_float(u & 0xffff0000u); }
__device__ __forceinline__ float bf_round(float x) { return __bfloat162float(__float2bfloat16_rn(x)); }
__device__ __forceinline__ float ex2_mufu(float x) { float y; asm("ex2.approx.ftz.f32 %0, %1;" : "=f"(y) : "f"(x)); return y; }

__device__ __forceinline__ void wgmma_ss_n80(float (&d)[40], uint64_t da, uint64_t db, int scale_d) {
  asm volatile("{\n.reg .pred p;\nsetp.ne.b32 p, %42, 0;\n"
    "wgmma.mma_async.sync.aligned.m64n80k16.f32.bf16.bf16 {%0,%1,%2,%3,%4,%5,%6,%7,%8,%9,%10,%11,%12,%13,%14,%15,%16,%17,%18,%19,%20,%21,%22,%23,%24,%25,%26,%27,%28,%29,%30,%31,%32,%33,%34,%35,%36,%37,%38,%39}, %40, %41, p, 1, 1, 0, 1;\n}\n"
    : "+f"(d[0]),"+f"(d[1]),"+f"(d[2]),"+f"(d[3]),"+f"(d[4]),"+f"(d[5]),"+f"(d[6]),"+f"(d[7]),"+f"(d[8]),"+f"(d[9]),"+f"(d[10]),"+f"(d[11]),"+f"(d[12]),"+f"(d[13]),"+f"(d[14]),"+f"(d[15]),"+f"(d[16]),"+f"(d[17]),"+f"(d[18]),"+f"(d[19]),"+f"(d[20]),"+f"(d[21]),"+f"(d[22]),"+f"(d[23]),"+f"(d[24]),"+f"(d[25]),"+f"(d[26]),"+f"(d[27]),"+f"(d[28]),"+f"(d[29]),"+f"(d[30]),"+f"(d[31]),"+f"(d[32]),"+f"(d[33]),"+f"(d[34]),"+f"(d[35]),"+f"(d[36]),"+f"(d[37]),"+f"(d[38]),"+f"(d[39])
    : "l"(da), "l"(db), "r"(scale_d));
}
__device__ __forceinline__ void wgmma_ss_n128(float (&d)[64], uint64_t da, uint64_t db, int scale_d) {
  asm volatile("{\n.reg .pred p;\nsetp.ne.b32 p, %66, 0;\n"
    "wgmma.mma_async.sync.aligned.m64n128k16.f32.bf16.bf16 {%0,%1,%2,%3,%4,%5,%6,%7,%8,%9,%10,%11,%12,%13,%14,%15,%16,%17,%18,%19,%20,%21,%22,%23,%24,%25,%26,%27,%28,%29,%30,%31,%32,%33,%34,%35,%36,%37,%38,%39,%40,%41,%42,%43,%44,%45,%46,%47,%48,%49,%50,%51,%52,%53,%54,%55,%56,%57,%58,%59,%60,%61,%62,%63}, %64, %65, p, 1, 1, 0, 1;\n}\n"
    : "+f"(d[0]),"+f"(d[1]),"+f"(d[2]),"+f"(d[3]),"+f"(d[4]),"+f"(d[5]),"+f"(d[6]),"+f"(d[7]),"+f"(d[8]),"+f"(d[9]),"+f"(d[10]),"+f"(d[11]),"+f"(d[12]),"+f"(d[13]),"+f"(d[14]),"+f"(d[15]),"+f"(d[16]),"+f"(d[17]),"+f"(d[18]),"+f"(d[19]),"+f"(d[20]),"+f"(d[21]),"+f"(d[22]),"+f"(d[23]),"+f"(d[24]),"+f"(d[25]),"+f"(d[26]),"+f"(d[27]),"+f"(d[28]),"+f"(d[29]),"+f"(d[30]),"+f"(d[31]),"+f"(d[32]),"+f"(d[33]),"+f"(d[34]),"+f"(d[35]),"+f"(d[36]),"+f"(d[37]),"+f"(d[38]),"+f"(d[39]),"+f"(d[40]),"+f"(d[41]),"+f"(d[42]),"+f"(d[43]),"+f"(d[44]),"+f"(d[45]),"+f"(d[46]),"+f"(d[47]),"+f"(d[48]),"+f"(d[49]),"+f"(d[50]),"+f"(d[51]),"+f"(d[52]),"+f"(d[53]),"+f"(d[54]),"+f"(d[55]),"+f"(d[56]),"+f"(d[57]),"+f"(d[58]),"+f"(d[59]),"+f"(d[60]),"+f"(d[61]),"+f"(d[62]),"+f"(d[63])
    : "l"(da), "l"(db), "r"(scale_d));
}
__device__ __forceinline__ void wgmma_ss_n192(float (&d)[96], uint64_t da, uint64_t db, int scale_d) {
  asm volatile("{\n.reg .pred p;\nsetp.ne.b32 p, %98, 0;\n"
    "wgmma.mma_async.sync.aligned.m64n192k16.f32.bf16.bf16 {%0,%1,%2,%3,%4,%5,%6,%7,%8,%9,%10,%11,%12,%13,%14,%15,%16,%17,%18,%19,%20,%21,%22,%23,%24,%25,%26,%27,%28,%29,%30,%31,%32,%33,%34,%35,%36,%37,%38,%39,%40,%41,%42,%43,%44,%45,%46,%47,%48,%49,%50,%51,%52,%53,%54,%55,%56,%57,%58,%59,%60,%61,%62,%63,%64,%65,%66,%67,%68,%69,%70,%71,%72,%73,%74,%75,%76,%77,%78,%79,%80,%81,%82,%83,%84,%85,%86,%87,%88,%89,%90,%91,%92,%93,%94,%95}, %96, %97, p, 1, 1, 0, 1;\n}\n"
    : "+f"(d[0]),"+f"(d[1]),"+f"(d[2]),"+f"(d[3]),"+f"(d[4]),"+f"(d[5]),"+f"(d[6]),"+f"(d[7]),"+f"(d[8]),"+f"(d[9]),"+f"(d[10]),"+f"(d[11]),"+f"(d[12]),"+f"(d[13]),"+f"(d[14]),"+f"(d[15]),"+f"(d[16]),"+f"(d[17]),"+f"(d[18]),"+f"(d[19]),"+f"(d[20]),"+f"(d[21]),"+f"(d[22]),"+f"(d[23]),"+f"(d[24]),"+f"(d[25]),"+f"(d[26]),"+f"(d[27]),"+f"(d[28]),"+f"(d[29]),"+f"(d[30]),"+f"(d[31]),"+f"(d[32]),"+f"(d[33]),"+f"(d[34]),"+f"(d[35]),"+f"(d[36]),"+f"(d[37]),"+f"(d[38]),"+f"(d[39]),"+f"(d[40]),"+f"(d[41]),"+f"(d[42]),"+f"(d[43]),"+f"(d[44]),"+f"(d[45]),"+f"(d[46]),"+f"(d[47]),"+f"(d[48]),"+f"(d[49]),"+f"(d[50]),"+f"(d[51]),"+f"(d[52]),"+f"(d[53]),"+f"(d[54]),"+f"(d[55]),"+f"(d[56]),"+f"(d[57]),"+f"(d[58]),"+f"(d[59]),"+f"(d[60]),"+f"(d[61]),"+f"(d[62]),"+f"(d[63]),"+f"(d[64]),"+f"(d[65]),"+f"(d[66]),"+f"(d[67]),"+f"(d[68]),"+f"(d[69]),"+f"(d[70]),"+f"(d[71]),"+f"(d[72]),"+f"(d[73]),"+f"(d[74]),"+f"(d[75]),"+f"(d[76]),"+f"(d[77]),"+f"(d[78]),"+f"(d[79]),"+f"(d[80]),"+f"(d[81]),"+f"(d[82]),"+f"(d[83]),"+f"(d[84]),"+f"(d[85]),"+f"(d[86]),"+f"(d[87]),"+f"(d[88]),"+f"(d[89]),"+f"(d[90]),"+f"(d[91]),"+f"(d[92]),"+f"(d[93]),"+f"(d[94]),"+f"(d[95])
    : "l"(da), "l"(db), "r"(scale_d));
}
__device__ __forceinline__ void wgmma_ss_n64_k(float (&d)[32], uint64_t da, uint64_t db, int scale_d) {
  asm volatile("{\n.reg .pred p;\nsetp.ne.b32 p, %34, 0;\n"
    "wgmma.mma_async.sync.aligned.m64n64k16.f32.bf16.bf16 {%0,%1,%2,%3,%4,%5,%6,%7,%8,%9,%10,%11,%12,%13,%14,%15,%16,%17,%18,%19,%20,%21,%22,%23,%24,%25,%26,%27,%28,%29,%30,%31}, %32, %33, p, 1, 1, 0, 0;\n}\n"
    : "+f"(d[0]),"+f"(d[1]),"+f"(d[2]),"+f"(d[3]),"+f"(d[4]),"+f"(d[5]),"+f"(d[6]),"+f"(d[7]),"+f"(d[8]),"+f"(d[9]),"+f"(d[10]),"+f"(d[11]),"+f"(d[12]),"+f"(d[13]),"+f"(d[14]),"+f"(d[15]),"+f"(d[16]),"+f"(d[17]),"+f"(d[18]),"+f"(d[19]),"+f"(d[20]),"+f"(d[21]),"+f"(d[22]),"+f"(d[23]),"+f"(d[24]),"+f"(d[25]),"+f"(d[26]),"+f"(d[27]),"+f"(d[28]),"+f"(d[29]),"+f"(d[30]),"+f"(d[31])
    : "l"(da), "l"(db), "r"(scale_d));
}
__device__ __forceinline__ void wgmma_rs_n24_tb(float (&d)[12], uint32_t a0, uint32_t a1, uint32_t a2, uint32_t a3, uint64_t db, int scale_d) {
  asm volatile("{\n.reg .pred p;\nsetp.ne.b32 p, %17, 0;\n"
    "wgmma.mma_async.sync.aligned.m64n24k16.f32.bf16.bf16 {%0,%1,%2,%3,%4,%5,%6,%7,%8,%9,%10,%11}, {%12,%13,%14,%15}, %16, p, 1, 1, 1;\n}\n"
    : "+f"(d[0]),"+f"(d[1]),"+f"(d[2]),"+f"(d[3]),"+f"(d[4]),"+f"(d[5]),"+f"(d[6]),"+f"(d[7]),"+f"(d[8]),"+f"(d[9]),"+f"(d[10]),"+f"(d[11])
    : "r"(a0), "r"(a1), "r"(a2), "r"(a3), "l"(db), "r"(scale_d));
}

constexpr int PRE_ROW_BLOCKS = 64;
constexpr int PRE_COL_BLOCKS = 3 * DM / 64;
__device__ __forceinline__ float2 ln_finish(float mean, float var) {
  float mb = bf_round(mean);
  float s = bf_round(sqrtf(bf_round(bf_round(var) + 1e-5f)));
  return make_float2(mb, 1.0f / s);
}
__device__ __forceinline__ void colsum64(const __nv_bfloat16* __restrict__ w, int ld, int c0, float* __restrict__ dst, float (*red)[65], int tid, int bar_id) {
  const int cg = tid & 7, r0 = tid >> 3;
  float acc[8];
#pragma unroll
  for (int i = 0; i < 8; i++) acc[i] = 0.f;
#pragma unroll 10
  for (int r = r0; r < DM; r += 32) {
    uint4 v = __ldg((const uint4*)(w + (size_t)r * ld + c0 + cg * 8));
    acc[0] += bf_lo(v.x); acc[1] += bf_hi(v.x); acc[2] += bf_lo(v.y); acc[3] += bf_hi(v.y);
    acc[4] += bf_lo(v.z); acc[5] += bf_hi(v.z); acc[6] += bf_lo(v.w); acc[7] += bf_hi(v.w);
  }
#pragma unroll
  for (int i = 0; i < 8; i++) red[r0][cg * 8 + i] = acc[i];
  named_bar(bar_id, 256);
  if (tid < 64) {
    float s = 0.f;
#pragma unroll
    for (int r = 0; r < 32; r++) s += red[r][tid];
    dst[c0 + tid] = s;
  }
  named_bar(bar_id, 256);
}
__global__ void __launch_bounds__(1024) pre_kernel(const __nv_bfloat16* __restrict__ x, const __nv_bfloat16* __restrict__ wqkv) {
  TS_BEGIN(0);
  pdl_launch();
  __shared__ float red[51][161];
  const int tid = threadIdx.x, lane = tid & 31, warp = tid >> 5;
  {
    const int ch = tid % 20, rl = tid / 20;
    if (rl < 51) {
      const __nv_bfloat16* w = wqkv + blockIdx.x * 160 + ch * 8;
      uint4 v[13];
#pragma unroll
      for (int i = 0; i < 13; i++) { const int r = rl + i * 51; v[i] = r < DM ? __ldg((const uint4*)(w + (size_t)r * (3 * DM))) : make_uint4(0, 0, 0, 0); }
      float acc[8];
#pragma unroll
      for (int i = 0; i < 8; i++) acc[i] = 0.f;
#pragma unroll
      for (int i = 0; i < 13; i++) {
        acc[0] += bf_lo(v[i].x); acc[1] += bf_hi(v[i].x); acc[2] += bf_lo(v[i].y); acc[3] += bf_hi(v[i].y);
        acc[4] += bf_lo(v[i].z); acc[5] += bf_hi(v[i].z); acc[6] += bf_lo(v[i].w); acc[7] += bf_hi(v[i].w);
      }
#pragma unroll
      for (int i = 0; i < 8; i++) red[rl][ch * 8 + i] = acc[i];
    }
  }
  const int rbeg = blockIdx.x * 171, rend = min(rbeg + 171, S_LEN);
  for (int row0 = rbeg + warp * 2; row0 < rend; row0 += 64) {
    uint4 v[2][3];
#pragma unroll
    for (int k = 0; k < 2; k++) {
      const int row = min(row0 + k, rend - 1);
      const uint4* p = (const uint4*)(x + (size_t)row * DM);
      v[k][0] = __ldg(p + lane); v[k][1] = __ldg(p + 32 + lane);
      v[k][2] = lane < 16 ? __ldg(p + 64 + lane) : make_uint4(0, 0, 0, 0);
    }
#pragma unroll
    for (int k = 0; k < 2; k++) {
      float f[24];
      const uint32_t u[12] = {v[k][0].x, v[k][0].y, v[k][0].z, v[k][0].w, v[k][1].x, v[k][1].y, v[k][1].z, v[k][1].w, v[k][2].x, v[k][2].y, v[k][2].z, v[k][2].w};
#pragma unroll
      for (int j = 0; j < 12; j++) { f[2 * j] = bf_lo(u[j]); f[2 * j + 1] = bf_hi(u[j]); }
      float s = 0.f;
#pragma unroll
      for (int j = 0; j < 24; j++) s += f[j];
#pragma unroll
      for (int o = 16; o; o >>= 1) s += __shfl_xor_sync(~0u, s, o);
      const float mean = s * (1.0f / DM);
      float q = 0.f;
#pragma unroll
      for (int j = 0; j < 16; j++) { const float d = f[j] - mean; q += d * d; }
      if (lane < 16) {
#pragma unroll
        for (int j = 16; j < 24; j++) { const float d = f[j] - mean; q += d * d; }
      }
#pragma unroll
      for (int o = 16; o; o >>= 1) q += __shfl_xor_sync(~0u, q, o);
      if (lane == 0 && row0 + k < rend) g_stat1[row0 + k] = ln_finish(mean, q * (1.0f / DM));
    }
  }
  __syncthreads();
  if (tid < 160) {
    float s = 0.f;
#pragma unroll 17
    for (int r = 0; r < 51; r++) s += red[r][tid];
    g_cs_qkv[blockIdx.x * 160 + tid] = s;
  }
  TS_END(0);
}

enum { EPI_QKV = 0, EPI_WO = 1, EPI_GLU = 2, EPI_DOWN = 3 };
template <int N> struct WG;
template <> struct WG<128> { static __device__ __forceinline__ void mma(float (&d)[64], uint64_t a, uint64_t b, int s) { wgmma_ss_n128(d, a, b, s); } };
template <> struct WG<192> { static __device__ __forceinline__ void mma(float (&d)[96], uint64_t a, uint64_t b, int s) { wgmma_ss_n192(d, a, b, s); } };

template <int BM, int BN, int NB, int STAGES> struct GemmCfg {
  static constexpr int A_BYTES = BM * 128;
  static constexpr int B_BYTES = NB * (BN / 64) * 8192;
  static constexpr int STAGE_BYTES = A_BYTES + B_BYTES;
  static constexpr int SMEM = STAGES * STAGE_BYTES + 1024   + 256   + 4096  ;
};

constexpr float QSCALE = 0.22360679774997896f * 1.4426950408889634f;

template <int BM, int BN, int NB, int KDIM, int STAGES, int EPI, int MINB, int CN, int CM>
__global__ void __launch_bounds__(EPI == EPI_GLU ? 384 : 288, MINB) gemm_kernel(const __grid_constant__ CUtensorMap tmA, const __grid_constant__ CUtensorMap tmB0,
                                                         const __grid_constant__ CUtensorMap tmB1,
                                                         const __nv_bfloat16* resid, __nv_bfloat16* out) {
  using Cfg = GemmCfg<BM, BN, NB, STAGES>;
  constexpr int MB = BM / 128;
  constexpr int KT = KDIM / 64;
  extern __shared__ uint8_t smem_raw[];
  const uint32_t sbase = (smem_u32(smem_raw) + 1023u) & ~1023u;
  uint8_t* sptr = smem_raw + (sbase - smem_u32(smem_raw));
  const uint32_t sbar = sbase + STAGES * Cfg::STAGE_BYTES;
  const int tid = threadIdx.x, warp = tid >> 5, lane = tid & 31;
  const int n0 = blockIdx.x * BN, m0 = blockIdx.y * BM;
  TS_BEGIN(EPI == EPI_QKV ? 1 : EPI + 2);
  TS_MID(EPI == EPI_QKV ? 1 : EPI + 2, 3);
  constexpr int NCL = CN + CM - 1;
  const int cx = blockIdx.x % CN, cy = blockIdx.y % CM;
  if (tid == 0) {
    for (int i = 0; i < STAGES; i++) { mbar_init(sbar + 8 * i, 1); mbar_init(sbar + 8 * (STAGES + i), 2 * NCL); }
    asm volatile("fence.mbarrier_init.release.cluster;" ::: "memory");
  }
  __syncthreads();
  if constexpr (CN * CM > 1) { cluster_arrive(); cluster_wait(); }
  pdl_launch();
  if (warp >= 8) {
    if constexpr (EPI == EPI_GLU) asm volatile("setmaxnreg.dec.sync.aligned.u32 40;");
    if (warp == 8 && lane == 0) {
      auto load_a = [&](int kt, int s) { tma_2d(sbase + s * Cfg::STAGE_BYTES, &tmA, kt * 64, m0, sbar + 8 * s); };
      auto load_b = [&](int kt, int s) {
        const uint32_t sb = sbase + s * Cfg::STAGE_BYTES + Cfg::A_BYTES;
        tma_3d(sb, &tmB0, 0, kt * 64, blockIdx.x * (BN / 64), sbar + 8 * s);
        if constexpr (NB == 2) tma_3d(sb + (BN / 64) * 8192, &tmB1, 0, kt * 64, blockIdx.x * (BN / 64), sbar + 8 * s);
      };
      if constexpr (EPI == EPI_QKV) {
        const int cta = blockIdx.y * gridDim.x + blockIdx.x;
        const uint32_t xb = S_LEN * DM * 2, xs = 21888;
        if (cta * xs < xb) asm volatile("cp.async.bulk.prefetch.L2.global [%0], %1;" :: "l"((const uint8_t*)resid + (size_t)cta * xs), "r"(min(xs, xb - cta * xs)));
        asm volatile("cp.async.bulk.prefetch.L2.global [%0], %1;" :: "l"((const uint8_t*)out + (size_t)cta * 20480), "r"(20480));
      }
      for (int s = 0; s < STAGES; s++) { mbar_expect_tx(sbar + 8 * s, Cfg::STAGE_BYTES); if (EPI != EPI_QKV || s == 0) load_b(s, s); }
      if (EPI != EPI_QKV) pdl_wait();
      for (int s = 0; s < STAGES; s++) { load_a(s, s); if (EPI == EPI_QKV && s > 0) load_b(s, s); }
      for (int kt = STAGES; kt < KT; kt++) {
        const int s = kt % STAGES;
        mbar_wait(sbar + 8 * (STAGES + s), ((kt / STAGES) - 1) & 1);
        mbar_expect_tx(sbar + 8 * s, Cfg::STAGE_BYTES);
        load_a(kt, s);
        load_b(kt, s);
      }
    }
    if constexpr (EPI == EPI_GLU) {
      if (warp > 8) {
        float2* s_st = (float2*)(sptr + STAGES * Cfg::STAGE_BYTES + 256);
        float* s_cs = (float*)(sptr + STAGES * Cfg::STAGE_BYTES + 256 + 1024);
        pdl_wait();
        for (int r = tid - 288; r < BM; r += 96) {
          const float2* pp = &g_part2[(m0 + r) * 8];
          float s = 0.f;
#pragma unroll
          for (int i = 0; i < 8; i++) s += pp[i].x;
          const float mean = s * (1.0f / DM);
          float q = 0.f;
#pragma unroll
          for (int i = 0; i < 8; i++) { const float2 p = pp[i]; const float d = p.x * (1.0f / 80.f) - mean; q += p.y + 80.f * d * d; }
          s_st[r] = ln_finish(mean, q * (1.0f / DM));
        }
        for (int c = tid - 288; c < BN; c += 96) { s_cs[c] = g_cs_g[n0 + c]; s_cs[BN + c] = g_cs_u[n0 + c]; }
        __threadfence_block();
        asm volatile("bar.arrive 2, 352;" ::: "memory");
      }
    }
    if constexpr (CN * CM > 1) { __syncwarp(); cluster_arrive(); cluster_wait(); }
    return;
  }
  if constexpr (EPI == EPI_GLU) asm volatile("setmaxnreg.inc.sync.aligned.u32 232;");
  const int wg = warp >> 2, g = lane >> 2, t = lane & 3;
  float acc[MB][NB][BN / 2];
#pragma unroll
  for (int mb = 0; mb < MB; mb++)
#pragma unroll
    for (int nb = 0; nb < NB; nb++)
#pragma unroll
      for (int i = 0; i < BN / 2; i++) acc[mb][nb][i] = 0.f;
  for (int kt = 0; kt < KT; kt++) {
    const int s = kt % STAGES;
    mbar_wait(sbar + 8 * s, (kt / STAGES) & 1);
    if (kt == 0) TS_MID(EPI == EPI_QKV ? 1 : EPI + 2, 0);
    const uint32_t sa = sbase + s * Cfg::STAGE_BYTES + wg * (MB * 64 * 128);
    const uint32_t sb = sbase + s * Cfg::STAGE_BYTES + Cfg::A_BYTES;
    wgmma_fence();
#pragma unroll
    for (int ks = 0; ks < 4; ks++) {
#pragma unroll
      for (int mb = 0; mb < MB; mb++) {
        const uint64_t da = make_desc(sa + mb * 8192 + ks * 32, 16, 1024, 1);
#pragma unroll
        for (int nb = 0; nb < NB; nb++) {
          const uint64_t db = make_desc(sb + nb * (BN / 64) * 8192 + ks * 2048, 8192, 1024, 1);
          WG<BN>::mma(acc[mb][nb], da, db, 1);
        }
      }
    }
    wgmma_commit();
    wgmma_wait<1>();
    if (kt > 0 && kt - 1 + STAGES < KT && (tid & 127) < NCL) {
      const uint32_t eb = sbar + 8 * (STAGES + (kt - 1) % STAGES);
      if constexpr (CN * CM > 1) {
        const int i = tid & 127;
        const uint32_t rank = i < CN ? cy * CN + i : ((i - CN + (i - CN >= cy ? 1 : 0)) * CN + cx);
        mbar_arrive_remote(eb, rank);
      } else mbar_arrive(eb);
    }
  }
  wgmma_wait<0>();
#pragma unroll
  for (int mb = 0; mb < MB; mb++)
#pragma unroll
    for (int nb = 0; nb < NB; nb++)
#pragma unroll
      for (int i = 0; i < BN / 2; i++) asm volatile("" : "+f"(acc[mb][nb][i]) :: "memory");
  if constexpr (CN * CM > 1) cluster_arrive();
  TS_MID(EPI == EPI_QKV ? 1 : EPI + 2, 1);
  pdl_wait();
  TS_MID(EPI == EPI_QKV ? 1 : EPI + 2, 2);
  named_bar(1, 256);
  constexpr int LDS = BN * 2 + 16;
  const int ctid = tid;

  if constexpr (EPI == EPI_QKV) {
    const int sec = n0 / DM;
    constexpr int lds = 264;
    __shared__ unsigned int s_kn[8];
    if (ctid < 8) s_kn[ctid] = 0u;
    float2 cs[BN / 8];
#pragma unroll
    for (int j = 0; j < BN / 8; j++) cs[j] = *(const float2*)&g_cs_qkv[n0 + j * 8 + 2 * t];
#pragma unroll
    for (int mb = 0; mb < MB; mb++) {
      const int r0 = wg * (MB * 64) + mb * 64 + (warp & 3) * 16 + g;
      const float2 st0 = g_stat1[m0 + r0], st1 = g_stat1[m0 + r0 + 8];
      const float sc0 = sec == 0 ? st0.y * QSCALE : st0.y, sc1 = sec == 0 ? st1.y * QSCALE : st1.y;
#pragma unroll
      for (int j = 0; j < BN / 8; j++) {
        const float* a = &acc[mb][0][4 * j];
        *(uint32_t*)(sptr + r0 * lds + j * 16 + t * 4) = pack_bf16(fmaf(-st0.x, cs[j].x, a[0]) * sc0, fmaf(-st0.x, cs[j].y, a[1]) * sc0);
        *(uint32_t*)(sptr + (r0 + 8) * lds + j * 16 + t * 4) = pack_bf16(fmaf(-st1.x, cs[j].x, a[2]) * sc1, fmaf(-st1.x, cs[j].y, a[3]) * sc1);
      }
    }
    named_bar(1, 256);
    {
      const int cbase = n0 - sec * DM;
      const int hfirst = cbase / DH;
      const int j = m0 + ctid;
      uint8_t* dst = (uint8_t*)(sec == 0 ? g_q : (sec == 1 ? g_k : g_v)) + (size_t)(j >> 3) * (sec == 0 ? 512 : 384) + (j & 7) * 16;
      const uint8_t* row = sptr + ctid * 264;
#pragma unroll
      for (int i = 0; i < 8; i++) {
        const int hh = hfirst + i;
        const int cr = hh * DH - cbase;
        if (cr < BN) {
          uint2 v[5];
          bool in[5];
          float s = 0.f;
#pragma unroll
          for (int qd = 0; qd < 5; qd++) {
            const int c = cr + 4 * qd;
            in[qd] = c >= 0 && c < BN;
            v[qd] = in[qd] ? *(const uint2*)(row + c * 2) : make_uint2(0u, 0u);
            s += bf_lo(v[qd].x) * bf_lo(v[qd].x) + bf_hi(v[qd].x) * bf_hi(v[qd].x) + bf_lo(v[qd].y) * bf_lo(v[qd].y) + bf_hi(v[qd].y) * bf_hi(v[qd].y);
          }
          uint8_t* p = dst + (size_t)hh * (sec == 0 ? S_LEN * 64 : S_LEN * 48);
          if (in[0] && in[1]) st_g16(p, make_uint4(v[0].x, v[0].y, v[1].x, v[1].y));
          else if (in[0]) st_g8(p, v[0]);
          else if (in[1]) st_g8(p + 8, v[1]);
          if (in[2] && in[3]) st_g16(p + 128, make_uint4(v[2].x, v[2].y, v[3].x, v[3].y));
          else if (in[2]) st_g8(p + 128, v[2]);
          else if (in[3]) st_g8(p + 136, v[3]);
          if (in[4]) {
            st_g16(p + 256, make_uint4(v[4].x, v[4].y, sec == 0 ? 0u : 0x00003f80u, 0u));
            if (sec == 0) st_g16(p + 384, make_uint4(0u, 0u, 0u, 0u));
          }
          if (sec == 1) {
            const unsigned int mxb = __reduce_max_sync(~0u, __float_as_uint(s) & 0x7fffffffu);
            if (lane == 0) atomicMax(&s_kn[i], mxb);
          }
        }
      }
      if (sec == 1) {
        named_bar(1, 256);
        const int hh = hfirst + ctid;
        if (ctid < 8 && hh * DH < cbase + BN) {
          const bool starts_here = hh * DH >= cbase, ends_here = hh * DH + DH <= cbase + BN;
          const float v = __uint_as_float(s_kn[ctid]);
          float* o = &g_kn[(blockIdx.y * NH + hh) * 2];
          if (starts_here) { o[0] = v; if (ends_here) o[1] = 0.f; }
          else o[1] = v;
        }
      }
    }
  } else if constexpr (EPI == EPI_WO || EPI == EPI_DOWN) {
    const int r0 = wg * 64 + (warp & 3) * 16 + g;
#pragma unroll
    for (int j = 0; j < BN / 8; j++) {
      const float* a = &acc[0][0][4 * j];
      *(uint32_t*)(sptr + r0 * LDS + j * 16 + t * 4) = pack_bf16(a[0], a[1]);
      *(uint32_t*)(sptr + (r0 + 8) * LDS + j * 16 + t * 4) = pack_bf16(a[2], a[3]);
    }
    named_bar(1, 256);
#pragma unroll
    for (int i = 0; i < BM * (BN / 8) / 256; i++) {
      const int idx = i * 256 + ctid, r = idx / (BN / 8), c = idx % (BN / 8);
      const uint4 a = *(const uint4*)(sptr + r * LDS + c * 16);
      const size_t go = (size_t)(m0 + r) * DM + n0 + c * 8;
      const uint4 b = ld_g16(resid + go);
      uint4 o;
      o.x = pack_bf16(bf_lo(a.x) + bf_lo(b.x), bf_hi(a.x) + bf_hi(b.x));
      o.y = pack_bf16(bf_lo(a.y) + bf_lo(b.y), bf_hi(a.y) + bf_hi(b.y));
      o.z = pack_bf16(bf_lo(a.z) + bf_lo(b.z), bf_hi(a.z) + bf_hi(b.z));
      o.w = pack_bf16(bf_lo(a.w) + bf_lo(b.w), bf_hi(a.w) + bf_hi(b.w));
      st_g16(out + go, o);
      if constexpr (EPI == EPI_WO) {
        static_assert(BN == 64, "stats assume 8 lanes per row");
        const float f[8] = {bf_lo(o.x), bf_hi(o.x), bf_lo(o.y), bf_hi(o.y), bf_lo(o.z), bf_hi(o.z), bf_lo(o.w), bf_hi(o.w)};
        float s = 0.f;
#pragma unroll
        for (int k = 0; k < 8; k++) s += f[k];
        s += __shfl_xor_sync(~0u, s, 1); s += __shfl_xor_sync(~0u, s, 2); s += __shfl_xor_sync(~0u, s, 4);
        const float mu = s * (1.0f / 64.f);
        float q = 0.f;
#pragma unroll
        for (int k = 0; k < 8; k++) { const float d = f[k] - mu; q += d * d; }
        q += __shfl_xor_sync(~0u, q, 1); q += __shfl_xor_sync(~0u, q, 2); q += __shfl_xor_sync(~0u, q, 4);
        if (c == 0) g_part2[(m0 + r) * 10 + blockIdx.x] = make_float2(s, q);
      }
    }
  } else {
    const int r0 = wg * 64 + (warp & 3) * 16 + g;
    const float2* s_st = (const float2*)(sptr + STAGES * Cfg::STAGE_BYTES + 256);
    const float* s_cs = (const float*)(sptr + STAGES * Cfg::STAGE_BYTES + 256 + 1024);
    named_bar(2, 352);
    float2 st[2] = {s_st[r0], s_st[r0 + 8]};
#pragma unroll
    for (int j = 0; j < BN / 8; j++) {
      const float2 cg = *(const float2*)&s_cs[j * 8 + 2 * t], cu = *(const float2*)&s_cs[BN + j * 8 + 2 * t];
      const float* a = &acc[0][0][4 * j];
      const float* b = &acc[0][1][4 * j];
#pragma unroll
      for (int e = 0; e < 2; e++) {
        const float2 s_ = st[e];
        const uint32_t gp = pack_bf16(fmaf(-s_.x, cg.x, a[2 * e]) * s_.y, fmaf(-s_.x, cg.y, a[2 * e + 1]) * s_.y);
        const uint32_t up = pack_bf16(fmaf(-s_.x, cu.x, b[2 * e]) * s_.y, fmaf(-s_.x, cu.y, b[2 * e + 1]) * s_.y);
        uint32_t r;
        asm("{\n.reg .b32 z;\nmax.bf16x2 z, %1, %3;\nmul.rn.bf16x2 %0, z, %2;\n}" : "=r"(r) : "r"(gp), "r"(up), "r"(0u));
        *(uint32_t*)(sptr + (r0 + 8 * e) * LDS + j * 16 + t * 4) = r;
      }
    }
    named_bar(1, 256);
#pragma unroll
    for (int i = 0; i < BM * (BN / 8) / 256; i++) {
      const int idx = i * 256 + ctid, r = idx / (BN / 8), c = idx % (BN / 8);
      st_g16(out + (size_t)(m0 + r) * DFF + n0 + c * 8, *(const uint4*)(sptr + r * LDS + c * 16));
    }
  }
  if constexpr (CN * CM > 1) cluster_wait();
  TS_END(EPI == EPI_QKV ? 1 : EPI + 2);
}

constexpr int R_STAGES = 8;
constexpr int R_STAGE_BYTES = 16384 + 5 * 2048;
constexpr int R_BAR_OFF = R_STAGES * R_STAGE_BYTES;
constexpr int R_SMEM = R_BAR_OFF + 256 + 1024;
template <int KDIM, bool STATS>
__global__ void __launch_bounds__(288, 1) gemm_res_kernel(const __grid_constant__ CUtensorMap tmA, const __grid_constant__ CUtensorMap tmB,
                                                          const __nv_bfloat16* resid, __nv_bfloat16* out) {
  constexpr int KT = KDIM / 64;
  extern __shared__ uint8_t smem_raw[];
  const uint32_t sbase = (smem_u32(smem_raw) + 1023u) & ~1023u;
  uint8_t* sptr = smem_raw + (sbase - smem_u32(smem_raw));
  const uint32_t sbar = sbase + R_BAR_OFF;
  const int tid = threadIdx.x, warp = tid >> 5, lane = tid & 31;
  const int n0 = blockIdx.x * 80, m0 = blockIdx.y * 128;
  TS_BEGIN(STATS ? 3 : 5);
  if (tid == 0) {
    for (int i = 0; i < R_STAGES; i++) { mbar_init(sbar + 8 * i, 1); mbar_init(sbar + 8 * (R_STAGES + i), 2); }
    asm volatile("fence.mbarrier_init.release.cluster;" ::: "memory");
  }
  __syncthreads();
  pdl_launch();
  if (warp == 8) {
    if (lane == 0) {
      auto load_b = [&](int kt, int s) { tma_3d(sbase + s * R_STAGE_BYTES + 16384, &tmB, 0, kt * 64, blockIdx.x * 5, sbar + 8 * s); };
      for (int s = 0; s < R_STAGES; s++) { mbar_expect_tx(sbar + 8 * s, R_STAGE_BYTES); if (s < 3) load_b(s, s); }
      pdl_wait();
      for (int s = 0; s < R_STAGES; s++) { tma_2d(sbase + s * R_STAGE_BYTES, &tmA, s * 64, m0, sbar + 8 * s); if (s >= 3) load_b(s, s); }
      for (int kt = R_STAGES; kt < KT; kt++) {
        const int s = kt % R_STAGES;
        mbar_wait(sbar + 8 * (R_STAGES + s), ((kt / R_STAGES) - 1) & 1);
        mbar_expect_tx(sbar + 8 * s, R_STAGE_BYTES);
        tma_2d(sbase + s * R_STAGE_BYTES, &tmA, kt * 64, m0, sbar + 8 * s);
        load_b(kt, s);
      }
    }
    return;
  }
  const int wg = warp >> 2, g = lane >> 2, t = lane & 3;
  pdl_wait();
  uint4 rv[5];
#pragma unroll
  for (int i = 0; i < 5; i++) {
    const int idx = i * 256 + tid, r = idx / 10, c = idx % 10;
    rv[i] = ld_g16(resid + (size_t)(m0 + r) * DM + n0 + c * 8);
  }
  float acc[40];
#pragma unroll
  for (int i = 0; i < 40; i++) acc[i] = 0.f;
  for (int kt = 0; kt < KT; kt++) {
    const int s = kt % R_STAGES;
    mbar_wait(sbar + 8 * s, (kt / R_STAGES) & 1);
    if (kt == 0) TS_MID(STATS ? 3 : 5, 0);
    const uint32_t sa = sbase + s * R_STAGE_BYTES + wg * 8192;
    const uint32_t sb = sbase + s * R_STAGE_BYTES + 16384;
    wgmma_fence();
#pragma unroll
    for (int ks = 0; ks < 4; ks++)
      wgmma_ss_n80(acc, make_desc(sa + ks * 32, 16, 1024, 1), make_desc(sb + ks * 512, 2048, 256, 3), 1);
    wgmma_commit();
    wgmma_wait<1>();
    if (kt > 0 && kt - 1 + R_STAGES < KT && (tid & 127) == 0) mbar_arrive(sbar + 8 * (R_STAGES + (kt - 1) % R_STAGES));
  }
  wgmma_wait<0>();
#pragma unroll
  for (int i = 0; i < 40; i++) asm volatile("" : "+f"(acc[i]) :: "memory");
  TS_MID(STATS ? 3 : 5, 1);
  named_bar(1, 256);
  constexpr int LDS = 176;
  const int r0 = wg * 64 + (warp & 3) * 16 + g;
#pragma unroll
  for (int i = 0; i < 10; i++) {
    *(uint32_t*)(sptr + r0 * LDS + i * 16 + t * 4) = pack_bf16(acc[4 * i], acc[4 * i + 1]);
    *(uint32_t*)(sptr + (r0 + 8) * LDS + i * 16 + t * 4) = pack_bf16(acc[4 * i + 2], acc[4 * i + 3]);
  }
  named_bar(1, 256);
  TS_MID(STATS ? 3 : 5, 2);
#pragma unroll
  for (int i = 0; i < 5; i++) {
    const int idx = i * 256 + tid, r = idx / 10, c = idx % 10;
    const uint4 a = *(const uint4*)(sptr + r * LDS + c * 16);
    const uint4 b = rv[i];
    uint4 o;
    o.x = pack_bf16(bf_lo(a.x) + bf_lo(b.x), bf_hi(a.x) + bf_hi(b.x));
    o.y = pack_bf16(bf_lo(a.y) + bf_lo(b.y), bf_hi(a.y) + bf_hi(b.y));
    o.z = pack_bf16(bf_lo(a.z) + bf_lo(b.z), bf_hi(a.z) + bf_hi(b.z));
    o.w = pack_bf16(bf_lo(a.w) + bf_lo(b.w), bf_hi(a.w) + bf_hi(b.w));
    st_g16(out + (size_t)(m0 + r) * DM + n0 + c * 8, o);
    if constexpr (STATS) *(uint4*)(sptr + r * LDS + c * 16) = o;
  }
  TS_MID(STATS ? 3 : 5, 3);
  if constexpr (STATS) {
    named_bar(1, 256);
    const int r = tid >> 1, hf = tid & 1;
    float f[40];
#pragma unroll
    for (int i = 0; i < 5; i++) {
      const uint4 v = *(const uint4*)(sptr + r * LDS + hf * 80 + i * 16);
      f[8 * i] = bf_lo(v.x); f[8 * i + 1] = bf_hi(v.x); f[8 * i + 2] = bf_lo(v.y); f[8 * i + 3] = bf_hi(v.y);
      f[8 * i + 4] = bf_lo(v.z); f[8 * i + 5] = bf_hi(v.z); f[8 * i + 6] = bf_lo(v.w); f[8 * i + 7] = bf_hi(v.w);
    }
    float s = 0.f;
#pragma unroll
    for (int i = 0; i < 40; i++) s += f[i];
    s += __shfl_xor_sync(~0u, s, 1);
    const float mu = s * (1.0f / 80.f);
    float q = 0.f;
#pragma unroll
    for (int i = 0; i < 40; i++) { const float d = f[i] - mu; q += d * d; }
    q += __shfl_xor_sync(~0u, q, 1);
    if (hf == 0) g_part2[(m0 + r) * 8 + blockIdx.x] = make_float2(s, q);
  }
  TS_END(STATS ? 3 : 5);
}

#define POLY_NUM 5
__device__ __forceinline__ float ex2_poly(float x, int shl23) {
  const float MAGIC = 12582912.f;
  const float tt = x + MAGIC;
  const float f = x - (tt - MAGIC);
  float p = fmaf(0.0013276472454890609f, f, 0.009675540961325169f);
  p = fmaf(p, f, 0.05550713092088699f);
  p = fmaf(p, f, 0.24022120237350464f);
  p = fmaf(p, f, 0.6931469440460205f);
  p = fmaf(p, f, 1.0000001192092896f);
  return __int_as_float(__float_as_int(tt) * shl23 + __float_as_int(p));
}
constexpr int KV_BYTES = S_LEN * 48;
constexpr int ATT_SMEM = 2 * KV_BYTES + 256 + 32768;
constexpr int ATT_BODY = 8;

__global__ void __launch_bounds__(512, 1) attn_kernel(int shl23, const __nv_bfloat16* __restrict__ wg_, const __nv_bfloat16* __restrict__ wu_,
                                                      const __nv_bfloat16* __restrict__ wo_, const __nv_bfloat16* __restrict__ wd_) {
  extern __shared__ __align__(1024) uint8_t smem[];
  if (blockIdx.x >= 128) {
    pdl_launch();
    const int e = blockIdx.x - 128, half = threadIdx.x >> 8;
    if (threadIdx.x == 0) {
      for (int i = 0; i < 13; i++) asm volatile("cp.async.bulk.prefetch.L2.global [%0], %1;" :: "l"((const uint8_t*)wo_ + (e * 13 + i) * 16384 * 0 + (size_t)(e * 13 + i >= 50 ? 0 : (e * 13 + i)) * 16384), "r"(16384));
      for (int i = 0; i < 30; i++) asm volatile("cp.async.bulk.prefetch.L2.global [%0], %1;" :: "l"((const uint8_t*)wd_ + (size_t)(e * 30 + i) * 16384), "r"(16384));
    }
    float (*red)[65] = (float (*)[65])(smem + half * 16384);
    for (int b = e * 12 + half; b < e * 12 + 12; b += 2) {
      if (b < 24) colsum64(wg_, DFF, b * 64, g_cs_g, red, threadIdx.x & 255, 1 + half);
      else colsum64(wu_, DFF, (b - 24) * 64, g_cs_u, red, threadIdx.x & 255, 1 + half);
    }
    return;
  }
  const int h = blockIdx.x >> 2, qb = blockIdx.x & 3;
  const uint32_t sK = smem_u32(smem), sV = sK + KV_BYTES, sBar = sV + KV_BYTES;
  const int tid = threadIdx.x;
  TS_BEGIN(2);
  if (tid == 0) {
    for (int i = 0; i < 9; i++) mbar_init(sBar + 8 * i, 1);
    asm volatile("fence.mbarrier_init.release.cluster;" ::: "memory");
  }
  __syncthreads();
  pdl_launch();
  pdl_wait();
  TS_MID(2, 0);
  const uint8_t* gk = (const uint8_t*)(g_k + (size_t)h * S_LEN * 24);
  const uint8_t* gv = (const uint8_t*)(g_v + (size_t)h * S_LEN * 24);
  auto load_kv = [&](int i0, int i1) {
    for (int i = i0; i < i1; i++) {
      mbar_expect_tx(sBar + 8 * i, 2 * 12288);
      bulk_g2s(sK + i * 12288, gk + i * 12288, 12288, sBar + 8 * i);
      bulk_g2s(sV + i * 12288, gv + i * 12288, 12288, sBar + 8 * i);
    }
  };
  if (tid == 0) {
    mbar_expect_tx(sBar + 64, 32768);
    bulk_g2s(sBar + 256, (const uint8_t*)g_q + ((size_t)h * S_LEN + qb * 512) * 64, 32768, sBar + 64);
    load_kv(0, 8);
  }
  float ka = 0.f, kb = 0.f;
#pragma unroll
  for (int i = 0; i < 8; i++) {
    const float2 v = *(const float2*)&g_kn[(i * NH + h) * 2];
    ka = (v.x > ka || v.x != v.x) ? v.x : ka;
    kb = (v.y > kb || v.y != v.y) ? v.y : kb;
  }
  bool fast;
  {
    const float kn = sqrtf(ka + kb);
    mbar_wait(sBar + 64, 0);
    uint8_t* qrow = smem + 2 * KV_BYTES + 256 + (tid >> 3) * 512 + (tid & 7) * 16;
    const uint4 c0 = *(const uint4*)qrow, c1 = *(const uint4*)(qrow + 128);
    const uint2 c2 = *(const uint2*)(qrow + 256);
    auto sq = [](uint32_t u) { const float a = bf_lo(u), b = bf_hi(u); return a * a + b * b; };
    const float n2 = sq(c0.x) + sq(c0.y) + sq(c0.z) + sq(c0.w) + sq(c1.x) + sq(c1.y) + sq(c1.z) + sq(c1.w) + sq(c2.x) + sq(c2.y);
    const float m = ceilf(sqrtf(n2) * kn * 1.001f) + 1.f;
    fast = __syncthreads_or(!(m <= 62.f)) == 0;
    if (fast) *(uint32_t*)(qrow + 256 + 8) = pack_bf16(-m, 0.f);
    asm volatile("fence.proxy.async.shared::cta;" ::: "memory");
    __syncthreads();
  }
  auto write_out = [&](float (&O)[12], int it) {
    uint32_t tid2;
    asm volatile("mov.u32 %0, %%tid.x;" : "=r"(tid2));
    const int lane2 = tid2 & 31, t2 = lane2 & 3;
    const int qq = (blockIdx.x & 3) * 512 + (it * 4 + (tid2 >> 7)) * 64 + ((tid2 >> 5) & 3) * 16 + (lane2 >> 2);
    const float l0 = __shfl_sync(~0u, O[8], (lane2 & ~3) | 2), l1 = __shfl_sync(~0u, O[10], (lane2 & ~3) | 2);
    const float r0 = 1.f / l0, r1 = 1.f / l1;
    uint32_t* o0 = (uint32_t*)(g_o + (size_t)qq * DM + (blockIdx.x >> 2) * DH);
    uint32_t* o1 = o0 + 8 * DM / 2;
    o0[t2] = pack_bf16(O[0] * r0, O[1] * r0); o1[t2] = pack_bf16(O[2] * r1, O[3] * r1);
    o0[t2 + 4] = pack_bf16(O[4] * r0, O[5] * r0); o1[t2 + 4] = pack_bf16(O[6] * r1, O[7] * r1);
    if (t2 < 2) { o0[t2 + 8] = pack_bf16(O[8] * r0, O[9] * r0); o1[t2 + 8] = pack_bf16(O[10] * r1, O[11] * r1); }
  };
  TS_MID(2, 1);
  if (fast) {
#pragma unroll 1
    for (int it = 0; it < 2; it++) {
      const uint64_t dq = make_desc(sBar + 256 + (it * 4 + (tid >> 7)) * 4096, 128, 512, 0);
      float O[12];
#pragma unroll
      for (int i = 0; i < 12; i++) { O[i] = 0.f; asm volatile("" : "+f"(O[i]) :: "memory"); }
      float S[2][32];
      uint32_t P[16];
#pragma unroll 1
      for (int jb = 0; jb < 32 / ATT_BODY; jb++) {
        if (it == 0) { for (int c = 0; c < ATT_BODY / 4; c++) mbar_wait(sBar + 8 * (jb * (ATT_BODY / 4) + c), 0); }
        const uint64_t dk0 = make_desc(sK + jb * ATT_BODY * 8 * 384, 128, 384, 0);
        const uint64_t dv0 = make_desc(sV + jb * ATT_BODY * 8 * 384, 384, 128, 0);
        wgmma_fence();
        wgmma_ss_n64_k(S[0], dq, dk0, 0);
        wgmma_ss_n64_k(S[0], dq + (256 >> 4), dk0 + (256 >> 4), 1);
        wgmma_commit();
#pragma unroll
        for (int u = 0; u < ATT_BODY; u++) {
          if (u + 1 < ATT_BODY) {
            const uint64_t dk = dk0 + (((u + 1) * 8 * 384) >> 4);
            wgmma_fence();
            wgmma_ss_n64_k(S[(u + 1) & 1], dq, dk, 0);
            wgmma_ss_n64_k(S[(u + 1) & 1], dq + (256 >> 4), dk + (256 >> 4), 1);
            wgmma_commit();
          }
          if (u == 0 || u == ATT_BODY - 1) wgmma_wait<1>(); else wgmma_wait<2>();
#pragma unroll
          for (int i = 0; i < 32; i++) asm volatile("" : "+f"(S[u & 1][i]) :: "memory");
          const uint64_t dv = dv0 + ((u * 8 * 384) >> 4);
#pragma unroll
          for (int hf = 0; hf < 2; hf++) {
            if (hf == 1 && u > 0) { if (u == ATT_BODY - 1) wgmma_wait<1>(); else wgmma_wait<2>(); }
#pragma unroll
            for (int i = hf * 8; i < hf * 8 + 8; i++) {
              const bool usepoly = ((i + 1) * POLY_NUM / 16) != (i * POLY_NUM / 16);
              float a, b;
              if (usepoly) { a = ex2_poly(S[u & 1][2 * i], shl23); b = ex2_poly(S[u & 1][2 * i + 1], shl23); }
              else { a = ex2_mufu(S[u & 1][2 * i]); b = ex2_mufu(S[u & 1][2 * i + 1]); }
              P[i] = pack_bf16(a, b);
            }
            wgmma_fence();
#pragma unroll
            for (int ks = hf * 2; ks < hf * 2 + 2; ks++)
              wgmma_rs_n24_tb(O, P[4 * ks], P[4 * ks + 1], P[4 * ks + 2], P[4 * ks + 3], dv + ((ks * 768) >> 4), 1);
            wgmma_commit();
          }
        }
        wgmma_wait<0>();
      }
#pragma unroll
      for (int i = 0; i < 12; i++) asm volatile("" : "+f"(O[i]) :: "memory");
      write_out(O, it);
      if (it == 0) TS_MID(2, 2);
    }
  } else {
#pragma unroll 1
    for (int it = 0; it < 2; it++) {
      const uint64_t dq = make_desc(sBar + 256 + (it * 4 + (tid >> 7)) * 4096, 128, 512, 0);
      float O[12];
#pragma unroll
      for (int i = 0; i < 12; i++) { O[i] = 0.f; asm volatile("" : "+f"(O[i]) :: "memory"); }
      float S[32];
      float mx0 = -INFINITY, mx1 = -INFINITY;
#pragma unroll 1
      for (int j = 0; j < 32; j++) {
        if (it == 0 && (j & 3) == 0) mbar_wait(sBar + 8 * (j >> 2), 0);
        const uint64_t dk = make_desc(sK + j * 8 * 384, 128, 384, 0);
        wgmma_fence();
        wgmma_ss_n64_k(S, dq, dk, 0);
        wgmma_ss_n64_k(S, dq + (256 >> 4), dk + (256 >> 4), 1);
        wgmma_commit();
        wgmma_wait<0>();
#pragma unroll
        for (int i = 0; i < 8; i++) {
          mx0 = fmaxf(mx0, fmaxf(S[4 * i], S[4 * i + 1]));
          mx1 = fmaxf(mx1, fmaxf(S[4 * i + 2], S[4 * i + 3]));
        }
      }
      mx0 = fmaxf(mx0, __shfl_xor_sync(~0u, mx0, 1)); mx0 = fmaxf(mx0, __shfl_xor_sync(~0u, mx0, 2));
      mx1 = fmaxf(mx1, __shfl_xor_sync(~0u, mx1, 1)); mx1 = fmaxf(mx1, __shfl_xor_sync(~0u, mx1, 2));
#pragma unroll 1
      for (int j = 0; j < 32; j++) {
        const uint64_t dk = make_desc(sK + j * 8 * 384, 128, 384, 0);
        wgmma_fence();
        wgmma_ss_n64_k(S, dq, dk, 0);
        wgmma_ss_n64_k(S, dq + (256 >> 4), dk + (256 >> 4), 1);
        wgmma_commit();
        wgmma_wait<0>();
        uint32_t P[16];
#pragma unroll
        for (int i = 0; i < 8; i++) {
          P[2 * i] = pack_bf16(ex2_mufu(S[4 * i] - mx0), ex2_mufu(S[4 * i + 1] - mx0));
          P[2 * i + 1] = pack_bf16(ex2_mufu(S[4 * i + 2] - mx1), ex2_mufu(S[4 * i + 3] - mx1));
        }
        wgmma_fence();
        const uint64_t dv = make_desc(sV + j * 8 * 384, 384, 128, 0);
#pragma unroll
        for (int ks = 0; ks < 4; ks++)
          wgmma_rs_n24_tb(O, P[4 * ks], P[4 * ks + 1], P[4 * ks + 2], P[4 * ks + 3], dv + ((ks * 768) >> 4), 1);
        wgmma_commit();
        wgmma_wait<0>();
      }
#pragma unroll
      for (int i = 0; i < 12; i++) asm volatile("" : "+f"(O[i]) :: "memory");
      write_out(O, it);
    }
  }
  TS_END(2);
}

typedef CUresult (*EncodeFn)(CUtensorMap*, CUtensorMapDataType, cuuint32_t, void*, const cuuint64_t*, const cuuint64_t*, const cuuint32_t*,
                             const cuuint32_t*, CUtensorMapInterleave, CUtensorMapSwizzle, CUtensorMapL2promotion, CUtensorMapFloatOOBfill);
static EncodeFn get_encode() {
  static EncodeFn fn = nullptr;
  if (!fn) {
    void* p = nullptr; cudaDriverEntryPointQueryResult st;
    cudaGetDriverEntryPoint("cuTensorMapEncodeTiled", &p, cudaEnableDefault, &st);
    fn = (EncodeFn)p;
  }
  return fn;
}
static CUtensorMap make_map(const void* ptr, int rows, int cols, int box_rows, int box_cols = 64) {
  CUtensorMap m;
  cuuint64_t dims[2] = {(cuuint64_t)cols, (cuuint64_t)rows};
  cuuint64_t strides[1] = {(cuuint64_t)cols * 2};
  cuuint32_t box[2] = {(cuuint32_t)box_cols, (cuuint32_t)box_rows};
  cuuint32_t es[2] = {1, 1};
  get_encode()(&m, CU_TENSOR_MAP_DATA_TYPE_BFLOAT16, 2, const_cast<void*>(ptr), dims, strides, box, es, CU_TENSOR_MAP_INTERLEAVE_NONE,
               box_cols == 64 ? CU_TENSOR_MAP_SWIZZLE_128B : (box_cols == 32 ? CU_TENSOR_MAP_SWIZZLE_64B : CU_TENSOR_MAP_SWIZZLE_32B), CU_TENSOR_MAP_L2_PROMOTION_L2_128B, CU_TENSOR_MAP_FLOAT_OOB_FILL_NONE);
  return m;
}
static CUtensorMap make_map_w(const void* ptr, int rows, int cols, int bc, int nblk) {
  CUtensorMap m;
  cuuint64_t dims[3] = {(cuuint64_t)bc, (cuuint64_t)rows, (cuuint64_t)(cols / bc)};
  cuuint64_t strides[2] = {(cuuint64_t)cols * 2, (cuuint64_t)bc * 2};
  cuuint32_t box[3] = {(cuuint32_t)bc, 64, (cuuint32_t)nblk};
  cuuint32_t es[3] = {1, 1, 1};
  get_encode()(&m, CU_TENSOR_MAP_DATA_TYPE_BFLOAT16, 3, const_cast<void*>(ptr), dims, strides, box, es, CU_TENSOR_MAP_INTERLEAVE_NONE,
               bc == 64 ? CU_TENSOR_MAP_SWIZZLE_128B : (bc == 32 ? CU_TENSOR_MAP_SWIZZLE_64B : CU_TENSOR_MAP_SWIZZLE_32B),
               CU_TENSOR_MAP_L2_PROMOTION_L2_128B, CU_TENSOR_MAP_FLOAT_OOB_FILL_NONE);
  return m;
}
template <typename... KArgs, typename... Args>
static void launch(void (*kern)(KArgs...), dim3 grid, dim3 block, size_t smem, bool pdl, dim3 cluster, Args... args) {
  cudaLaunchConfig_t cfg = {};
  cfg.gridDim = grid; cfg.blockDim = block; cfg.dynamicSmemBytes = smem; cfg.stream = cudaStreamPerThread;
  cudaLaunchAttribute at[2];
  int na = 0;
  if (pdl) { at[na].id = cudaLaunchAttributeProgrammaticStreamSerialization; at[na].val.programmaticStreamSerializationAllowed = 1; na++; }
  if (cluster.x * cluster.y > 1) { at[na].id = cudaLaunchAttributeClusterDimension; at[na].val.clusterDim.x = cluster.x; at[na].val.clusterDim.y = cluster.y; at[na].val.clusterDim.z = 1; na++; }
  cfg.attrs = at; cfg.numAttrs = na;
  cudaLaunchKernelEx(&cfg, kern, KArgs(args)...);
}

extern "C" void kernel_launch(void* const* d_in, const int* in_sizes, int n_in, void* d_out, int out_size) {
  const __nv_bfloat16* x = (const __nv_bfloat16*)d_in[0];
  const __nv_bfloat16* wqkv = (const __nv_bfloat16*)d_in[1];
  const __nv_bfloat16* wo = (const __nv_bfloat16*)d_in[2];
  const __nv_bfloat16* wgate = (const __nv_bfloat16*)d_in[4];
  const __nv_bfloat16* wup = (const __nv_bfloat16*)d_in[5];
  const __nv_bfloat16* wdown = (const __nv_bfloat16*)d_in[6];
  __nv_bfloat16* out = (__nv_bfloat16*)d_out;
  void *p_o, *p_h, *p_act;
  cudaGetSymbolAddress(&p_o, g_o); cudaGetSymbolAddress(&p_h, g_h); cudaGetSymbolAddress(&p_act, g_act);

#define A_CN 1
#define A_CM 1
#define D_CN 1
#define D_CM 1
  auto kA = gemm_kernel<256, 128, 1, DM, 4, EPI_QKV, 1, A_CN, A_CM>;
  auto kC = gemm_res_kernel<DM, true>;
  auto kD = gemm_kernel<128, 192, 2, DM, 3, EPI_GLU, 1, D_CN, D_CM>;
  auto kE = gemm_res_kernel<DFF, false>;
  constexpr int smA = GemmCfg<256, 128, 1, 4>::SMEM, smC = R_SMEM, smD = GemmCfg<128, 192, 2, 3>::SMEM;
  cudaFuncSetAttribute(kA, cudaFuncAttributeMaxDynamicSharedMemorySize, smA);
  cudaFuncSetAttribute(kC, cudaFuncAttributeMaxDynamicSharedMemorySize, smC);
  cudaFuncSetAttribute(kD, cudaFuncAttributeMaxDynamicSharedMemorySize, smD);
  cudaFuncSetAttribute(kE, cudaFuncAttributeMaxDynamicSharedMemorySize, smC);
  cudaFuncSetAttribute(attn_kernel, cudaFuncAttributeMaxDynamicSharedMemorySize, ATT_SMEM);

  const CUtensorMap tm_x = make_map(x, S_LEN, DM, 256), tm_wqkv = make_map_w(wqkv, DM, 3 * DM, 64, 2);
  const CUtensorMap tm_o = make_map(p_o, S_LEN, DM, 128), tm_wo = make_map_w(wo, DM, DM, 16, 5);
  const CUtensorMap tm_h = make_map(p_h, S_LEN, DM, 128), tm_wg = make_map_w(wgate, DM, DFF, 64, 3), tm_wu = make_map_w(wup, DM, DFF, 64, 3);
  const CUtensorMap tm_act = make_map(p_act, S_LEN, DFF, 128), tm_wd = make_map_w(wdown, DFF, DM, 16, 5);

  launch(pre_kernel, dim3(12), dim3(1024), 0, false, dim3(1, 1), x, wqkv);
  launch(kA, dim3(15, 8), dim3(288), smA, true, dim3(A_CN, A_CM), tm_x, tm_wqkv, tm_wqkv, x, (__nv_bfloat16*)wqkv);
  launch(attn_kernel, dim3(132), dim3(512), ATT_SMEM, true, dim3(1, 1), 0x800000, wgate, wup, wo, wdown);
  launch(kC, dim3(8, 16), dim3(288), smC, true, dim3(1, 1), tm_o, tm_wo, x, (__nv_bfloat16*)p_h);
  launch(kD, dim3(8, 16), dim3(384), smD, true, dim3(D_CN, D_CM), tm_h, tm_wg, tm_wu, (const __nv_bfloat16*)nullptr, (__nv_bfloat16*)p_act);
  launch(kE, dim3(8, 16), dim3(288), smC, true, dim3(1, 1), tm_act, tm_wd, (const __nv_bfloat16*)p_h, out);
}
```

```cpp
#include <cuda_runtime.h>
#include <cuda_bf16.h>
#include <cuda.h>
#include <stdint.h>

constexpr int S_LEN = 2048, DM = 640, NH = 32, DH = 20, DFF = 1536;

__device__ __align__(1024) __nv_bfloat16 g_q[NH * S_LEN * 32];
__device__ __align__(1024) __nv_bfloat16 g_k[NH * S_LEN * 24];
__device__ __align__(1024) __nv_bfloat16 g_v[NH * S_LEN * 24];
__device__ __align__(1024) __nv_bfloat16 g_o[S_LEN * DM];
__device__ __align__(1024) __nv_bfloat16 g_h[S_LEN * DM];
__device__ __align__(1024) __nv_bfloat16 g_act[S_LEN * DFF];
__device__ float g_kn[8 * NH * 2];
__device__ float2 g_stat1[S_LEN];
__device__ float g_cs_qkv[3 * DM];
__device__ float g_cs_g[DFF];
__device__ float g_cs_u[DFF];
__device__ unsigned int g_flag[32];
__device__ float2 g_part2[S_LEN * 10];

#define TS_BEGIN(k)
#define TS_END(k)
#define TS_MID(k, i)
__device__ __forceinline__ uint32_t smem_u32(const void* p) { return (uint32_t)__cvta_generic_to_shared(p); }
__device__ __forceinline__ void mbar_init(uint32_t bar, uint32_t cnt) { asm volatile("mbarrier.init.shared::cta.b64 [%0], %1;" :: "r"(bar), "r"(cnt)); }
__device__ __forceinline__ void mbar_expect_tx(uint32_t bar, uint32_t bytes) { asm volatile("mbarrier.arrive.expect_tx.shared::cta.b64 _, [%0], %1;" :: "r"(bar), "r"(bytes) : "memory"); }
__device__ __forceinline__ void mbar_arrive(uint32_t bar) { asm volatile("mbarrier.arrive.shared::cta.b64 _, [%0];" :: "r"(bar) : "memory"); }
__device__ __forceinline__ void mbar_wait(uint32_t bar, uint32_t parity) {
  uint32_t done;
  uint32_t spins = 0;
  do {
    asm volatile("{\n.reg .pred P1;\nmbarrier.try_wait.parity.shared::cta.b64 P1, [%1], %2;\nselp.u32 %0, 1, 0, P1;\n}" : "=r"(done) : "r"(bar), "r"(parity) : "memory");
  } while (!done && ++spins < (1u << 24));
}
__device__ __forceinline__ void bulk_g2s(uint32_t dst, const void* src, uint32_t bytes, uint32_t bar) {
  asm volatile("cp.async.bulk.shared::cluster.global.mbarrier::complete_tx::bytes [%0], [%1], %2, [%3];" :: "r"(dst), "l"(src), "r"(bytes), "r"(bar) : "memory");
}
__device__ __forceinline__ void tma_2d(uint32_t dst, const CUtensorMap* tm, int c0, int c1, uint32_t bar) {
  asm volatile("cp.async.bulk.tensor.2d.shared::cluster.global.mbarrier::complete_tx::bytes [%0], [%1, {%3, %4}], [%2];"
               :: "r"(dst), "l"(tm), "r"(bar), "r"(c0), "r"(c1) : "memory");
}
__device__ __forceinline__ void tma_3d(uint32_t dst, const CUtensorMap* tm, int c0, int c1, int c2, uint32_t bar) {
  asm volatile("cp.async.bulk.tensor.3d.shared::cluster.global.mbarrier::complete_tx::bytes [%0], [%1, {%3, %4, %5}], [%2];"
               :: "r"(dst), "l"(tm), "r"(bar), "r"(c0), "r"(c1), "r"(c2) : "memory");
}
__device__ __forceinline__ void tma_2d_mc(uint32_t dst, const CUtensorMap* tm, int c0, int c1, uint32_t bar, uint16_t mask) {
  asm volatile("cp.async.bulk.tensor.2d.shared::cluster.global.mbarrier::complete_tx::bytes.multicast::cluster [%0], [%1, {%3, %4}], [%2], %5;"
               :: "r"(dst), "l"(tm), "r"(bar), "r"(c0), "r"(c1), "h"(mask) : "memory");
}
__device__ __forceinline__ void mbar_arrive_remote(uint32_t bar, uint32_t rank) {
  asm volatile("{\n.reg .b32 ra;\nmapa.shared::cluster.u32 ra, %0, %1;\nmbarrier.arrive.release.cluster.shared::cluster.b64 _, [ra];\n}" :: "r"(bar), "r"(rank) : "memory");
}
__device__ __forceinline__ void cluster_arrive() { asm volatile("barrier.cluster.arrive.release.aligned;" ::: "memory"); }
__device__ __forceinline__ void cluster_wait() { asm volatile("barrier.cluster.wait.acquire.aligned;" ::: "memory"); }
__device__ __forceinline__ void wgmma_fence() { asm volatile("wgmma.fence.sync.aligned;" ::: "memory"); }
__device__ __forceinline__ void wgmma_commit() { asm volatile("wgmma.commit_group.sync.aligned;" ::: "memory"); }
template <int N> __device__ __forceinline__ void wgmma_wait() { asm volatile("wgmma.wait_group.sync.aligned %0;" :: "n"(N) : "memory"); }
__device__ __forceinline__ void pdl_wait() { asm volatile("griddepcontrol.wait;" ::: "memory"); }
__device__ __forceinline__ void pdl_launch() { asm volatile("griddepcontrol.launch_dependents;" ::: "memory"); }
__device__ __forceinline__ void named_bar(int id, int n) { asm volatile("bar.sync %0, %1;" :: "r"(id), "r"(n) : "memory"); }
__device__ __forceinline__ uint64_t make_desc(uint32_t addr, uint32_t lbo, uint32_t sbo, uint32_t swz) {
  return (uint64_t)((addr & 0x3FFFF) >> 4) | ((uint64_t)(lbo >> 4) << 16) | ((uint64_t)(sbo >> 4) << 32) | ((uint64_t)swz << 62);
}
__device__ __forceinline__ void st_g16(void* p, uint4 v) { asm volatile("st.global.v4.b32 [%0], {%1, %2, %3, %4};" :: "l"(p), "r"(v.x), "r"(v.y), "r"(v.z), "r"(v.w) : "memory"); }
__device__ __forceinline__ void st_g8(void* p, uint2 v) { asm volatile("st.global.v2.b32 [%0], {%1, %2};" :: "l"(p), "r"(v.x), "r"(v.y) : "memory"); }
__device__ __forceinline__ uint4 ld_g16(const void* p) { uint4 v; asm volatile("ld.global.v4.b32 {%0, %1, %2, %3}, [%4];" : "=r"(v.x), "=r"(v.y), "=r"(v.z), "=r"(v.w) : "l"(p) : "memory"); return v; }
__device__ __forceinline__ uint32_t pack_bf16(float lo, float hi) { uint32_t r; asm("cvt.rn.bf16x2.f32 %0, %1, %2;" : "=r"(r) : "f"(hi), "f"(lo)); return r; }
__device__ __forceinline__ float bf_lo(uint32_t u) { return __uint_as_float(u << 16); }
__device__ __forceinline__ float bf_hi(uint32_t u) { return __uint_as_float(u & 0xffff0000u); }
__device__ __forceinline__ float bf_round(float x) { return __bfloat162float(__float2bfloat16_rn(x)); }
__device__ __forceinline__ float ex2_mufu(float x) { float y; asm("ex2.approx.ftz.f32 %0, %1;" : "=f"(y) : "f"(x)); return y; }

__device__ __forceinline__ void wgmma_ss_n80(float (&d)[40], uint64_t da, uint64_t db, int scale_d) {
  asm volatile("{\n.reg .pred p;\nsetp.ne.b32 p, %42, 0;\n"
    "wgmma.mma_async.sync.aligned.m64n80k16.f32.bf16.bf16 {%0,%1,%2,%3,%4,%5,%6,%7,%8,%9,%10,%11,%12,%13,%14,%15,%16,%17,%18,%19,%20,%21,%22,%23,%24,%25,%26,%27,%28,%29,%30,%31,%32,%33,%34,%35,%36,%37,%38,%39}, %40, %41, p, 1, 1, 0, 1;\n}\n"
    : "+f"(d[0]),"+f"(d[1]),"+f"(d[2]),"+f"(d[3]),"+f"(d[4]),"+f"(d[5]),"+f"(d[6]),"+f"(d[7]),"+f"(d[8]),"+f"(d[9]),"+f"(d[10]),"+f"(d[11]),"+f"(d[12]),"+f"(d[13]),"+f"(d[14]),"+f"(d[15]),"+f"(d[16]),"+f"(d[17]),"+f"(d[18]),"+f"(d[19]),"+f"(d[20]),"+f"(d[21]),"+f"(d[22]),"+f"(d[23]),"+f"(d[24]),"+f"(d[25]),"+f"(d[26]),"+f"(d[27]),"+f"(d[28]),"+f"(d[29]),"+f"(d[30]),"+f"(d[31]),"+f"(d[32]),"+f"(d[33]),"+f"(d[34]),"+f"(d[35]),"+f"(d[36]),"+f"(d[37]),"+f"(d[38]),"+f"(d[39])
    : "l"(da), "l"(db), "r"(scale_d));
}
__device__ __forceinline__ void wgmma_ss_n128(float (&d)[64], uint64_t da, uint64_t db, int scale_d) {
  asm volatile("{\n.reg .pred p;\nsetp.ne.b32 p, %66, 0;\n"
    "wgmma.mma_async.sync.aligned.m64n128k16.f32.bf16.bf16 {%0,%1,%2,%3,%4,%5,%6,%7,%8,%9,%10,%11,%12,%13,%14,%15,%16,%17,%18,%19,%20,%21,%22,%23,%24,%25,%26,%27,%28,%29,%30,%31,%32,%33,%34,%35,%36,%37,%38,%39,%40,%41,%42,%43,%44,%45,%46,%47,%48,%49,%50,%51,%52,%53,%54,%55,%56,%57,%58,%59,%60,%61,%62,%63}, %64, %65, p, 1, 1, 0, 1;\n}\n"
    : "+f"(d[0]),"+f"(d[1]),"+f"(d[2]),"+f"(d[3]),"+f"(d[4]),"+f"(d[5]),"+f"(d[6]),"+f"(d[7]),"+f"(d[8]),"+f"(d[9]),"+f"(d[10]),"+f"(d[11]),"+f"(d[12]),"+f"(d[13]),"+f"(d[14]),"+f"(d[15]),"+f"(d[16]),"+f"(d[17]),"+f"(d[18]),"+f"(d[19]),"+f"(d[20]),"+f"(d[21]),"+f"(d[22]),"+f"(d[23]),"+f"(d[24]),"+f"(d[25]),"+f"(d[26]),"+f"(d[27]),"+f"(d[28]),"+f"(d[29]),"+f"(d[30]),"+f"(d[31]),"+f"(d[32]),"+f"(d[33]),"+f"(d[34]),"+f"(d[35]),"+f"(d[36]),"+f"(d[37]),"+f"(d[38]),"+f"(d[39]),"+f"(d[40]),"+f"(d[41]),"+f"(d[42]),"+f"(d[43]),"+f"(d[44]),"+f"(d[45]),"+f"(d[46]),"+f"(d[47]),"+f"(d[48]),"+f"(d[49]),"+f"(d[50]),"+f"(d[51]),"+f"(d[52]),"+f"(d[53]),"+f"(d[54]),"+f"(d[55]),"+f"(d[56]),"+f"(d[57]),"+f"(d[58]),"+f"(d[59]),"+f"(d[60]),"+f"(d[61]),"+f"(d[62]),"+f"(d[63])
    : "l"(da), "l"(db), "r"(scale_d));
}
__device__ __forceinline__ void wgmma_ss_n192(float (&d)[96], uint64_t da, uint64_t db, int scale_d) {
  asm volatile("{\n.reg .pred p;\nsetp.ne.b32 p, %98, 0;\n"
    "wgmma.mma_async.sync.aligned.m64n192k16.f32.bf16.bf16 {%0,%1,%2,%3,%4,%5,%6,%7,%8,%9,%10,%11,%12,%13,%14,%15,%16,%17,%18,%19,%20,%21,%22,%23,%24,%25,%26,%27,%28,%29,%30,%31,%32,%33,%34,%35,%36,%37,%38,%39,%40,%41,%42,%43,%44,%45,%46,%47,%48,%49,%50,%51,%52,%53,%54,%55,%56,%57,%58,%59,%60,%61,%62,%63,%64,%65,%66,%67,%68,%69,%70,%71,%72,%73,%74,%75,%76,%77,%78,%79,%80,%81,%82,%83,%84,%85,%86,%87,%88,%89,%90,%91,%92,%93,%94,%95}, %96, %97, p, 1, 1, 0, 1;\n}\n"
    : "+f"(d[0]),"+f"(d[1]),"+f"(d[2]),"+f"(d[3]),"+f"(d[4]),"+f"(d[5]),"+f"(d[6]),"+f"(d[7]),"+f"(d[8]),"+f"(d[9]),"+f"(d[10]),"+f"(d[11]),"+f"(d[12]),"+f"(d[13]),"+f"(d[14]),"+f"(d[15]),"+f"(d[16]),"+f"(d[17]),"+f"(d[18]),"+f"(d[19]),"+f"(d[20]),"+f"(d[21]),"+f"(d[22]),"+f"(d[23]),"+f"(d[24]),"+f"(d[25]),"+f"(d[26]),"+f"(d[27]),"+f"(d[28]),"+f"(d[29]),"+f"(d[30]),"+f"(d[31]),"+f"(d[32]),"+f"(d[33]),"+f"(d[34]),"+f"(d[35]),"+f"(d[36]),"+f"(d[37]),"+f"(d[38]),"+f"(d[39]),"+f"(d[40]),"+f"(d[41]),"+f"(d[42]),"+f"(d[43]),"+f"(d[44]),"+f"(d[45]),"+f"(d[46]),"+f"(d[47]),"+f"(d[48]),"+f"(d[49]),"+f"(d[50]),"+f"(d[51]),"+f"(d[52]),"+f"(d[53]),"+f"(d[54]),"+f"(d[55]),"+f"(d[56]),"+f"(d[57]),"+f"(d[58]),"+f"(d[59]),"+f"(d[60]),"+f"(d[61]),"+f"(d[62]),"+f"(d[63]),"+f"(d[64]),"+f"(d[65]),"+f"(d[66]),"+f"(d[67]),"+f"(d[68]),"+f"(d[69]),"+f"(d[70]),"+f"(d[71]),"+f"(d[72]),"+f"(d[73]),"+f"(d[74]),"+f"(d[75]),"+f"(d[76]),"+f"(d[77]),"+f"(d[78]),"+f"(d[79]),"+f"(d[80]),"+f"(d[81]),"+f"(d[82]),"+f"(d[83]),"+f"(d[84]),"+f"(d[85]),"+f"(d[86]),"+f"(d[87]),"+f"(d[88]),"+f"(d[89]),"+f"(d[90]),"+f"(d[91]),"+f"(d[92]),"+f"(d[93]),"+f"(d[94]),"+f"(d[95])
    : "l"(da), "l"(db), "r"(scale_d));
}
__device__ __forceinline__ void wgmma_ss_n64_k(float (&d)[32], uint64_t da, uint64_t db, int scale_d) {
  asm volatile("{\n.reg .pred p;\nsetp.ne.b32 p, %34, 0;\n"
    "wgmma.mma_async.sync.aligned.m64n64k16.f32.bf16.bf16 {%0,%1,%2,%3,%4,%5,%6,%7,%8,%9,%10,%11,%12,%13,%14,%15,%16,%17,%18,%19,%20,%21,%22,%23,%24,%25,%26,%27,%28,%29,%30,%31}, %32, %33, p, 1, 1, 0, 0;\n}\n"
    : "+f"(d[0]),"+f"(d[1]),"+f"(d[2]),"+f"(d[3]),"+f"(d[4]),"+f"(d[5]),"+f"(d[6]),"+f"(d[7]),"+f"(d[8]),"+f"(d[9]),"+f"(d[10]),"+f"(d[11]),"+f"(d[12]),"+f"(d[13]),"+f"(d[14]),"+f"(d[15]),"+f"(d[16]),"+f"(d[17]),"+f"(d[18]),"+f"(d[19]),"+f"(d[20]),"+f"(d[21]),"+f"(d[22]),"+f"(d[23]),"+f"(d[24]),"+f"(d[25]),"+f"(d[26]),"+f"(d[27]),"+f"(d[28]),"+f"(d[29]),"+f"(d[30]),"+f"(d[31])
    : "l"(da), "l"(db), "r"(scale_d));
}
__device__ __forceinline__ void wgmma_rs_n24_tb(float (&d)[12], uint32_t a0, uint32_t a1, uint32_t a2, uint32_t a3, uint64_t db, int scale_d) {
  asm volatile("{\n.reg .pred p;\nsetp.ne.b32 p, %17, 0;\n"
    "wgmma.mma_async.sync.aligned.m64n24k16.f32.bf16.bf16 {%0,%1,%2,%3,%4,%5,%6,%7,%8,%9,%10,%11}, {%12,%13,%14,%15}, %16, p, 1, 1, 1;\n}\n"
    : "+f"(d[0]),"+f"(d[1]),"+f"(d[2]),"+f"(d[3]),"+f"(d[4]),"+f"(d[5]),"+f"(d[6]),"+f"(d[7]),"+f"(d[8]),"+f"(d[9]),"+f"(d[10]),"+f"(d[11])
    : "r"(a0), "r"(a1), "r"(a2), "r"(a3), "l"(db), "r"(scale_d));
}

constexpr int PRE_ROW_BLOCKS = 64;
constexpr int PRE_COL_BLOCKS = 3 * DM / 64;
__device__ __forceinline__ float2 ln_finish(float mean, float var) {
  float mb = bf_round(mean);
  float s = bf_round(sqrtf(bf_round(bf_round(var) + 1e-5f)));
  return make_float2(mb, 1.0f / s);
}
__device__ __forceinline__ void colsum64(const __nv_bfloat16* __restrict__ w, int ld, int c0, float* __restrict__ dst, float (*red)[65], int tid, int bar_id) {
  const int cg = tid & 7, r0 = tid >> 3;
  float acc[8];
#pragma unroll
  for (int i = 0; i < 8; i++) acc[i] = 0.f;
#pragma unroll 10
  for (int r = r0; r < DM; r += 32) {
    uint4 v = __ldg((const uint4*)(w + (size_t)r * ld + c0 + cg * 8));
    acc[0] += bf_lo(v.x); acc[1] += bf_hi(v.x); acc[2] += bf_lo(v.y); acc[3] += bf_hi(v.y);
    acc[4] += bf_lo(v.z); acc[5] += bf_hi(v.z); acc[6] += bf_lo(v.w); acc[7] += bf_hi(v.w);
  }
#pragma unroll
  for (int i = 0; i < 8; i++) red[r0][cg * 8 + i] = acc[i];
  named_bar(bar_id, 256);
  if (tid < 64) {
    float s = 0.f;
#pragma unroll
    for (int r = 0; r < 32; r++) s += red[r][tid];
    dst[c0 + tid] = s;
  }
  named_bar(bar_id, 256);
}
__global__ void __launch_bounds__(1024) pre_kernel(const __nv_bfloat16* __restrict__ x, const __nv_bfloat16* __restrict__ wqkv) {
  TS_BEGIN(0);
  pdl_launch();
  __shared__ float red[51][161];
  const int tid = threadIdx.x, lane = tid & 31, warp = tid >> 5;
  {
    const int ch = tid % 20, rl = tid / 20;
    if (rl < 51) {
      const __nv_bfloat16* w = wqkv + blockIdx.x * 160 + ch * 8;
      uint4 v[13];
#pragma unroll
      for (int i = 0; i < 13; i++) { const int r = rl + i * 51; v[i] = r < DM ? __ldg((const uint4*)(w + (size_t)r * (3 * DM))) : make_uint4(0, 0, 0, 0); }
      float acc[8];
#pragma unroll
      for (int i = 0; i < 8; i++) acc[i] = 0.f;
#pragma unroll
      for (int i = 0; i < 13; i++) {
        acc[0] += bf_lo(v[i].x); acc[1] += bf_hi(v[i].x); acc[2] += bf_lo(v[i].y); acc[3] += bf_hi(v[i].y);
        acc[4] += bf_lo(v[i].z); acc[5] += bf_hi(v[i].z); acc[6] += bf_lo(v[i].w); acc[7] += bf_hi(v[i].w);
      }
#pragma unroll
      for (int i = 0; i < 8; i++) red[rl][ch * 8 + i] = acc[i];
    }
  }
  const int rbeg = blockIdx.x * 171, rend = min(rbeg + 171, S_LEN);
  for (int row0 = rbeg + warp * 2; row0 < rend; row0 += 64) {
    uint4 v[2][3];
#pragma unroll
    for (int k = 0; k < 2; k++) {
      const int row = min(row0 + k, rend - 1);
      const uint4* p = (const uint4*)(x + (size_t)row * DM);
      v[k][0] = __ldg(p + lane); v[k][1] = __ldg(p + 32 + lane);
      v[k][2] = lane < 16 ? __ldg(p + 64 + lane) : make_uint4(0, 0, 0, 0);
    }
#pragma unroll
    for (int k = 0; k < 2; k++) {
      float f[24];
      const uint32_t u[12] = {v[k][0].x, v[k][0].y, v[k][0].z, v[k][0].w, v[k][1].x, v[k][1].y, v[k][1].z, v[k][1].w, v[k][2].x, v[k][2].y, v[k][2].z, v[k][2].w};
#pragma unroll
      for (int j = 0; j < 12; j++) { f[2 * j] = bf_lo(u[j]); f[2 * j + 1] = bf_hi(u[j]); }
      float s = 0.f;
#pragma unroll
      for (int j = 0; j < 24; j++) s += f[j];
#pragma unroll
      for (int o = 16; o; o >>= 1) s += __shfl_xor_sync(~0u, s, o);
      const float mean = s * (1.0f / DM);
      float q = 0.f;
#pragma unroll
      for (int j = 0; j < 16; j++) { const float d = f[j] - mean; q += d * d; }
      if (lane < 16) {
#pragma unroll
        for (int j = 16; j < 24; j++) { const float d = f[j] - mean; q += d * d; }
      }
#pragma unroll
      for (int o = 16; o; o >>= 1) q += __shfl_xor_sync(~0u, q, o);
      if (lane == 0 && row0 + k < rend) g_stat1[row0 + k] = ln_finish(mean, q * (1.0f / DM));
    }
  }
  __syncthreads();
  if (tid < 160) {
    float s = 0.f;
#pragma unroll 17
    for (int r = 0; r < 51; r++) s += red[r][tid];
    g_cs_qkv[blockIdx.x * 160 + tid] = s;
  }
  TS_END(0);
}

enum { EPI_QKV = 0, EPI_WO = 1, EPI_GLU = 2, EPI_DOWN = 3 };
template <int N> struct WG;
template <> struct WG<128> { static __device__ __forceinline__ void mma(float (&d)[64], uint64_t a, uint64_t b, int s) { wgmma_ss_n128(d, a, b, s); } };
template <> struct WG<192> { static __device__ __forceinline__ void mma(float (&d)[96], uint64_t a, uint64_t b, int s) { wgmma_ss_n192(d, a, b, s); } };

template <int BM, int BN, int NB, int STAGES> struct GemmCfg {
  static constexpr int A_BYTES = BM * 128;
  static constexpr int B_BYTES = NB * (BN / 64) * 8192;
  static constexpr int STAGE_BYTES = A_BYTES + B_BYTES;
  static constexpr int SMEM = STAGES * STAGE_BYTES + 1024   + 256   + 4096  ;
};

constexpr float QSCALE = 0.22360679774997896f * 1.4426950408889634f;

template <int BM, int BN, int NB, int KDIM, int STAGES, int EPI, int MINB, int CN, int CM>
__global__ void __launch_bounds__(EPI == EPI_GLU ? 384 : 288, MINB) gemm_kernel(const __grid_constant__ CUtensorMap tmA, const __grid_constant__ CUtensorMap tmB0,
                                                         const __grid_constant__ CUtensorMap tmB1,
                                                         const __nv_bfloat16* resid, __nv_bfloat16* out) {
  using Cfg = GemmCfg<BM, BN, NB, STAGES>;
  constexpr int MB = BM / 128;
  constexpr int KT = KDIM / 64;
  extern __shared__ uint8_t smem_raw[];
  const uint32_t sbase = (smem_u32(smem_raw) + 1023u) & ~1023u;
  uint8_t* sptr = smem_raw + (sbase - smem_u32(smem_raw));
  const uint32_t sbar = sbase + STAGES * Cfg::STAGE_BYTES;
  const int tid = threadIdx.x, warp = tid >> 5, lane = tid & 31;
  const int n0 = blockIdx.x * BN, m0 = blockIdx.y * BM;
  TS_BEGIN(EPI == EPI_QKV ? 1 : EPI + 2);
  TS_MID(EPI == EPI_QKV ? 1 : EPI + 2, 3);
  constexpr int NCL = CN + CM - 1;
  const int cx = blockIdx.x % CN, cy = blockIdx.y % CM;
  if (tid == 0) {
    for (int i = 0; i < STAGES; i++) { mbar_init(sbar + 8 * i, 1); mbar_init(sbar + 8 * (STAGES + i), 2 * NCL); }
    asm volatile("fence.mbarrier_init.release.cluster;" ::: "memory");
  }
  __syncthreads();
  if constexpr (CN * CM > 1) { cluster_arrive(); cluster_wait(); }
  pdl_launch();
  if (warp >= 8) {
    if constexpr (EPI == EPI_GLU) asm volatile("setmaxnreg.dec.sync.aligned.u32 40;");
    if (warp == 8 && lane == 0) {
      auto load_a = [&](int kt, int s) { tma_2d(sbase + s * Cfg::STAGE_BYTES, &tmA, kt * 64, m0, sbar + 8 * s); };
      auto load_b = [&](int kt, int s) {
        const uint32_t sb = sbase + s * Cfg::STAGE_BYTES + Cfg::A_BYTES;
        tma_3d(sb, &tmB0, 0, kt * 64, blockIdx.x * (BN / 64), sbar + 8 * s);
        if constexpr (NB == 2) tma_3d(sb + (BN / 64) * 8192, &tmB1, 0, kt * 64, blockIdx.x * (BN / 64), sbar + 8 * s);
      };
      if constexpr (EPI == EPI_QKV) {
        const int cta = blockIdx.y * gridDim.x + blockIdx.x;
        const uint32_t xb = S_LEN * DM * 2, xs = 21888;
        if (cta * xs < xb) asm volatile("cp.async.bulk.prefetch.L2.global [%0], %1;" :: "l"((const uint8_t*)resid + (size_t)cta * xs), "r"(min(xs, xb - cta * xs)));
        asm volatile("cp.async.bulk.prefetch.L2.global [%0], %1;" :: "l"((const uint8_t*)out + (size_t)cta * 20480), "r"(20480));
      }
      for (int s = 0; s < STAGES; s++) { mbar_expect_tx(sbar + 8 * s, Cfg::STAGE_BYTES); if (EPI != EPI_QKV || s == 0) load_b(s, s); }
      if (EPI != EPI_QKV) pdl_wait();
      for (int s = 0; s < STAGES; s++) { load_a(s, s); if (EPI == EPI_QKV && s > 0) load_b(s, s); }
      for (int kt = STAGES; kt < KT; kt++) {
        const int s = kt % STAGES;
        mbar_wait(sbar + 8 * (STAGES + s), ((kt / STAGES) - 1) & 1);
        mbar_expect_tx(sbar + 8 * s, Cfg::STAGE_BYTES);
        load_a(kt, s);
        load_b(kt, s);
      }
    }
    if constexpr (EPI == EPI_GLU) {
      if (warp > 8) {
        float2* s_st = (float2*)(sptr + STAGES * Cfg::STAGE_BYTES + 256);
        float* s_cs = (float*)(sptr + STAGES * Cfg::STAGE_BYTES + 256 + 1024);
        pdl_wait();
        for (int r = tid - 288; r < BM; r += 96) {
          const float2* pp = &g_part2[(m0 + r) * 8];
          float s = 0.f;
#pragma unroll
          for (int i = 0; i < 8; i++) s += pp[i].x;
          const float mean = s * (1.0f / DM);
          float q = 0.f;
#pragma unroll
          for (int i = 0; i < 8; i++) { const float2 p = pp[i]; const float d = p.x * (1.0f / 80.f) - mean; q += p.y + 80.f * d * d; }
          s_st[r] = ln_finish(mean, q * (1.0f / DM));
        }
        for (int c = tid - 288; c < BN; c += 96) { s_cs[c] = g_cs_g[n0 + c]; s_cs[BN + c] = g_cs_u[n0 + c]; }
        __threadfence_block();
        asm volatile("bar.arrive 2, 352;" ::: "memory");
      }
    }
    if constexpr (CN * CM > 1) { __syncwarp(); cluster_arrive(); cluster_wait(); }
    return;
  }
  if constexpr (EPI == EPI_GLU) asm volatile("setmaxnreg.inc.sync.aligned.u32 232;");
  const int wg = warp >> 2, g = lane >> 2, t = lane & 3;
  float acc[MB][NB][BN / 2];
#pragma unroll
  for (int mb = 0; mb < MB; mb++)
#pragma unroll
    for (int nb = 0; nb < NB; nb++)
#pragma unroll
      for (int i = 0; i < BN / 2; i++) acc[mb][nb][i] = 0.f;
  for (int kt = 0; kt < KT; kt++) {
    const int s = kt % STAGES;
    mbar_wait(sbar + 8 * s, (kt / STAGES) & 1);
    if (kt == 0) TS_MID(EPI == EPI_QKV ? 1 : EPI + 2, 0);
    const uint32_t sa = sbase + s * Cfg::STAGE_BYTES + wg * (MB * 64 * 128);
    const uint32_t sb = sbase + s * Cfg::STAGE_BYTES + Cfg::A_BYTES;
    wgmma_fence();
#pragma unroll
    for (int ks = 0; ks < 4; ks++) {
#pragma unroll
      for (int mb = 0; mb < MB; mb++) {
        const uint64_t da = make_desc(sa + mb * 8192 + ks * 32, 16, 1024, 1);
#pragma unroll
        for (int nb = 0; nb < NB; nb++) {
          const uint64_t db = make_desc(sb + nb * (BN / 64) * 8192 + ks * 2048, 8192, 1024, 1);
          WG<BN>::mma(acc[mb][nb], da, db, 1);
        }
      }
    }
    wgmma_commit();
    wgmma_wait<1>();
    if (kt > 0 && kt - 1 + STAGES < KT && (tid & 127) < NCL) {
      const uint32_t eb = sbar + 8 * (STAGES + (kt - 1) % STAGES);
      if constexpr (CN * CM > 1) {
        const int i = tid & 127;
        const uint32_t rank = i < CN ? cy * CN + i : ((i - CN + (i - CN >= cy ? 1 : 0)) * CN + cx);
        mbar_arrive_remote(eb, rank);
      } else mbar_arrive(eb);
    }
  }
  wgmma_wait<0>();
#pragma unroll
  for (int mb = 0; mb < MB; mb++)
#pragma unroll
    for (int nb = 0; nb < NB; nb++)
#pragma unroll
      for (int i = 0; i < BN / 2; i++) asm volatile("" : "+f"(acc[mb][nb][i]) :: "memory");
  if constexpr (CN * CM > 1) cluster_arrive();
  TS_MID(EPI == EPI_QKV ? 1 : EPI + 2, 1);
  pdl_wait();
  TS_MID(EPI == EPI_QKV ? 1 : EPI + 2, 2);
  named_bar(1, 256);
  constexpr int LDS = BN * 2 + 16;
  const int ctid = tid;

  if constexpr (EPI == EPI_QKV) {
    const int sec = n0 / DM;
    constexpr int lds = 264;
    __shared__ unsigned int s_kn[8];
    if (ctid < 8) s_kn[ctid] = 0u;
    if (blockIdx.x == 0 && blockIdx.y == 0 && ctid < 32) g_flag[ctid] = 0u;
    float2 cs[BN / 8];
#pragma unroll
    for (int j = 0; j < BN / 8; j++) cs[j] = *(const float2*)&g_cs_qkv[n0 + j * 8 + 2 * t];
#pragma unroll
    for (int mb = 0; mb < MB; mb++) {
      const int r0 = wg * (MB * 64) + mb * 64 + (warp & 3) * 16 + g;
      const float2 st0 = g_stat1[m0 + r0], st1 = g_stat1[m0 + r0 + 8];
      const float sc0 = sec == 0 ? st0.y * QSCALE : st0.y, sc1 = sec == 0 ? st1.y * QSCALE : st1.y;
#pragma unroll
      for (int j = 0; j < BN / 8; j++) {
        const float* a = &acc[mb][0][4 * j];
        *(uint32_t*)(sptr + r0 * lds + j * 16 + t * 4) = pack_bf16(fmaf(-st0.x, cs[j].x, a[0]) * sc0, fmaf(-st0.x, cs[j].y, a[1]) * sc0);
        *(uint32_t*)(sptr + (r0 + 8) * lds + j * 16 + t * 4) = pack_bf16(fmaf(-st1.x, cs[j].x, a[2]) * sc1, fmaf(-st1.x, cs[j].y, a[3]) * sc1);
      }
    }
    named_bar(1, 256);
    {
      const int cbase = n0 - sec * DM;
      const int hfirst = cbase / DH;
      const int j = m0 + ctid;
      uint8_t* dst = (uint8_t*)(sec == 0 ? g_q : (sec == 1 ? g_k : g_v)) + (size_t)(j >> 3) * (sec == 0 ? 512 : 384) + (j & 7) * 16;
      const uint8_t* row = sptr + ctid * 264;
#pragma unroll
      for (int i = 0; i < 8; i++) {
        const int hh = hfirst + i;
        const int cr = hh * DH - cbase;
        if (cr < BN) {
          uint2 v[5];
          bool in[5];
          float s = 0.f;
#pragma unroll
          for (int qd = 0; qd < 5; qd++) {
            const int c = cr + 4 * qd;
            in[qd] = c >= 0 && c < BN;
            v[qd] = in[qd] ? *(const uint2*)(row + c * 2) : make_uint2(0u, 0u);
            s += bf_lo(v[qd].x) * bf_lo(v[qd].x) + bf_hi(v[qd].x) * bf_hi(v[qd].x) + bf_lo(v[qd].y) * bf_lo(v[qd].y) + bf_hi(v[qd].y) * bf_hi(v[qd].y);
          }
          uint8_t* p = dst + (size_t)hh * (sec == 0 ? S_LEN * 64 : S_LEN * 48);
          if (in[0] && in[1]) st_g16(p, make_uint4(v[0].x, v[0].y, v[1].x, v[1].y));
          else if (in[0]) st_g8(p, v[0]);
          else if (in[1]) st_g8(p + 8, v[1]);
          if (in[2] && in[3]) st_g16(p + 128, make_uint4(v[2].x, v[2].y, v[3].x, v[3].y));
          else if (in[2]) st_g8(p + 128, v[2]);
          else if (in[3]) st_g8(p + 136, v[3]);
          if (in[4]) {
            st_g16(p + 256, make_uint4(v[4].x, v[4].y, sec == 0 ? 0u : 0x00003f80u, 0u));
            if (sec == 0) st_g16(p + 384, make_uint4(0u, 0u, 0u, 0u));
          }
          if (sec == 1) {
            const unsigned int mxb = __reduce_max_sync(~0u, __float_as_uint(s) & 0x7fffffffu);
            if (lane == 0) atomicMax(&s_kn[i], mxb);
          }
        }
      }
      if (sec == 1) {
        named_bar(1, 256);
        const int hh = hfirst + ctid;
        if (ctid < 8 && hh * DH < cbase + BN) {
          const bool starts_here = hh * DH >= cbase, ends_here = hh * DH + DH <= cbase + BN;
          const float v = __uint_as_float(s_kn[ctid]);
          float* o = &g_kn[(blockIdx.y * NH + hh) * 2];
          if (starts_here) { o[0] = v; if (ends_here) o[1] = 0.f; }
          else o[1] = v;
        }
      }
    }
  } else if constexpr (EPI == EPI_WO || EPI == EPI_DOWN) {
    const int r0 = wg * 64 + (warp & 3) * 16 + g;
#pragma unroll
    for (int j = 0; j < BN / 8; j++) {
      const float* a = &acc[0][0][4 * j];
      *(uint32_t*)(sptr + r0 * LDS + j * 16 + t * 4) = pack_bf16(a[0], a[1]);
      *(uint32_t*)(sptr + (r0 + 8) * LDS + j * 16 + t * 4) = pack_bf16(a[2], a[3]);
    }
    named_bar(1, 256);
#pragma unroll
    for (int i = 0; i < BM * (BN / 8) / 256; i++) {
      const int idx = i * 256 + ctid, r = idx / (BN / 8), c = idx % (BN / 8);
      const uint4 a = *(const uint4*)(sptr + r * LDS + c * 16);
      const size_t go = (size_t)(m0 + r) * DM + n0 + c * 8;
      const uint4 b = ld_g16(resid + go);
      uint4 o;
      o.x = pack_bf16(bf_lo(a.x) + bf_lo(b.x), bf_hi(a.x) + bf_hi(b.x));
      o.y = pack_bf16(bf_lo(a.y) + bf_lo(b.y), bf_hi(a.y) + bf_hi(b.y));
      o.z = pack_bf16(bf_lo(a.z) + bf_lo(b.z), bf_hi(a.z) + bf_hi(b.z));
      o.w = pack_bf16(bf_lo(a.w) + bf_lo(b.w), bf_hi(a.w) + bf_hi(b.w));
      st_g16(out + go, o);
      if constexpr (EPI == EPI_WO) {
        static_assert(BN == 64, "stats assume 8 lanes per row");
        const float f[8] = {bf_lo(o.x), bf_hi(o.x), bf_lo(o.y), bf_hi(o.y), bf_lo(o.z), bf_hi(o.z), bf_lo(o.w), bf_hi(o.w)};
        float s = 0.f;
#pragma unroll
        for (int k = 0; k < 8; k++) s += f[k];
        s += __shfl_xor_sync(~0u, s, 1); s += __shfl_xor_sync(~0u, s, 2); s += __shfl_xor_sync(~0u, s, 4);
        const float mu = s * (1.0f / 64.f);
        float q = 0.f;
#pragma unroll
        for (int k = 0; k < 8; k++) { const float d = f[k] - mu; q += d * d; }
        q += __shfl_xor_sync(~0u, q, 1); q += __shfl_xor_sync(~0u, q, 2); q += __shfl_xor_sync(~0u, q, 4);
        if (c == 0) g_part2[(m0 + r) * 10 + blockIdx.x] = make_float2(s, q);
      }
    }
  } else {
    const int r0 = wg * 64 + (warp & 3) * 16 + g;
    const float2* s_st = (const float2*)(sptr + STAGES * Cfg::STAGE_BYTES + 256);
    const float* s_cs = (const float*)(sptr + STAGES * Cfg::STAGE_BYTES + 256 + 1024);
    named_bar(2, 352);
    float2 st[2] = {s_st[r0], s_st[r0 + 8]};
#pragma unroll
    for (int j = 0; j < BN / 8; j++) {
      const float2 cg = *(const float2*)&s_cs[j * 8 + 2 * t], cu = *(const float2*)&s_cs[BN + j * 8 + 2 * t];
      const float* a = &acc[0][0][4 * j];
      const float* b = &acc[0][1][4 * j];
#pragma unroll
      for (int e = 0; e < 2; e++) {
        const float2 s_ = st[e];
        const uint32_t gp = pack_bf16(fmaf(-s_.x, cg.x, a[2 * e]) * s_.y, fmaf(-s_.x, cg.y, a[2 * e + 1]) * s_.y);
        const uint32_t up = pack_bf16(fmaf(-s_.x, cu.x, b[2 * e]) * s_.y, fmaf(-s_.x, cu.y, b[2 * e + 1]) * s_.y);
        uint32_t r;
        asm("{\n.reg .b32 z;\nmax.bf16x2 z, %1, %3;\nmul.rn.bf16x2 %0, z, %2;\n}" : "=r"(r) : "r"(gp), "r"(up), "r"(0u));
        *(uint32_t*)(sptr + (r0 + 8 * e) * LDS + j * 16 + t * 4) = r;
      }
    }
    named_bar(1, 256);
#pragma unroll
    for (int i = 0; i < BM * (BN / 8) / 256; i++) {
      const int idx = i * 256 + ctid, r = idx / (BN / 8), c = idx % (BN / 8);
      st_g16(out + (size_t)(m0 + r) * DFF + n0 + c * 8, *(const uint4*)(sptr + r * LDS + c * 16));
    }
  }
  if constexpr (CN * CM > 1) cluster_wait();
  TS_END(EPI == EPI_QKV ? 1 : EPI + 2);
}

constexpr int R_STAGES = 8;
constexpr int R_STAGE_BYTES = 16384 + 5 * 2048;
constexpr int R_BAR_OFF = R_STAGES * R_STAGE_BYTES;
constexpr int R_SMEM = R_BAR_OFF + 256 + 1024;
template <int KDIM, bool STATS>
__global__ void __launch_bounds__(288, 1) gemm_res_kernel(const __grid_constant__ CUtensorMap tmA, const __grid_constant__ CUtensorMap tmB,
                                                          const __nv_bfloat16* resid, __nv_bfloat16* out) {
  constexpr int KT = KDIM / 64;
  extern __shared__ uint8_t smem_raw[];
  const uint32_t sbase = (smem_u32(smem_raw) + 1023u) & ~1023u;
  uint8_t* sptr = smem_raw + (sbase - smem_u32(smem_raw));
  const uint32_t sbar = sbase + R_BAR_OFF;
  const int tid = threadIdx.x, warp = tid >> 5, lane = tid & 31;
  const int n0 = blockIdx.x * 80, m0 = blockIdx.y * 128;
  TS_BEGIN(STATS ? 3 : 5);
  if (tid == 0) {
    for (int i = 0; i < R_STAGES; i++) { mbar_init(sbar + 8 * i, 1); mbar_init(sbar + 8 * (R_STAGES + i), 2); }
    asm volatile("fence.mbarrier_init.release.cluster;" ::: "memory");
  }
  __syncthreads();
  pdl_launch();
  if (warp == 8) {
    if (lane == 0) {
      auto load_b = [&](int kt, int s) { tma_3d(sbase + s * R_STAGE_BYTES + 16384, &tmB, 0, kt * 64, blockIdx.x * 5, sbar + 8 * s); };
      for (int s = 0; s < R_STAGES; s++) { mbar_expect_tx(sbar + 8 * s, R_STAGE_BYTES); if (s < 3) load_b(s, s); }
      pdl_wait();
      for (int s = 0; s < R_STAGES; s++) { tma_2d(sbase + s * R_STAGE_BYTES, &tmA, s * 64, m0, sbar + 8 * s); if (s >= 3) load_b(s, s); }
      for (int kt = R_STAGES; kt < KT; kt++) {
        const int s = kt % R_STAGES;
        mbar_wait(sbar + 8 * (R_STAGES + s), ((kt / R_STAGES) - 1) & 1);
        mbar_expect_tx(sbar + 8 * s, R_STAGE_BYTES);
        tma_2d(sbase + s * R_STAGE_BYTES, &tmA, kt * 64, m0, sbar + 8 * s);
        load_b(kt, s);
      }
    }
    return;
  }
  const int wg = warp >> 2, g = lane >> 2, t = lane & 3;
  pdl_wait();
  uint4 rv[5];
#pragma unroll
  for (int i = 0; i < 5; i++) {
    const int idx = i * 256 + tid, r = idx / 10, c = idx % 10;
    rv[i] = ld_g16(resid + (size_t)(m0 + r) * DM + n0 + c * 8);
  }
  float acc[40];
#pragma unroll
  for (int i = 0; i < 40; i++) acc[i] = 0.f;
  for (int kt = 0; kt < KT; kt++) {
    const int s = kt % R_STAGES;
    mbar_wait(sbar + 8 * s, (kt / R_STAGES) & 1);
    if (kt == 0) TS_MID(STATS ? 3 : 5, 0);
    const uint32_t sa = sbase + s * R_STAGE_BYTES + wg * 8192;
    const uint32_t sb = sbase + s * R_STAGE_BYTES + 16384;
    wgmma_fence();
#pragma unroll
    for (int ks = 0; ks < 4; ks++)
      wgmma_ss_n80(acc, make_desc(sa + ks * 32, 16, 1024, 1), make_desc(sb + ks * 512, 2048, 256, 3), 1);
    wgmma_commit();
    wgmma_wait<1>();
    if (kt > 0 && kt - 1 + R_STAGES < KT && (tid & 127) == 0) mbar_arrive(sbar + 8 * (R_STAGES + (kt - 1) % R_STAGES));
  }
  wgmma_wait<0>();
#pragma unroll
  for (int i = 0; i < 40; i++) asm volatile("" : "+f"(acc[i]) :: "memory");
  TS_MID(STATS ? 3 : 5, 1);
  named_bar(1, 256);
  constexpr int LDS = 176;
  const int r0 = wg * 64 + (warp & 3) * 16 + g;
#pragma unroll
  for (int i = 0; i < 10; i++) {
    *(uint32_t*)(sptr + r0 * LDS + i * 16 + t * 4) = pack_bf16(acc[4 * i], acc[4 * i + 1]);
    *(uint32_t*)(sptr + (r0 + 8) * LDS + i * 16 + t * 4) = pack_bf16(acc[4 * i + 2], acc[4 * i + 3]);
  }
  named_bar(1, 256);
  TS_MID(STATS ? 3 : 5, 2);
#pragma unroll
  for (int i = 0; i < 5; i++) {
    const int idx = i * 256 + tid, r = idx / 10, c = idx % 10;
    const uint4 a = *(const uint4*)(sptr + r * LDS + c * 16);
    const uint4 b = rv[i];
    uint4 o;
    o.x = pack_bf16(bf_lo(a.x) + bf_lo(b.x), bf_hi(a.x) + bf_hi(b.x));
    o.y = pack_bf16(bf_lo(a.y) + bf_lo(b.y), bf_hi(a.y) + bf_hi(b.y));
    o.z = pack_bf16(bf_lo(a.z) + bf_lo(b.z), bf_hi(a.z) + bf_hi(b.z));
    o.w = pack_bf16(bf_lo(a.w) + bf_lo(b.w), bf_hi(a.w) + bf_hi(b.w));
    st_g16(out + (size_t)(m0 + r) * DM + n0 + c * 8, o);
    if constexpr (STATS) *(uint4*)(sptr + r * LDS + c * 16) = o;
  }
  TS_MID(STATS ? 3 : 5, 3);
  if constexpr (STATS) {
    named_bar(1, 256);
    const int r = tid >> 1, hf = tid & 1;
    float f[40];
#pragma unroll
    for (int i = 0; i < 5; i++) {
      const uint4 v = *(const uint4*)(sptr + r * LDS + hf * 80 + i * 16);
      f[8 * i] = bf_lo(v.x); f[8 * i + 1] = bf_hi(v.x); f[8 * i + 2] = bf_lo(v.y); f[8 * i + 3] = bf_hi(v.y);
      f[8 * i + 4] = bf_lo(v.z); f[8 * i + 5] = bf_hi(v.z); f[8 * i + 6] = bf_lo(v.w); f[8 * i + 7] = bf_hi(v.w);
    }
    float s = 0.f;
#pragma unroll
    for (int i = 0; i < 40; i++) s += f[i];
    s += __shfl_xor_sync(~0u, s, 1);
    const float mu = s * (1.0f / 80.f);
    float q = 0.f;
#pragma unroll
    for (int i = 0; i < 40; i++) { const float d = f[i] - mu; q += d * d; }
    q += __shfl_xor_sync(~0u, q, 1);
    if (hf == 0) g_part2[(m0 + r) * 8 + blockIdx.x] = make_float2(s, q);
  }
  TS_END(STATS ? 3 : 5);
}

constexpr int F_CST = 7, F_DST = 3, F_EST = 5;
constexpr int F_RS = 16384 + 5 * 2048;
constexpr int F_DS = 16384 + 6 * 8192;
constexpr int F_E_OFF = 53248;
constexpr int F_STG_OFF = F_DST * F_DS;
constexpr int F_BAR_OFF = F_STG_OFF + 128 * 176;
constexpr int F_VEC_OFF = F_BAR_OFF + 256;
constexpr int F_SMEM = F_VEC_OFF + 1024 + 1536 + 1024;

__device__ __forceinline__ void flag_wait(const unsigned int* f, unsigned int target) {
  unsigned int v, spins = 0;
  do { asm volatile("ld.acquire.gpu.global.u32 %0, [%1];" : "=r"(v) : "l"(f) : "memory"); } while (v < target && ++spins < (1u << 22));
  asm volatile("fence.proxy.async;" ::: "memory");
}
__device__ __forceinline__ void flag_signal(unsigned int* f) {
  asm volatile("fence.proxy.async;" ::: "memory");
  asm volatile("red.release.gpu.global.add.u32 [%0], 1;" :: "l"(f) : "memory");
}

template <bool STATS>
__device__ __forceinline__ void res_epilogue(float (&acc)[40], const uint4 (&rv)[5], uint8_t* stg, __nv_bfloat16* out, int m0, int n0, int tid, int bx) {
  constexpr int LDS = 176;
  const int warp = tid >> 5, lane = tid & 31;
  const int r0 = (warp >> 2) * 64 + (warp & 3) * 16 + (lane >> 2), t = lane & 3;
#pragma unroll
  for (int i = 0; i < 10; i++) {
    *(uint32_t*)(stg + r0 * LDS + i * 16 + t * 4) = pack_bf16(acc[4 * i], acc[4 * i + 1]);
    *(uint32_t*)(stg + (r0 + 8) * LDS + i * 16 + t * 4) = pack_bf16(acc[4 * i + 2], acc[4 * i + 3]);
  }
  named_bar(1, 256);
#pragma unroll
  for (int i = 0; i < 5; i++) {
    const int idx = i * 256 + tid, r = idx / 10, c = idx % 10;
    const uint4 a = *(const uint4*)(stg + r * LDS + c * 16);
    const uint4 b = rv[i];
    uint4 o;
    o.x = pack_bf16(bf_lo(a.x) + bf_lo(b.x), bf_hi(a.x) + bf_hi(b.x));
    o.y = pack_bf16(bf_lo(a.y) + bf_lo(b.y), bf_hi(a.y) + bf_hi(b.y));
    o.z = pack_bf16(bf_lo(a.z) + bf_lo(b.z), bf_hi(a.z) + bf_hi(b.z));
    o.w = pack_bf16(bf_lo(a.w) + bf_lo(b.w), bf_hi(a.w) + bf_hi(b.w));
    st_g16(out + (size_t)(m0 + r) * DM + n0 + c * 8, o);
    if constexpr (STATS) *(uint4*)(stg + r * LDS + c * 16) = o;
  }
  if constexpr (STATS) {
    named_bar(1, 256);
    const int r = tid >> 1, hf = tid & 1;
    float f[40];
#pragma unroll
    for (int i = 0; i < 5; i++) {
      const uint4 v = *(const uint4*)(stg + r * LDS + hf * 80 + i * 16);
      f[8 * i] = bf_lo(v.x); f[8 * i + 1] = bf_hi(v.x); f[8 * i + 2] = bf_lo(v.y); f[8 * i + 3] = bf_hi(v.y);
      f[8 * i + 4] = bf_lo(v.z); f[8 * i + 5] = bf_hi(v.z); f[8 * i + 6] = bf_lo(v.w); f[8 * i + 7] = bf_hi(v.w);
    }
    float s = 0.f;
#pragma unroll
    for (int i = 0; i < 40; i++) s += f[i];
    s += __shfl_xor_sync(~0u, s, 1);
    const float mu = s * (1.0f / 80.f);
    float q = 0.f;
#pragma unroll
    for (int i = 0; i < 40; i++) { const float d = f[i] - mu; q += d * d; }
    q += __shfl_xor_sync(~0u, q, 1);
    if (hf == 0) g_part2[(m0 + r) * 8 + bx] = make_float2(s, q);
  }
}

__global__ void __launch_bounds__(384, 1) post_kernel(const __grid_constant__ CUtensorMap tmO, const __grid_constant__ CUtensorMap tmWo,
                                                      const __grid_constant__ CUtensorMap tmH, const __grid_constant__ CUtensorMap tmWg,
                                                      const __grid_constant__ CUtensorMap tmWu, const __grid_constant__ CUtensorMap tmAct,
                                                      const __grid_constant__ CUtensorMap tmWd, const __nv_bfloat16* x, __nv_bfloat16* out) {
  extern __shared__ uint8_t smem_raw[];
  const uint32_t sbase = (smem_u32(smem_raw) + 1023u) & ~1023u;
  uint8_t* sptr = smem_raw + (sbase - smem_u32(smem_raw));
  const uint32_t bC = sbase + F_BAR_OFF, bD = bC + 16 * F_CST, bE = bD + 16 * F_DST;
  const int tid = threadIdx.x, warp = tid >> 5, lane = tid & 31;
  const int bx = blockIdx.x, rb = blockIdx.y, m0 = rb * 128, cx = bx & 1;
  TS_BEGIN(3);
  if (tid == 0) {
    for (int i = 0; i < F_CST; i++) { mbar_init(bC + 8 * i, 1); mbar_init(bC + 8 * (F_CST + i), 4); }
    for (int i = 0; i < F_DST; i++) { mbar_init(bD + 8 * i, 1); mbar_init(bD + 8 * (F_DST + i), 4); }
    for (int i = 0; i < F_EST; i++) { mbar_init(bE + 8 * i, 1); mbar_init(bE + 8 * (F_EST + i), 4); }
    asm volatile("fence.mbarrier_init.release.cluster;" ::: "memory");
  }
  __syncthreads();
  cluster_arrive(); cluster_wait();
  if (warp >= 8) {
    asm volatile("setmaxnreg.dec.sync.aligned.u32 40;");
    if (warp == 8) {
      if (lane == 0) {
        auto load_a = [&](const CUtensorMap* tm, uint32_t stage, int kt, uint32_t bar) { tma_2d_mc(stage + cx * 8192, tm, kt * 64, m0 + cx * 64, bar, (uint16_t)3); };
        for (int s = 0; s < F_CST; s++) { mbar_expect_tx(bC + 8 * s, F_RS); if (s < 3) tma_3d(sbase + s * F_RS + 16384, &tmWo, 0, s * 64, bx * 5, bC + 8 * s); }
        pdl_wait();
        for (int s = 0; s < F_CST; s++) { load_a(&tmO, sbase + s * F_RS, s, bC + 8 * s); if (s >= 3) tma_3d(sbase + s * F_RS + 16384, &tmWo, 0, s * 64, bx * 5, bC + 8 * s); }
        for (int kt = F_CST; kt < 10; kt++) {
          const int s = kt - F_CST;
          mbar_wait(bC + 8 * (F_CST + s), 0);
          mbar_expect_tx(bC + 8 * s, F_RS);
          load_a(&tmO, sbase + s * F_RS, kt, bC + 8 * s);
          tma_3d(sbase + s * F_RS + 16384, &tmWo, 0, kt * 64, bx * 5, bC + 8 * s);
        }
        auto load_bd = [&](int kt, int s) {
          tma_3d(sbase + s * F_DS + 16384, &tmWg, 0, kt * 64, bx * 3, bD + 8 * s);
          tma_3d(sbase + s * F_DS + 16384 + 3 * 8192, &tmWu, 0, kt * 64, bx * 3, bD + 8 * s);
        };
        for (int s = 0; s < F_DST; s++) { mbar_wait(bD + 8 * (F_DST + s), 0); mbar_expect_tx(bD + 8 * s, F_DS); load_bd(s, s); }
        flag_wait(&g_flag[rb], 8);
        for (int s = 0; s < F_DST; s++) load_a(&tmH, sbase + s * F_DS, s, bD + 8 * s);
        for (int kt = F_DST; kt < 10; kt++) {
          const int s = kt % F_DST;
          mbar_wait(bD + 8 * (F_DST + s), (kt / F_DST) & 1);
          mbar_expect_tx(bD + 8 * s, F_DS);
          load_a(&tmH, sbase + s * F_DS, kt, bD + 8 * s);
          load_bd(kt, s);
        }
        const uint32_t eb = sbase + F_E_OFF;
        for (int s = 0; s < F_EST; s++) { mbar_wait(bE + 8 * (F_EST + s), 0); mbar_expect_tx(bE + 8 * s, F_RS); tma_3d(eb + s * F_RS + 16384, &tmWd, 0, s * 64, bx * 5, bE + 8 * s); }
        flag_wait(&g_flag[16 + rb], 8);
        for (int s = 0; s < F_EST; s++) load_a(&tmAct, eb + s * F_RS, s, bE + 8 * s);
        for (int kt = F_EST; kt < 24; kt++) {
          const int s = kt % F_EST;
          mbar_wait(bE + 8 * (F_EST + s), (kt / F_EST) & 1);
          mbar_expect_tx(bE + 8 * s, F_RS);
          load_a(&tmAct, eb + s * F_RS, kt, bE + 8 * s);
          tma_3d(eb + s * F_RS + 16384, &tmWd, 0, kt * 64, bx * 5, bE + 8 * s);
        }
      }
    } else {
      float2* s_st = (float2*)(sptr + F_VEC_OFF);
      float* s_cs = (float*)(sptr + F_VEC_OFF + 1024);
      pdl_wait();
      for (int c = tid - 288; c < 192; c += 96) { s_cs[c] = g_cs_g[bx * 192 + c]; s_cs[192 + c] = g_cs_u[bx * 192 + c]; }
      flag_wait(&g_flag[rb], 8);
      for (int r = tid - 288; r < 128; r += 96) {
        const float2* pp = &g_part2[(m0 + r) * 8];
        float2 p[8];
        float s = 0.f;
#pragma unroll
        for (int i = 0; i < 8; i++) { asm volatile("ld.global.v2.f32 {%0, %1}, [%2];" : "=f"(p[i].x), "=f"(p[i].y) : "l"(pp + i) : "memory"); s += p[i].x; }
        const float mean = s * (1.0f / DM);
        float q = 0.f;
#pragma unroll
        for (int i = 0; i < 8; i++) { const float d = p[i].x * (1.0f / 80.f) - mean; q += p[i].y + 80.f * d * d; }
        s_st[r] = ln_finish(mean, q * (1.0f / DM));
      }
      __threadfence_block();
      asm volatile("bar.arrive 2, 352;" ::: "memory");
    }
    __syncwarp();
    cluster_arrive(); cluster_wait();
    return;
  }
  asm volatile("setmaxnreg.inc.sync.aligned.u32 232;");
  const int wg = warp >> 2, g = lane >> 2, t = lane & 3;
  auto release = [&](uint32_t bar) { if ((tid & 127) < 2) mbar_arrive_remote(bar, (tid & 127) ^ cx); };
  const int n0 = bx * 80;
  uint4 rv[5];
  pdl_wait();
  {
#pragma unroll
    for (int i = 0; i < 5; i++) { const int idx = i * 256 + tid, r = idx / 10, c = idx % 10; rv[i] = ld_g16(x + (size_t)(m0 + r) * DM + n0 + c * 8); }
    float acc[40];
#pragma unroll
    for (int i = 0; i < 40; i++) acc[i] = 0.f;
    for (int kt = 0; kt < 10; kt++) {
      const int s = kt % F_CST;
      mbar_wait(bC + 8 * s, kt / F_CST);
      if (kt == 0) TS_MID(3, 0);
      const uint32_t sa = sbase + s * F_RS + wg * 8192, sb = sbase + s * F_RS + 16384;
      wgmma_fence();
#pragma unroll
      for (int ks = 0; ks < 4; ks++) wgmma_ss_n80(acc, make_desc(sa + ks * 32, 16, 1024, 1), make_desc(sb + ks * 512, 2048, 256, 3), 1);
      wgmma_commit();
      wgmma_wait<1>();
      if (kt > 0 && kt - 1 + F_CST < 10) release(bC + 8 * (F_CST + kt - 1));
    }
    wgmma_wait<0>();
#pragma unroll
    for (int i = 0; i < 40; i++) asm volatile("" : "+f"(acc[i]) :: "memory");
    for (int s = 0; s < F_DST; s++) release(bD + 8 * (F_DST + s));
    TS_MID(3, 1);
    res_epilogue<true>(acc, rv, sptr + F_STG_OFF, g_h, m0, n0, tid, bx);
    __threadfence();
    named_bar(1, 256);
    if (tid == 0) flag_signal(&g_flag[rb]);
    TS_END(3);
  }
  {
    float acc[2][96];
#pragma unroll
    for (int i = 0; i < 96; i++) { acc[0][i] = 0.f; acc[1][i] = 0.f; }
    for (int kt = 0; kt < 10; kt++) {
      const int s = kt % F_DST;
      mbar_wait(bD + 8 * s, (kt / F_DST) & 1);
      if (kt == 0) TS_MID(4, 0);
      const uint32_t sa = sbase + s * F_DS + wg * 8192, sb = sbase + s * F_DS + 16384;
      wgmma_fence();
#pragma unroll
      for (int ks = 0; ks < 4; ks++) {
        const uint64_t da = make_desc(sa + ks * 32, 16, 1024, 1);
        wgmma_ss_n192(acc[0], da, make_desc(sb + ks * 2048, 8192, 1024, 1), 1);
        wgmma_ss_n192(acc[1], da, make_desc(sb + 3 * 8192 + ks * 2048, 8192, 1024, 1), 1);
      }
      wgmma_commit();
      wgmma_wait<1>();
      if (kt > 0 && kt - 1 + F_DST < 10) release(bD + 8 * (F_DST + (kt - 1) % F_DST));
    }
    wgmma_wait<0>();
#pragma unroll
    for (int i = 0; i < 96; i++) { asm volatile("" : "+f"(acc[0][i]) :: "memory"); asm volatile("" : "+f"(acc[1][i]) :: "memory"); }
    for (int s = 0; s < F_EST; s++) release(bE + 8 * (F_EST + s));
    TS_MID(4, 1);
    named_bar(1, 256);
    named_bar(2, 352);
    constexpr int LDS = 400;
    const float2* s_st = (const float2*)(sptr + F_VEC_OFF);
    const float* s_cs = (const float*)(sptr + F_VEC_OFF + 1024);
    const int r0 = wg * 64 + (warp & 3) * 16 + g;
    const float2 st[2] = {s_st[r0], s_st[r0 + 8]};
#pragma unroll
    for (int j = 0; j < 24; j++) {
      const float2 cg = *(const float2*)&s_cs[j * 8 + 2 * t], cu = *(const float2*)&s_cs[192 + j * 8 + 2 * t];
      const float* a = &acc[0][4 * j];
      const float* b = &acc[1][4 * j];
#pragma unroll
      for (int e = 0; e < 2; e++) {
        const float2 s_ = st[e];
        const uint32_t gp = pack_bf16(fmaf(-s_.x, cg.x, a[2 * e]) * s_.y, fmaf(-s_.x, cg.y, a[2 * e + 1]) * s_.y);
        const uint32_t up = pack_bf16(fmaf(-s_.x, cu.x, b[2 * e]) * s_.y, fmaf(-s_.x, cu.y, b[2 * e + 1]) * s_.y);
        uint32_t r;
        asm("{\n.reg .b32 z;\nmax.bf16x2 z, %1, %3;\nmul.rn.bf16x2 %0, z, %2;\n}" : "=r"(r) : "r"(gp), "r"(up), "r"(0u));
        *(uint32_t*)(sptr + (r0 + 8 * e) * LDS + j * 16 + t * 4) = r;
      }
    }
    named_bar(1, 256);
#pragma unroll
    for (int i = 0; i < 12; i++) {
      const int idx = i * 256 + tid, r = idx / 24, c = idx % 24;
      st_g16(g_act + (size_t)(m0 + r) * DFF + bx * 192 + c * 8, *(const uint4*)(sptr + r * LDS + c * 16));
    }
    __threadfence();
    named_bar(1, 256);
    if (tid == 0) flag_signal(&g_flag[16 + rb]);
    TS_END(4);
  }
  {
#pragma unroll
    for (int i = 0; i < 5; i++) { const int idx = i * 256 + tid, r = idx / 10, c = idx % 10; rv[i] = ld_g16(g_h + (size_t)(m0 + r) * DM + n0 + c * 8); }
    float acc[40];
#pragma unroll
    for (int i = 0; i < 40; i++) acc[i] = 0.f;
    const uint32_t eb = sbase + F_E_OFF;
    for (int kt = 0; kt < 24; kt++) {
      const int s = kt % F_EST;
      mbar_wait(bE + 8 * s, (kt / F_EST) & 1);
      if (kt == 0) TS_MID(5, 0);
      const uint32_t sa = eb + s * F_RS + wg * 8192, sb = eb + s * F_RS + 16384;
      wgmma_fence();
#pragma unroll
      for (int ks = 0; ks < 4; ks++) wgmma_ss_n80(acc, make_desc(sa + ks * 32, 16, 1024, 1), make_desc(sb + ks * 512, 2048, 256, 3), 1);
      wgmma_commit();
      wgmma_wait<1>();
      if (kt > 0 && kt - 1 + F_EST < 24) release(bE + 8 * (F_EST + (kt - 1) % F_EST));
    }
    wgmma_wait<0>();
#pragma unroll
    for (int i = 0; i < 40; i++) asm volatile("" : "+f"(acc[i]) :: "memory");
    cluster_arrive();
    TS_MID(5, 1);
    res_epilogue<false>(acc, rv, sptr + F_STG_OFF, out, m0, n0, tid, bx);
    cluster_wait();
    TS_END(5);
  }
}

#define POLY_NUM 5
__device__ __forceinline__ float ex2_poly(float x, int shl23) {
  const float MAGIC = 12582912.f;
  const float tt = x + MAGIC;
  const float f = x - (tt - MAGIC);
  float p = fmaf(0.0013276472454890609f, f, 0.009675540961325169f);
  p = fmaf(p, f, 0.05550713092088699f);
  p = fmaf(p, f, 0.24022120237350464f);
  p = fmaf(p, f, 0.6931469440460205f);
  p = fmaf(p, f, 1.0000001192092896f);
  return __int_as_float(__float_as_int(tt) * shl23 + __float_as_int(p));
}
constexpr int KV_BYTES = S_LEN * 48;
constexpr int ATT_SMEM = 2 * KV_BYTES + 256 + 32768;
constexpr int ATT_BODY = 8;

__global__ void __launch_bounds__(512, 1) attn_kernel(int shl23, const __nv_bfloat16* __restrict__ wg_, const __nv_bfloat16* __restrict__ wu_,
                                                      const __nv_bfloat16* __restrict__ wo_, const __nv_bfloat16* __restrict__ wd_) {
  extern __shared__ __align__(1024) uint8_t smem[];
  if (blockIdx.x >= 128) {
    pdl_launch();
    const int e = blockIdx.x - 128, half = threadIdx.x >> 8;
    if (threadIdx.x == 0) {
      for (int i = 0; i < 13; i++) asm volatile("cp.async.bulk.prefetch.L2.global [%0], %1;" :: "l"((const uint8_t*)wo_ + (e * 13 + i) * 16384 * 0 + (size_t)(e * 13 + i >= 50 ? 0 : (e * 13 + i)) * 16384), "r"(16384));
      for (int i = 0; i < 30; i++) asm volatile("cp.async.bulk.prefetch.L2.global [%0], %1;" :: "l"((const uint8_t*)wd_ + (size_t)(e * 30 + i) * 16384), "r"(16384));
    }
    float (*red)[65] = (float (*)[65])(smem + half * 16384);
    for (int b = e * 12 + half; b < e * 12 + 12; b += 2) {
      if (b < 24) colsum64(wg_, DFF, b * 64, g_cs_g, red, threadIdx.x & 255, 1 + half);
      else colsum64(wu_, DFF, (b - 24) * 64, g_cs_u, red, threadIdx.x & 255, 1 + half);
    }
    return;
  }
  const int h = blockIdx.x >> 2, qb = blockIdx.x & 3;
  const uint32_t sK = smem_u32(smem), sV = sK + KV_BYTES, sBar = sV + KV_BYTES;
  const int tid = threadIdx.x;
  TS_BEGIN(2);
  if (tid == 0) {
    for (int i = 0; i < 9; i++) mbar_init(sBar + 8 * i, 1);
    asm volatile("fence.mbarrier_init.release.cluster;" ::: "memory");
  }
  __syncthreads();
  pdl_launch();
  pdl_wait();
  TS_MID(2, 0);
  const uint8_t* gk = (const uint8_t*)(g_k + (size_t)h * S_LEN * 24);
  const uint8_t* gv = (const uint8_t*)(g_v + (size_t)h * S_LEN * 24);
  auto load_kv = [&](int i0, int i1) {
    for (int i = i0; i < i1; i++) {
      mbar_expect_tx(sBar + 8 * i, 2 * 12288);
      bulk_g2s(sK + i * 12288, gk + i * 12288, 12288, sBar + 8 * i);
      bulk_g2s(sV + i * 12288, gv + i * 12288, 12288, sBar + 8 * i);
    }
  };
  if (tid == 0) {
    mbar_expect_tx(sBar + 64, 32768);
    bulk_g2s(sBar + 256, (const uint8_t*)g_q + ((size_t)h * S_LEN + qb * 512) * 64, 32768, sBar + 64);
    load_kv(0, 2);
  }
  float ka = 0.f, kb = 0.f;
#pragma unroll
  for (int i = 0; i < 8; i++) {
    const float2 v = *(const float2*)&g_kn[(i * NH + h) * 2];
    ka = (v.x > ka || v.x != v.x) ? v.x : ka;
    kb = (v.y > kb || v.y != v.y) ? v.y : kb;
  }
  bool fast;
  {
    const float kn = sqrtf(ka + kb);
    mbar_wait(sBar + 64, 0);
    if (tid == 0) load_kv(2, 8);
    uint8_t* qrow = smem + 2 * KV_BYTES + 256 + (tid >> 3) * 512 + (tid & 7) * 16;
    const uint4 c0 = *(const uint4*)qrow, c1 = *(const uint4*)(qrow + 128);
    const uint2 c2 = *(const uint2*)(qrow + 256);
    auto sq = [](uint32_t u) { const float a = bf_lo(u), b = bf_hi(u); return a * a + b * b; };
    const float n2 = sq(c0.x) + sq(c0.y) + sq(c0.z) + sq(c0.w) + sq(c1.x) + sq(c1.y) + sq(c1.z) + sq(c1.w) + sq(c2.x) + sq(c2.y);
    const float m = ceilf(sqrtf(n2) * kn * 1.001f) + 1.f;
    fast = __syncthreads_or(!(m <= 62.f)) == 0;
    if (fast) *(uint32_t*)(qrow + 256 + 8) = pack_bf16(-m, 0.f);
    asm volatile("fence.proxy.async.shared::cta;" ::: "memory");
    __syncthreads();
  }
  auto write_out = [&](float (&O)[12], int it) {
    uint32_t tid2;
    asm volatile("mov.u32 %0, %%tid.x;" : "=r"(tid2));
    const int lane2 = tid2 & 31, t2 = lane2 & 3;
    const int qq = (blockIdx.x & 3) * 512 + (it * 4 + (tid2 >> 7)) * 64 + ((tid2 >> 5) & 3) * 16 + (lane2 >> 2);
    const float l0 = __shfl_sync(~0u, O[8], (lane2 & ~3) | 2), l1 = __shfl_sync(~0u, O[10], (lane2 & ~3) | 2);
    const float r0 = 1.f / l0, r1 = 1.f / l1;
    uint32_t* o0 = (uint32_t*)(g_o + (size_t)qq * DM + (blockIdx.x >> 2) * DH);
    uint32_t* o1 = o0 + 8 * DM / 2;
    o0[t2] = pack_bf16(O[0] * r0, O[1] * r0); o1[t2] = pack_bf16(O[2] * r1, O[3] * r1);
    o0[t2 + 4] = pack_bf16(O[4] * r0, O[5] * r0); o1[t2 + 4] = pack_bf16(O[6] * r1, O[7] * r1);
    if (t2 < 2) { o0[t2 + 8] = pack_bf16(O[8] * r0, O[9] * r0); o1[t2 + 8] = pack_bf16(O[10] * r1, O[11] * r1); }
  };
  TS_MID(2, 1);
  if (fast) {
#pragma unroll 1
    for (int it = 0; it < 2; it++) {
      const uint64_t dq = make_desc(sBar + 256 + (it * 4 + (tid >> 7)) * 4096, 128, 512, 0);
      float O[12];
#pragma unroll
      for (int i = 0; i < 12; i++) { O[i] = 0.f; asm volatile("" : "+f"(O[i]) :: "memory"); }
      float S[2][32];
      uint32_t P[16];
#pragma unroll 1
      for (int jb = 0; jb < 32 / ATT_BODY; jb++) {
        if (it == 0) { for (int c = 0; c < ATT_BODY / 4; c++) mbar_wait(sBar + 8 * (jb * (ATT_BODY / 4) + c), 0); }
        const uint64_t dk0 = make_desc(sK + jb * ATT_BODY * 8 * 384, 128, 384, 0);
        const uint64_t dv0 = make_desc(sV + jb * ATT_BODY * 8 * 384, 384, 128, 0);
        wgmma_fence();
        wgmma_ss_n64_k(S[0], dq, dk0, 0);
        wgmma_ss_n64_k(S[0], dq + (256 >> 4), dk0 + (256 >> 4), 1);
        wgmma_commit();
#pragma unroll
        for (int u = 0; u < ATT_BODY; u++) {
          if (u + 1 < ATT_BODY) {
            const uint64_t dk = dk0 + (((u + 1) * 8 * 384) >> 4);
            wgmma_fence();
            wgmma_ss_n64_k(S[(u + 1) & 1], dq, dk, 0);
            wgmma_ss_n64_k(S[(u + 1) & 1], dq + (256 >> 4), dk + (256 >> 4), 1);
            wgmma_commit();
          }
          if (u == 0 || u == ATT_BODY - 1) wgmma_wait<1>(); else wgmma_wait<2>();
#pragma unroll
          for (int i = 0; i < 32; i++) asm volatile("" : "+f"(S[u & 1][i]) :: "memory");
          const uint64_t dv = dv0 + ((u * 8 * 384) >> 4);
#pragma unroll
          for (int hf = 0; hf < 2; hf++) {
            if (hf == 1 && u > 0) { if (u == ATT_BODY - 1) wgmma_wait<1>(); else wgmma_wait<2>(); }
#pragma unroll
            for (int i = hf * 8; i < hf * 8 + 8; i++) {
              const bool usepoly = ((i + 1) * POLY_NUM / 16) != (i * POLY_NUM / 16);
              float a, b;
              if (usepoly) { a = ex2_poly(S[u & 1][2 * i], shl23); b = ex2_poly(S[u & 1][2 * i + 1], shl23); }
              else { a = ex2_mufu(S[u & 1][2 * i]); b = ex2_mufu(S[u & 1][2 * i + 1]); }
              P[i] = pack_bf16(a, b);
            }
            wgmma_fence();
#pragma unroll
            for (int ks = hf * 2; ks < hf * 2 + 2; ks++)
              wgmma_rs_n24_tb(O, P[4 * ks], P[4 * ks + 1], P[4 * ks + 2], P[4 * ks + 3], dv + ((ks * 768) >> 4), 1);
            wgmma_commit();
          }
        }
        wgmma_wait<0>();
      }
#pragma unroll
      for (int i = 0; i < 12; i++) asm volatile("" : "+f"(O[i]) :: "memory");
      write_out(O, it);
      if (it == 0) TS_MID(2, 2);
    }
  } else {
#pragma unroll 1
    for (int it = 0; it < 2; it++) {
      const uint64_t dq = make_desc(sBar + 256 + (it * 4 + (tid >> 7)) * 4096, 128, 512, 0);
      float O[12];
#pragma unroll
      for (int i = 0; i < 12; i++) { O[i] = 0.f; asm volatile("" : "+f"(O[i]) :: "memory"); }
      float S[32];
      float mx0 = -INFINITY, mx1 = -INFINITY;
#pragma unroll 1
      for (int j = 0; j < 32; j++) {
        if (it == 0 && (j & 3) == 0) mbar_wait(sBar + 8 * (j >> 2), 0);
        const uint64_t dk = make_desc(sK + j * 8 * 384, 128, 384, 0);
        wgmma_fence();
        wgmma_ss_n64_k(S, dq, dk, 0);
        wgmma_ss_n64_k(S, dq + (256 >> 4), dk + (256 >> 4), 1);
        wgmma_commit();
        wgmma_wait<0>();
#pragma unroll
        for (int i = 0; i < 8; i++) {
          mx0 = fmaxf(mx0, fmaxf(S[4 * i], S[4 * i + 1]));
          mx1 = fmaxf(mx1, fmaxf(S[4 * i + 2], S[4 * i + 3]));
        }
      }
      mx0 = fmaxf(mx0, __shfl_xor_sync(~0u, mx0, 1)); mx0 = fmaxf(mx0, __shfl_xor_sync(~0u, mx0, 2));
      mx1 = fmaxf(mx1, __shfl_xor_sync(~0u, mx1, 1)); mx1 = fmaxf(mx1, __shfl_xor_sync(~0u, mx1, 2));
#pragma unroll 1
      for (int j = 0; j < 32; j++) {
        const uint64_t dk = make_desc(sK + j * 8 * 384, 128, 384, 0);
        wgmma_fence();
        wgmma_ss_n64_k(S, dq, dk, 0);
        wgmma_ss_n64_k(S, dq + (256 >> 4), dk + (256 >> 4), 1);
        wgmma_commit();
        wgmma_wait<0>();
        uint32_t P[16];
#pragma unroll
        for (int i = 0; i < 8; i++) {
          P[2 * i] = pack_bf16(ex2_mufu(S[4 * i] - mx0), ex2_mufu(S[4 * i + 1] - mx0));
          P[2 * i + 1] = pack_bf16(ex2_mufu(S[4 * i + 2] - mx1), ex2_mufu(S[4 * i + 3] - mx1));
        }
        wgmma_fence();
        const uint64_t dv = make_desc(sV + j * 8 * 384, 384, 128, 0);
#pragma unroll
        for (int ks = 0; ks < 4; ks++)
          wgmma_rs_n24_tb(O, P[4 * ks], P[4 * ks + 1], P[4 * ks + 2], P[4 * ks + 3], dv + ((ks * 768) >> 4), 1);
        wgmma_commit();
        wgmma_wait<0>();
      }
#pragma unroll
      for (int i = 0; i < 12; i++) asm volatile("" : "+f"(O[i]) :: "memory");
      write_out(O, it);
    }
  }
  TS_END(2);
}

typedef CUresult (*EncodeFn)(CUtensorMap*, CUtensorMapDataType, cuuint32_t, void*, const cuuint64_t*, const cuuint64_t*, const cuuint32_t*,
                             const cuuint32_t*, CUtensorMapInterleave, CUtensorMapSwizzle, CUtensorMapL2promotion, CUtensorMapFloatOOBfill);
static EncodeFn get_encode() {
  static EncodeFn fn = nullptr;
  if (!fn) {
    void* p = nullptr; cudaDriverEntryPointQueryResult st;
    cudaGetDriverEntryPoint("cuTensorMapEncodeTiled", &p, cudaEnableDefault, &st);
    fn = (EncodeFn)p;
  }
  return fn;
}
static CUtensorMap make_map(const void* ptr, int rows, int cols, int box_rows, int box_cols = 64) {
  CUtensorMap m;
  cuuint64_t dims[2] = {(cuuint64_t)cols, (cuuint64_t)rows};
  cuuint64_t strides[1] = {(cuuint64_t)cols * 2};
  cuuint32_t box[2] = {(cuuint32_t)box_cols, (cuuint32_t)box_rows};
  cuuint32_t es[2] = {1, 1};
  get_encode()(&m, CU_TENSOR_MAP_DATA_TYPE_BFLOAT16, 2, const_cast<void*>(ptr), dims, strides, box, es, CU_TENSOR_MAP_INTERLEAVE_NONE,
               box_cols == 64 ? CU_TENSOR_MAP_SWIZZLE_128B : (box_cols == 32 ? CU_TENSOR_MAP_SWIZZLE_64B : CU_TENSOR_MAP_SWIZZLE_32B), CU_TENSOR_MAP_L2_PROMOTION_L2_128B, CU_TENSOR_MAP_FLOAT_OOB_FILL_NONE);
  return m;
}
static CUtensorMap make_map_w(const void* ptr, int rows, int cols, int bc, int nblk) {
  CUtensorMap m;
  cuuint64_t dims[3] = {(cuuint64_t)bc, (cuuint64_t)rows, (cuuint64_t)(cols / bc)};
  cuuint64_t strides[2] = {(cuuint64_t)cols * 2, (cuuint64_t)bc * 2};
  cuuint32_t box[3] = {(cuuint32_t)bc, 64, (cuuint32_t)nblk};
  cuuint32_t es[3] = {1, 1, 1};
  get_encode()(&m, CU_TENSOR_MAP_DATA_TYPE_BFLOAT16, 3, const_cast<void*>(ptr), dims, strides, box, es, CU_TENSOR_MAP_INTERLEAVE_NONE,
               bc == 64 ? CU_TENSOR_MAP_SWIZZLE_128B : (bc == 32 ? CU_TENSOR_MAP_SWIZZLE_64B : CU_TENSOR_MAP_SWIZZLE_32B),
               CU_TENSOR_MAP_L2_PROMOTION_L2_128B, CU_TENSOR_MAP_FLOAT_OOB_FILL_NONE);
  return m;
}
template <typename... KArgs, typename... Args>
static void launch(void (*kern)(KArgs...), dim3 grid, dim3 block, size_t smem, bool pdl, dim3 cluster, Args... args) {
  cudaLaunchConfig_t cfg = {};
  cfg.gridDim = grid; cfg.blockDim = block; cfg.dynamicSmemBytes = smem; cfg.stream = cudaStreamPerThread;
  cudaLaunchAttribute at[2];
  int na = 0;
  if (pdl) { at[na].id = cudaLaunchAttributeProgrammaticStreamSerialization; at[na].val.programmaticStreamSerializationAllowed = 1; na++; }
  if (cluster.x * cluster.y > 1) { at[na].id = cudaLaunchAttributeClusterDimension; at[na].val.clusterDim.x = cluster.x; at[na].val.clusterDim.y = cluster.y; at[na].val.clusterDim.z = 1; na++; }
  cfg.attrs = at; cfg.numAttrs = na;
  cudaLaunchKernelEx(&cfg, kern, KArgs(args)...);
}

extern "C" void kernel_launch(void* const* d_in, const int* in_sizes, int n_in, void* d_out, int out_size) {
  const __nv_bfloat16* x = (const __nv_bfloat16*)d_in[0];
  const __nv_bfloat16* wqkv = (const __nv_bfloat16*)d_in[1];
  const __nv_bfloat16* wo = (const __nv_bfloat16*)d_in[2];
  const __nv_bfloat16* wgate = (const __nv_bfloat16*)d_in[4];
  const __nv_bfloat16* wup = (const __nv_bfloat16*)d_in[5];
  const __nv_bfloat16* wdown = (const __nv_bfloat16*)d_in[6];
  __nv_bfloat16* out = (__nv_bfloat16*)d_out;
  void *p_o, *p_h, *p_act;
  cudaGetSymbolAddress(&p_o, g_o); cudaGetSymbolAddress(&p_h, g_h); cudaGetSymbolAddress(&p_act, g_act);

#define A_CN 1
#define A_CM 1
#define D_CN 1
#define D_CM 1
  auto kA = gemm_kernel<256, 128, 1, DM, 4, EPI_QKV, 1, A_CN, A_CM>;
  auto kC = gemm_res_kernel<DM, true>;
  auto kD = gemm_kernel<128, 192, 2, DM, 3, EPI_GLU, 1, D_CN, D_CM>;
  auto kE = gemm_res_kernel<DFF, false>;
  constexpr int smA = GemmCfg<256, 128, 1, 4>::SMEM, smC = R_SMEM, smD = GemmCfg<128, 192, 2, 3>::SMEM;
  cudaFuncSetAttribute(kA, cudaFuncAttributeMaxDynamicSharedMemorySize, smA);
  cudaFuncSetAttribute(kC, cudaFuncAttributeMaxDynamicSharedMemorySize, smC);
  cudaFuncSetAttribute(kD, cudaFuncAttributeMaxDynamicSharedMemorySize, smD);
  cudaFuncSetAttribute(kE, cudaFuncAttributeMaxDynamicSharedMemorySize, smC);
  cudaFuncSetAttribute(attn_kernel, cudaFuncAttributeMaxDynamicSharedMemorySize, ATT_SMEM);

  const CUtensorMap tm_x = make_map(x, S_LEN, DM, 256), tm_wqkv = make_map_w(wqkv, DM, 3 * DM, 64, 2);
  const CUtensorMap tm_o = make_map(p_o, S_LEN, DM, 128), tm_wo = make_map_w(wo, DM, DM, 16, 5);
  const CUtensorMap tm_h = make_map(p_h, S_LEN, DM, 128), tm_wg = make_map_w(wgate, DM, DFF, 64, 3), tm_wu = make_map_w(wup, DM, DFF, 64, 3);
  const CUtensorMap tm_act = make_map(p_act, S_LEN, DFF, 128), tm_wd = make_map_w(wdown, DFF, DM, 16, 5);

  launch(pre_kernel, dim3(12), dim3(1024), 0, false, dim3(1, 1), x, wqkv);
  launch(kA, dim3(15, 8), dim3(288), smA, true, dim3(A_CN, A_CM), tm_x, tm_wqkv, tm_wqkv, x, (__nv_bfloat16*)wqkv);
  launch(attn_kernel, dim3(132), dim3(512), ATT_SMEM, true, dim3(1, 1), 0x800000, wgate, wup, wo, wdown);
  cudaFuncSetAttribute(post_kernel, cudaFuncAttributeMaxDynamicSharedMemorySize, F_SMEM);
  const CUtensorMap tm_o2 = make_map(p_o, S_LEN, DM, 64), tm_h2 = make_map(p_h, S_LEN, DM, 64), tm_act2 = make_map(p_act, S_LEN, DFF, 64);
  launch(post_kernel, dim3(8, 16), dim3(384), F_SMEM, true, dim3(2, 1), tm_o2, tm_wo, tm_h2, tm_wg, tm_wu, tm_act2, tm_wd, x, out);
}
```

```cpp
#include <cuda_runtime.h>
#include <cuda_bf16.h>
#include <cuda.h>
#include <stdint.h>

constexpr int S_LEN = 2048, DM = 640, NH = 32, DH = 20, DFF = 1536;

__device__ __align__(1024) __nv_bfloat16 g_q[NH * S_LEN * 32];
__device__ __align__(1024) __nv_bfloat16 g_k[NH * S_LEN * 24];
__device__ __align__(1024) __nv_bfloat16 g_v[NH * S_LEN * 24];
__device__ __align__(1024) __nv_bfloat16 g_o[S_LEN * DM];
__device__ __align__(1024) __nv_bfloat16 g_h[S_LEN * DM];
__device__ __align__(1024) __nv_bfloat16 g_act[S_LEN * DFF];
__device__ float g_kn[8 * NH * 2];
__device__ float2 g_stat1[S_LEN];
__device__ float g_cs_qkv[3 * DM];
__device__ float g_cs_g[DFF];
__device__ float g_cs_u[DFF];
__device__ unsigned int g_flag[32];
__device__ float2 g_part2[S_LEN * 10];

#define TS_BEGIN(k)
#define TS_END(k)
#define TS_MID(k, i)
__device__ __forceinline__ uint32_t smem_u32(const void* p) { return (uint32_t)__cvta_generic_to_shared(p); }
__device__ __forceinline__ void mbar_init(uint32_t bar, uint32_t cnt) { asm volatile("mbarrier.init.shared::cta.b64 [%0], %1;" :: "r"(bar), "r"(cnt)); }
__device__ __forceinline__ void mbar_expect_tx(uint32_t bar, uint32_t bytes) { asm volatile("mbarrier.arrive.expect_tx.shared::cta.b64 _, [%0], %1;" :: "r"(bar), "r"(bytes) : "memory"); }
__device__ __forceinline__ void mbar_arrive(uint32_t bar) { asm volatile("mbarrier.arrive.shared::cta.b64 _, [%0];" :: "r"(bar) : "memory"); }
__device__ __forceinline__ void mbar_wait(uint32_t bar, uint32_t parity) {
  uint32_t done;
  uint32_t spins = 0;
  do {
    asm volatile("{\n.reg .pred P1;\nmbarrier.try_wait.parity.shared::cta.b64 P1, [%1], %2;\nselp.u32 %0, 1, 0, P1;\n}" : "=r"(done) : "r"(bar), "r"(parity) : "memory");
  } while (!done && ++spins < (1u << 24));
}
__device__ __forceinline__ void bulk_g2s(uint32_t dst, const void* src, uint32_t bytes, uint32_t bar) {
  asm volatile("cp.async.bulk.shared::cluster.global.mbarrier::complete_tx::bytes [%0], [%1], %2, [%3];" :: "r"(dst), "l"(src), "r"(bytes), "r"(bar) : "memory");
}
__device__ __forceinline__ void tma_2d(uint32_t dst, const CUtensorMap* tm, int c0, int c1, uint32_t bar) {
  asm volatile("cp.async.bulk.tensor.2d.shared::cluster.global.mbarrier::complete_tx::bytes [%0], [%1, {%3, %4}], [%2];"
               :: "r"(dst), "l"(tm), "r"(bar), "r"(c0), "r"(c1) : "memory");
}
__device__ __forceinline__ void tma_3d(uint32_t dst, const CUtensorMap* tm, int c0, int c1, int c2, uint32_t bar) {
  asm volatile("cp.async.bulk.tensor.3d.shared::cluster.global.mbarrier::complete_tx::bytes [%0], [%1, {%3, %4, %5}], [%2];"
               :: "r"(dst), "l"(tm), "r"(bar), "r"(c0), "r"(c1), "r"(c2) : "memory");
}
__device__ __forceinline__ void tma_2d_mc(uint32_t dst, const CUtensorMap* tm, int c0, int c1, uint32_t bar, uint16_t mask) {
  asm volatile("cp.async.bulk.tensor.2d.shared::cluster.global.mbarrier::complete_tx::bytes.multicast::cluster [%0], [%1, {%3, %4}], [%2], %5;"
               :: "r"(dst), "l"(tm), "r"(bar), "r"(c0), "r"(c1), "h"(mask) : "memory");
}
__device__ __forceinline__ void mbar_arrive_remote(uint32_t bar, uint32_t rank) {
  asm volatile("{\n.reg .b32 ra;\nmapa.shared::cluster.u32 ra, %0, %1;\nmbarrier.arrive.release.cluster.shared::cluster.b64 _, [ra];\n}" :: "r"(bar), "r"(rank) : "memory");
}
__device__ __forceinline__ void cluster_arrive() { asm volatile("barrier.cluster.arrive.release.aligned;" ::: "memory"); }
__device__ __forceinline__ void cluster_wait() { asm volatile("barrier.cluster.wait.acquire.aligned;" ::: "memory"); }
__device__ __forceinline__ void wgmma_fence() { asm volatile("wgmma.fence.sync.aligned;" ::: "memory"); }
__device__ __forceinline__ void wgmma_commit() { asm volatile("wgmma.commit_group.sync.aligned;" ::: "memory"); }
template <int N> __device__ __forceinline__ void wgmma_wait() { asm volatile("wgmma.wait_group.sync.aligned %0;" :: "n"(N) : "memory"); }
__device__ __forceinline__ void pdl_wait() { asm volatile("griddepcontrol.wait;" ::: "memory"); }
__device__ __forceinline__ void pdl_launch() { asm volatile("griddepcontrol.launch_dependents;" ::: "memory"); }
__device__ __forceinline__ void named_bar(int id, int n) { asm volatile("bar.sync %0, %1;" :: "r"(id), "r"(n) : "memory"); }
__device__ __forceinline__ uint64_t make_desc(uint32_t addr, uint32_t lbo, uint32_t sbo, uint32_t swz) {
  return (uint64_t)((addr & 0x3FFFF) >> 4) | ((uint64_t)(lbo >> 4) << 16) | ((uint64_t)(sbo >> 4) << 32) | ((uint64_t)swz << 62);
}
__device__ __forceinline__ void st_g16(void* p, uint4 v) { asm volatile("st.global.v4.b32 [%0], {%1, %2, %3, %4};" :: "l"(p), "r"(v.x), "r"(v.y), "r"(v.z), "r"(v.w) : "memory"); }
__device__ __forceinline__ void st_g8(void* p, uint2 v) { asm volatile("st.global.v2.b32 [%0], {%1, %2};" :: "l"(p), "r"(v.x), "r"(v.y) : "memory"); }
__device__ __forceinline__ uint4 ld_g16(const void* p) { uint4 v; asm volatile("ld.global.v4.b32 {%0, %1, %2, %3}, [%4];" : "=r"(v.x), "=r"(v.y), "=r"(v.z), "=r"(v.w) : "l"(p) : "memory"); return v; }
__device__ __forceinline__ uint32_t pack_bf16(float lo, float hi) { uint32_t r; asm("cvt.rn.bf16x2.f32 %0, %1, %2;" : "=r"(r) : "f"(hi), "f"(lo)); return r; }
__device__ __forceinline__ float bf_lo(uint32_t u) { return __uint_as_float(u << 16); }
__device__ __forceinline__ float bf_hi(uint32_t u) { return __uint_as_float(u & 0xffff0000u); }
__device__ __forceinline__ float bf_round(float x) { return __bfloat162float(__float2bfloat16_rn(x)); }
__device__ __forceinline__ float ex2_mufu(float x) { float y; asm("ex2.approx.ftz.f32 %0, %1;" : "=f"(y) : "f"(x)); return y; }

__device__ __forceinline__ void wgmma_ss_n80(float (&d)[40], uint64_t da, uint64_t db, int scale_d) {
  asm volatile("{\n.reg .pred p;\nsetp.ne.b32 p, %42, 0;\n"
    "wgmma.mma_async.sync.aligned.m64n80k16.f32.bf16.bf16 {%0,%1,%2,%3,%4,%5,%6,%7,%8,%9,%10,%11,%12,%13,%14,%15,%16,%17,%18,%19,%20,%21,%22,%23,%24,%25,%26,%27,%28,%29,%30,%31,%32,%33,%34,%35,%36,%37,%38,%39}, %40, %41, p, 1, 1, 0, 1;\n}\n"
    : "+f"(d[0]),"+f"(d[1]),"+f"(d[2]),"+f"(d[3]),"+f"(d[4]),"+f"(d[5]),"+f"(d[6]),"+f"(d[7]),"+f"(d[8]),"+f"(d[9]),"+f"(d[10]),"+f"(d[11]),"+f"(d[12]),"+f"(d[13]),"+f"(d[14]),"+f"(d[15]),"+f"(d[16]),"+f"(d[17]),"+f"(d[18]),"+f"(d[19]),"+f"(d[20]),"+f"(d[21]),"+f"(d[22]),"+f"(d[23]),"+f"(d[24]),"+f"(d[25]),"+f"(d[26]),"+f"(d[27]),"+f"(d[28]),"+f"(d[29]),"+f"(d[30]),"+f"(d[31]),"+f"(d[32]),"+f"(d[33]),"+f"(d[34]),"+f"(d[35]),"+f"(d[36]),"+f"(d[37]),"+f"(d[38]),"+f"(d[39])
    : "l"(da), "l"(db), "r"(scale_d));
}
__device__ __forceinline__ void wgmma_ss_n128(float (&d)[64], uint64_t da, uint64_t db, int scale_d) {
  asm volatile("{\n.reg .pred p;\nsetp.ne.b32 p, %66, 0;\n"
    "wgmma.mma_async.sync.aligned.m64n128k16.f32.bf16.bf16 {%0,%1,%2,%3,%4,%5,%6,%7,%8,%9,%10,%11,%12,%13,%14,%15,%16,%17,%18,%19,%20,%21,%22,%23,%24,%25,%26,%27,%28,%29,%30,%31,%32,%33,%34,%35,%36,%37,%38,%39,%40,%41,%42,%43,%44,%45,%46,%47,%48,%49,%50,%51,%52,%53,%54,%55,%56,%57,%58,%59,%60,%61,%62,%63}, %64, %65, p, 1, 1, 0, 1;\n}\n"
    : "+f"(d[0]),"+f"(d[1]),"+f"(d[2]),"+f"(d[3]),"+f"(d[4]),"+f"(d[5]),"+f"(d[6]),"+f"(d[7]),"+f"(d[8]),"+f"(d[9]),"+f"(d[10]),"+f"(d[11]),"+f"(d[12]),"+f"(d[13]),"+f"(d[14]),"+f"(d[15]),"+f"(d[16]),"+f"(d[17]),"+f"(d[18]),"+f"(d[19]),"+f"(d[20]),"+f"(d[21]),"+f"(d[22]),"+f"(d[23]),"+f"(d[24]),"+f"(d[25]),"+f"(d[26]),"+f"(d[27]),"+f"(d[28]),"+f"(d[29]),"+f"(d[30]),"+f"(d[31]),"+f"(d[32]),"+f"(d[33]),"+f"(d[34]),"+f"(d[35]),"+f"(d[36]),"+f"(d[37]),"+f"(d[38]),"+f"(d[39]),"+f"(d[40]),"+f"(d[41]),"+f"(d[42]),"+f"(d[43]),"+f"(d[44]),"+f"(d[45]),"+f"(d[46]),"+f"(d[47]),"+f"(d[48]),"+f"(d[49]),"+f"(d[50]),"+f"(d[51]),"+f"(d[52]),"+f"(d[53]),"+f"(d[54]),"+f"(d[55]),"+f"(d[56]),"+f"(d[57]),"+f"(d[58]),"+f"(d[59]),"+f"(d[60]),"+f"(d[61]),"+f"(d[62]),"+f"(d[63])
    : "l"(da), "l"(db), "r"(scale_d));
}
__device__ __forceinline__ void wgmma_ss_n192(float (&d)[96], uint64_t da, uint64_t db, int scale_d) {
  asm volatile("{\n.reg .pred p;\nsetp.ne.b32 p, %98, 0;\n"
    "wgmma.mma_async.sync.aligned.m64n192k16.f32.bf16.bf16 {%0,%1,%2,%3,%4,%5,%6,%7,%8,%9,%10,%11,%12,%13,%14,%15,%16,%17,%18,%19,%20,%21,%22,%23,%24,%25,%26,%27,%28,%29,%30,%31,%32,%33,%34,%35,%36,%37,%38,%39,%40,%41,%42,%43,%44,%45,%46,%47,%48,%49,%50,%51,%52,%53,%54,%55,%56,%57,%58,%59,%60,%61,%62,%63,%64,%65,%66,%67,%68,%69,%70,%71,%72,%73,%74,%75,%76,%77,%78,%79,%80,%81,%82,%83,%84,%85,%86,%87,%88,%89,%90,%91,%92,%93,%94,%95}, %96, %97, p, 1, 1, 0, 1;\n}\n"
    : "+f"(d[0]),"+f"(d[1]),"+f"(d[2]),"+f"(d[3]),"+f"(d[4]),"+f"(d[5]),"+f"(d[6]),"+f"(d[7]),"+f"(d[8]),"+f"(d[9]),"+f"(d[10]),"+f"(d[11]),"+f"(d[12]),"+f"(d[13]),"+f"(d[14]),"+f"(d[15]),"+f"(d[16]),"+f"(d[17]),"+f"(d[18]),"+f"(d[19]),"+f"(d[20]),"+f"(d[21]),"+f"(d[22]),"+f"(d[23]),"+f"(d[24]),"+f"(d[25]),"+f"(d[26]),"+f"(d[27]),"+f"(d[28]),"+f"(d[29]),"+f"(d[30]),"+f"(d[31]),"+f"(d[32]),"+f"(d[33]),"+f"(d[34]),"+f"(d[35]),"+f"(d[36]),"+f"(d[37]),"+f"(d[38]),"+f"(d[39]),"+f"(d[40]),"+f"(d[41]),"+f"(d[42]),"+f"(d[43]),"+f"(d[44]),"+f"(d[45]),"+f"(d[46]),"+f"(d[47]),"+f"(d[48]),"+f"(d[49]),"+f"(d[50]),"+f"(d[51]),"+f"(d[52]),"+f"(d[53]),"+f"(d[54]),"+f"(d[55]),"+f"(d[56]),"+f"(d[57]),"+f"(d[58]),"+f"(d[59]),"+f"(d[60]),"+f"(d[61]),"+f"(d[62]),"+f"(d[63]),"+f"(d[64]),"+f"(d[65]),"+f"(d[66]),"+f"(d[67]),"+f"(d[68]),"+f"(d[69]),"+f"(d[70]),"+f"(d[71]),"+f"(d[72]),"+f"(d[73]),"+f"(d[74]),"+f"(d[75]),"+f"(d[76]),"+f"(d[77]),"+f"(d[78]),"+f"(d[79]),"+f"(d[80]),"+f"(d[81]),"+f"(d[82]),"+f"(d[83]),"+f"(d[84]),"+f"(d[85]),"+f"(d[86]),"+f"(d[87]),"+f"(d[88]),"+f"(d[89]),"+f"(d[90]),"+f"(d[91]),"+f"(d[92]),"+f"(d[93]),"+f"(d[94]),"+f"(d[95])
    : "l"(da), "l"(db), "r"(scale_d));
}
__device__ __forceinline__ void wgmma_ss_n64_k(float (&d)[32], uint64_t da, uint64_t db, int scale_d) {
  asm volatile("{\n.reg .pred p;\nsetp.ne.b32 p, %34, 0;\n"
    "wgmma.mma_async.sync.aligned.m64n64k16.f32.bf16.bf16 {%0,%1,%2,%3,%4,%5,%6,%7,%8,%9,%10,%11,%12,%13,%14,%15,%16,%17,%18,%19,%20,%21,%22,%23,%24,%25,%26,%27,%28,%29,%30,%31}, %32, %33, p, 1, 1, 0, 0;\n}\n"
    : "+f"(d[0]),"+f"(d[1]),"+f"(d[2]),"+f"(d[3]),"+f"(d[4]),"+f"(d[5]),"+f"(d[6]),"+f"(d[7]),"+f"(d[8]),"+f"(d[9]),"+f"(d[10]),"+f"(d[11]),"+f"(d[12]),"+f"(d[13]),"+f"(d[14]),"+f"(d[15]),"+f"(d[16]),"+f"(d[17]),"+f"(d[18]),"+f"(d[19]),"+f"(d[20]),"+f"(d[21]),"+f"(d[22]),"+f"(d[23]),"+f"(d[24]),"+f"(d[25]),"+f"(d[26]),"+f"(d[27]),"+f"(d[28]),"+f"(d[29]),"+f"(d[30]),"+f"(d[31])
    : "l"(da), "l"(db), "r"(scale_d));
}
__device__ __forceinline__ void wgmma_rs_n24_tb(float (&d)[12], uint32_t a0, uint32_t a1, uint32_t a2, uint32_t a3, uint64_t db, int scale_d) {
  asm volatile("{\n.reg .pred p;\nsetp.ne.b32 p, %17, 0;\n"
    "wgmma.mma_async.sync.aligned.m64n24k16.f32.bf16.bf16 {%0,%1,%2,%3,%4,%5,%6,%7,%8,%9,%10,%11}, {%12,%13,%14,%15}, %16, p, 1, 1, 1;\n}\n"
    : "+f"(d[0]),"+f"(d[1]),"+f"(d[2]),"+f"(d[3]),"+f"(d[4]),"+f"(d[5]),"+f"(d[6]),"+f"(d[7]),"+f"(d[8]),"+f"(d[9]),"+f"(d[10]),"+f"(d[11])
    : "r"(a0), "r"(a1), "r"(a2), "r"(a3), "l"(db), "r"(scale_d));
}

constexpr int PRE_ROW_BLOCKS = 64;
constexpr int PRE_COL_BLOCKS = 3 * DM / 64;
__device__ __forceinline__ float2 ln_finish(float mean, float var) {
  float mb = bf_round(mean);
  float s = bf_round(sqrtf(bf_round(bf_round(var) + 1e-5f)));
  return make_float2(mb, 1.0f / s);
}
__device__ __forceinline__ void colsum64(const __nv_bfloat16* __restrict__ w, int ld, int c0, float* __restrict__ dst, float (*red)[65], int tid, int bar_id) {
  const int cg = tid & 7, r0 = tid >> 3;
  float acc[8];
#pragma unroll
  for (int i = 0; i < 8; i++) acc[i] = 0.f;
#pragma unroll 10
  for (int r = r0; r < DM; r += 32) {
    uint4 v = __ldg((const uint4*)(w + (size_t)r * ld + c0 + cg * 8));
    acc[0] += bf_lo(v.x); acc[1] += bf_hi(v.x); acc[2] += bf_lo(v.y); acc[3] += bf_hi(v.y);
    acc[4] += bf_lo(v.z); acc[5] += bf_hi(v.z); acc[6] += bf_lo(v.w); acc[7] += bf_hi(v.w);
  }
#pragma unroll
  for (int i = 0; i < 8; i++) red[r0][cg * 8 + i] = acc[i];
  named_bar(bar_id, 256);
  if (tid < 64) {
    float s = 0.f;
#pragma unroll
    for (int r = 0; r < 32; r++) s += red[r][tid];
    dst[c0 + tid] = s;
  }
  named_bar(bar_id, 256);
}
__global__ void __launch_bounds__(1024) pre_kernel(const __nv_bfloat16* __restrict__ x, const __nv_bfloat16* __restrict__ wqkv) {
  TS_BEGIN(0);
  pdl_launch();
  __shared__ float red[51][161];
  const int tid = threadIdx.x, lane = tid & 31, warp = tid >> 5;
  {
    const int ch = tid % 20, rl = tid / 20;
    if (rl < 51) {
      const __nv_bfloat16* w = wqkv + blockIdx.x * 160 + ch * 8;
      uint4 v[13];
#pragma unroll
      for (int i = 0; i < 13; i++) { const int r = rl + i * 51; v[i] = r < DM ? __ldg((const uint4*)(w + (size_t)r * (3 * DM))) : make_uint4(0, 0, 0, 0); }
      float acc[8];
#pragma unroll
      for (int i = 0; i < 8; i++) acc[i] = 0.f;
#pragma unroll
      for (int i = 0; i < 13; i++) {
        acc[0] += bf_lo(v[i].x); acc[1] += bf_hi(v[i].x); acc[2] += bf_lo(v[i].y); acc[3] += bf_hi(v[i].y);
        acc[4] += bf_lo(v[i].z); acc[5] += bf_hi(v[i].z); acc[6] += bf_lo(v[i].w); acc[7] += bf_hi(v[i].w);
      }
#pragma unroll
      for (int i = 0; i < 8; i++) red[rl][ch * 8 + i] = acc[i];
    }
  }
  const int rbeg = blockIdx.x * 171, rend = min(rbeg + 171, S_LEN);
  for (int row0 = rbeg + warp * 2; row0 < rend; row0 += 64) {
    uint4 v[2][3];
#pragma unroll
    for (int k = 0; k < 2; k++) {
      const int row = min(row0 + k, rend - 1);
      const uint4* p = (const uint4*)(x + (size_t)row * DM);
      v[k][0] = __ldg(p + lane); v[k][1] = __ldg(p + 32 + lane);
      v[k][2] = lane < 16 ? __ldg(p + 64 + lane) : make_uint4(0, 0, 0, 0);
    }
#pragma unroll
    for (int k = 0; k < 2; k++) {
      float f[24];
      const uint32_t u[12] = {v[k][0].x, v[k][0].y, v[k][0].z, v[k][0].w, v[k][1].x, v[k][1].y, v[k][1].z, v[k][1].w, v[k][2].x, v[k][2].y, v[k][2].z, v[k][2].w};
#pragma unroll
      for (int j = 0; j < 12; j++) { f[2 * j] = bf_lo(u[j]); f[2 * j + 1] = bf_hi(u[j]); }
      float s = 0.f;
#pragma unroll
      for (int j = 0; j < 24; j++) s += f[j];
#pragma unroll
      for (int o = 16; o; o >>= 1) s += __shfl_xor_sync(~0u, s, o);
      const float mean = s * (1.0f / DM);
      float q = 0.f;
#pragma unroll
      for (int j = 0; j < 16; j++) { const float d = f[j] - mean; q += d * d; }
      if (lane < 16) {
#pragma unroll
        for (int j = 16; j < 24; j++) { const float d = f[j] - mean; q += d * d; }
      }
#pragma unroll
      for (int o = 16; o; o >>= 1) q += __shfl_xor_sync(~0u, q, o);
      if (lane == 0 && row0 + k < rend) g_stat1[row0 + k] = ln_finish(mean, q * (1.0f / DM));
    }
  }
  __syncthreads();
  if (tid < 160) {
    float s = 0.f;
#pragma unroll 17
    for (int r = 0; r < 51; r++) s += red[r][tid];
    g_cs_qkv[blockIdx.x * 160 + tid] = s;
  }
  TS_END(0);
}

enum { EPI_QKV = 0, EPI_WO = 1, EPI_GLU = 2, EPI_DOWN = 3 };
template <int N> struct WG;
template <> struct WG<128> { static __device__ __forceinline__ void mma(float (&d)[64], uint64_t a, uint64_t b, int s) { wgmma_ss_n128(d, a, b, s); } };
template <> struct WG<192> { static __device__ __forceinline__ void mma(float (&d)[96], uint64_t a, uint64_t b, int s) { wgmma_ss_n192(d, a, b, s); } };

template <int BM, int BN, int NB, int STAGES> struct GemmCfg {
  static constexpr int A_BYTES = BM * 128;
  static constexpr int B_BYTES = NB * (BN / 64) * 8192;
  static constexpr int STAGE_BYTES = A_BYTES + B_BYTES;
  static constexpr int SMEM = STAGES * STAGE_BYTES + 1024   + 256   + 4096  ;
};

constexpr float QSCALE = 0.22360679774997896f * 1.4426950408889634f;

template <int BM, int BN, int NB, int KDIM, int STAGES, int EPI, int MINB, int CN, int CM>
__global__ void __launch_bounds__(EPI == EPI_GLU ? 384 : 288, MINB) gemm_kernel(const __grid_constant__ CUtensorMap tmA, const __grid_constant__ CUtensorMap tmB0,
                                                         const __grid_constant__ CUtensorMap tmB1,
                                                         const __nv_bfloat16* resid, __nv_bfloat16* out) {
  using Cfg = GemmCfg<BM, BN, NB, STAGES>;
  constexpr int MB = BM / 128;
  constexpr int KT = KDIM / 64;
  extern __shared__ uint8_t smem_raw[];
  const uint32_t sbase = (smem_u32(smem_raw) + 1023u) & ~1023u;
  uint8_t* sptr = smem_raw + (sbase - smem_u32(smem_raw));
  const uint32_t sbar = sbase + STAGES * Cfg::STAGE_BYTES;
  const int tid = threadIdx.x, warp = tid >> 5, lane = tid & 31;
  const int n0 = blockIdx.x * BN, m0 = blockIdx.y * BM;
  TS_BEGIN(EPI == EPI_QKV ? 1 : EPI + 2);
  TS_MID(EPI == EPI_QKV ? 1 : EPI + 2, 3);
  constexpr int NCL = CN + CM - 1;
  const int cx = blockIdx.x % CN, cy = blockIdx.y % CM;
  if (tid == 0) {
    for (int i = 0; i < STAGES; i++) { mbar_init(sbar + 8 * i, 1); mbar_init(sbar + 8 * (STAGES + i), 2 * NCL); }
    asm volatile("fence.mbarrier_init.release.cluster;" ::: "memory");
  }
  __syncthreads();
  if constexpr (CN * CM > 1) { cluster_arrive(); cluster_wait(); }
  pdl_launch();
  if (warp >= 8) {
    if constexpr (EPI == EPI_GLU) asm volatile("setmaxnreg.dec.sync.aligned.u32 40;");
    if (warp == 8 && lane == 0) {
      auto load_a = [&](int kt, int s) { tma_2d(sbase + s * Cfg::STAGE_BYTES, &tmA, kt * 64, m0, sbar + 8 * s); };
      auto load_b = [&](int kt, int s) {
        const uint32_t sb = sbase + s * Cfg::STAGE_BYTES + Cfg::A_BYTES;
        tma_3d(sb, &tmB0, 0, kt * 64, blockIdx.x * (BN / 64), sbar + 8 * s);
        if constexpr (NB == 2) tma_3d(sb + (BN / 64) * 8192, &tmB1, 0, kt * 64, blockIdx.x * (BN / 64), sbar + 8 * s);
      };
      if constexpr (EPI == EPI_QKV) {
        const int cta = blockIdx.y * gridDim.x + blockIdx.x;
        const uint32_t xb = S_LEN * DM * 2, xs = 21888;
        if (cta * xs < xb) asm volatile("cp.async.bulk.prefetch.L2.global [%0], %1;" :: "l"((const uint8_t*)resid + (size_t)cta * xs), "r"(min(xs, xb - cta * xs)));
        asm volatile("cp.async.bulk.prefetch.L2.global [%0], %1;" :: "l"((const uint8_t*)out + (size_t)cta * 20480), "r"(20480));
      }
      for (int s = 0; s < STAGES; s++) { mbar_expect_tx(sbar + 8 * s, Cfg::STAGE_BYTES); if (EPI != EPI_QKV || s == 0) load_b(s, s); }
      if (EPI != EPI_QKV) pdl_wait();
      for (int s = 0; s < STAGES; s++) { load_a(s, s); if (EPI == EPI_QKV && s > 0) load_b(s, s); }
      for (int kt = STAGES; kt < KT; kt++) {
        const int s = kt % STAGES;
        mbar_wait(sbar + 8 * (STAGES + s), ((kt / STAGES) - 1) & 1);
        mbar_expect_tx(sbar + 8 * s, Cfg::STAGE_BYTES);
        load_a(kt, s);
        load_b(kt, s);
      }
    }
    if constexpr (EPI == EPI_GLU) {
      if (warp > 8) {
        float2* s_st = (float2*)(sptr + STAGES * Cfg::STAGE_BYTES + 256);
        float* s_cs = (float*)(sptr + STAGES * Cfg::STAGE_BYTES + 256 + 1024);
        pdl_wait();
        for (int r = tid - 288; r < BM; r += 96) {
          const float2* pp = &g_part2[(m0 + r) * 8];
          float s = 0.f;
#pragma unroll
          for (int i = 0; i < 8; i++) s += pp[i].x;
          const float mean = s * (1.0f / DM);
          float q = 0.f;
#pragma unroll
          for (int i = 0; i < 8; i++) { const float2 p = pp[i]; const float d = p.x * (1.0f / 80.f) - mean; q += p.y + 80.f * d * d; }
          s_st[r] = ln_finish(mean, q * (1.0f / DM));
        }
        for (int c = tid - 288; c < BN; c += 96) { s_cs[c] = g_cs_g[n0 + c]; s_cs[BN + c] = g_cs_u[n0 + c]; }
        __threadfence_block();
        asm volatile("bar.arrive 2, 352;" ::: "memory");
      }
    }
    if constexpr (CN * CM > 1) { __syncwarp(); cluster_arrive(); cluster_wait(); }
    return;
  }
  if constexpr (EPI == EPI_GLU) asm volatile("setmaxnreg.inc.sync.aligned.u32 232;");
  const int wg = warp >> 2, g = lane >> 2, t = lane & 3;
  float acc[MB][NB][BN / 2];
#pragma unroll
  for (int mb = 0; mb < MB; mb++)
#pragma unroll
    for (int nb = 0; nb < NB; nb++)
#pragma unroll
      for (int i = 0; i < BN / 2; i++) acc[mb][nb][i] = 0.f;
  for (int kt = 0; kt < KT; kt++) {
    const int s = kt % STAGES;
    mbar_wait(sbar + 8 * s, (kt / STAGES) & 1);
    if (kt == 0) TS_MID(EPI == EPI_QKV ? 1 : EPI + 2, 0);
    const uint32_t sa = sbase + s * Cfg::STAGE_BYTES + wg * (MB * 64 * 128);
    const uint32_t sb = sbase + s * Cfg::STAGE_BYTES + Cfg::A_BYTES;
    wgmma_fence();
#pragma unroll
    for (int ks = 0; ks < 4; ks++) {
#pragma unroll
      for (int mb = 0; mb < MB; mb++) {
        const uint64_t da = make_desc(sa + mb * 8192 + ks * 32, 16, 1024, 1);
#pragma unroll
        for (int nb = 0; nb < NB; nb++) {
          const uint64_t db = make_desc(sb + nb * (BN / 64) * 8192 + ks * 2048, 8192, 1024, 1);
          WG<BN>::mma(acc[mb][nb], da, db, 1);
        }
      }
    }
    wgmma_commit();
    wgmma_wait<1>();
    if (kt > 0 && kt - 1 + STAGES < KT && (tid & 127) < NCL) {
      const uint32_t eb = sbar + 8 * (STAGES + (kt - 1) % STAGES);
      if constexpr (CN * CM > 1) {
        const int i = tid & 127;
        const uint32_t rank = i < CN ? cy * CN + i : ((i - CN + (i - CN >= cy ? 1 : 0)) * CN + cx);
        mbar_arrive_remote(eb, rank);
      } else mbar_arrive(eb);
    }
  }
  wgmma_wait<0>();
#pragma unroll
  for (int mb = 0; mb < MB; mb++)
#pragma unroll
    for (int nb = 0; nb < NB; nb++)
#pragma unroll
      for (int i = 0; i < BN / 2; i++) asm volatile("" : "+f"(acc[mb][nb][i]) :: "memory");
  if constexpr (CN * CM > 1) cluster_arrive();
  TS_MID(EPI == EPI_QKV ? 1 : EPI + 2, 1);
  pdl_wait();
  TS_MID(EPI == EPI_QKV ? 1 : EPI + 2, 2);
  named_bar(1, 256);
  constexpr int LDS = BN * 2 + 16;
  const int ctid = tid;

  if constexpr (EPI == EPI_QKV) {
    const int sec = n0 / DM;
    constexpr int lds = 264;
    __shared__ unsigned int s_kn[8];
    if (ctid < 8) s_kn[ctid] = 0u;
    if (blockIdx.x == 0 && blockIdx.y == 0 && ctid < 32) g_flag[ctid] = 0u;
    float2 cs[BN / 8];
#pragma unroll
    for (int j = 0; j < BN / 8; j++) cs[j] = *(const float2*)&g_cs_qkv[n0 + j * 8 + 2 * t];
#pragma unroll
    for (int mb = 0; mb < MB; mb++) {
      const int r0 = wg * (MB * 64) + mb * 64 + (warp & 3) * 16 + g;
      const float2 st0 = g_stat1[m0 + r0], st1 = g_stat1[m0 + r0 + 8];
      const float sc0 = sec == 0 ? st0.y * QSCALE : st0.y, sc1 = sec == 0 ? st1.y * QSCALE : st1.y;
#pragma unroll
      for (int j = 0; j < BN / 8; j++) {
        const float* a = &acc[mb][0][4 * j];
        *(uint32_t*)(sptr + r0 * lds + j * 16 + t * 4) = pack_bf16(fmaf(-st0.x, cs[j].x, a[0]) * sc0, fmaf(-st0.x, cs[j].y, a[1]) * sc0);
        *(uint32_t*)(sptr + (r0 + 8) * lds + j * 16 + t * 4) = pack_bf16(fmaf(-st1.x, cs[j].x, a[2]) * sc1, fmaf(-st1.x, cs[j].y, a[3]) * sc1);
      }
    }
    named_bar(1, 256);
    {
      const int cbase = n0 - sec * DM;
      const int hfirst = cbase / DH;
      const int j = m0 + ctid;
      uint8_t* dst = (uint8_t*)(sec == 0 ? g_q : (sec == 1 ? g_k : g_v)) + (size_t)(j >> 3) * (sec == 0 ? 512 : 384) + (j & 7) * 16;
      const uint8_t* row = sptr + ctid * 264;
#pragma unroll
      for (int i = 0; i < 8; i++) {
        const int hh = hfirst + i;
        const int cr = hh * DH - cbase;
        if (cr < BN) {
          uint2 v[5];
          bool in[5];
          float s = 0.f;
#pragma unroll
          for (int qd = 0; qd < 5; qd++) {
            const int c = cr + 4 * qd;
            in[qd] = c >= 0 && c < BN;
            v[qd] = in[qd] ? *(const uint2*)(row + c * 2) : make_uint2(0u, 0u);
            s += bf_lo(v[qd].x) * bf_lo(v[qd].x) + bf_hi(v[qd].x) * bf_hi(v[qd].x) + bf_lo(v[qd].y) * bf_lo(v[qd].y) + bf_hi(v[qd].y) * bf_hi(v[qd].y);
          }
          uint8_t* p = dst + (size_t)hh * (sec == 0 ? S_LEN * 64 : S_LEN * 48);
          if (in[0] && in[1]) st_g16(p, make_uint4(v[0].x, v[0].y, v[1].x, v[1].y));
          else if (in[0]) st_g8(p, v[0]);
          else if (in[1]) st_g8(p + 8, v[1]);
          if (in[2] && in[3]) st_g16(p + 128, make_uint4(v[2].x, v[2].y, v[3].x, v[3].y));
          else if (in[2]) st_g8(p + 128, v[2]);
          else if (in[3]) st_g8(p + 136, v[3]);
          if (in[4]) {
            st_g16(p + 256, make_uint4(v[4].x, v[4].y, sec == 0 ? 0u : 0x00003f80u, 0u));
            if (sec == 0) st_g16(p + 384, make_uint4(0u, 0u, 0u, 0u));
          }
          if (sec == 1) {
            const unsigned int mxb = __reduce_max_sync(~0u, __float_as_uint(s) & 0x7fffffffu);
            if (lane == 0) atomicMax(&s_kn[i], mxb);
          }
        }
      }
      if (sec == 1) {
        named_bar(1, 256);
        const int hh = hfirst + ctid;
        if (ctid < 8 && hh * DH < cbase + BN) {
          const bool starts_here = hh * DH >= cbase, ends_here = hh * DH + DH <= cbase + BN;
          const float v = __uint_as_float(s_kn[ctid]);
          float* o = &g_kn[(blockIdx.y * NH + hh) * 2];
          if (starts_here) { o[0] = v; if (ends_here) o[1] = 0.f; }
          else o[1] = v;
        }
      }
    }
  } else if constexpr (EPI == EPI_WO || EPI == EPI_DOWN) {
    const int r0 = wg * 64 + (warp & 3) * 16 + g;
#pragma unroll
    for (int j = 0; j < BN / 8; j++) {
      const float* a = &acc[0][0][4 * j];
      *(uint32_t*)(sptr + r0 * LDS + j * 16 + t * 4) = pack_bf16(a[0], a[1]);
      *(uint32_t*)(sptr + (r0 + 8) * LDS + j * 16 + t * 4) = pack_bf16(a[2], a[3]);
    }
    named_bar(1, 256);
#pragma unroll
    for (int i = 0; i < BM * (BN / 8) / 256; i++) {
      const int idx = i * 256 + ctid, r = idx / (BN / 8), c = idx % (BN / 8);
      const uint4 a = *(const uint4*)(sptr + r * LDS + c * 16);
      const size_t go = (size_t)(m0 + r) * DM + n0 + c * 8;
      const uint4 b = ld_g16(resid + go);
      uint4 o;
      o.x = pack_bf16(bf_lo(a.x) + bf_lo(b.x), bf_hi(a.x) + bf_hi(b.x));
      o.y = pack_bf16(bf_lo(a.y) + bf_lo(b.y), bf_hi(a.y) + bf_hi(b.y));
      o.z = pack_bf16(bf_lo(a.z) + bf_lo(b.z), bf_hi(a.z) + bf_hi(b.z));
      o.w = pack_bf16(bf_lo(a.w) + bf_lo(b.w), bf_hi(a.w) + bf_hi(b.w));
      st_g16(out + go, o);
      if constexpr (EPI == EPI_WO) {
        static_assert(BN == 64, "stats assume 8 lanes per row");
        const float f[8] = {bf_lo(o.x), bf_hi(o.x), bf_lo(o.y), bf_hi(o.y), bf_lo(o.z), bf_hi(o.z), bf_lo(o.w), bf_hi(o.w)};
        float s = 0.f;
#pragma unroll
        for (int k = 0; k < 8; k++) s += f[k];
        s += __shfl_xor_sync(~0u, s, 1); s += __shfl_xor_sync(~0u, s, 2); s += __shfl_xor_sync(~0u, s, 4);
        const float mu = s * (1.0f / 64.f);
        float q = 0.f;
#pragma unroll
        for (int k = 0; k < 8; k++) { const float d = f[k] - mu; q += d * d; }
        q += __shfl_xor_sync(~0u, q, 1); q += __shfl_xor_sync(~0u, q, 2); q += __shfl_xor_sync(~0u, q, 4);
        if (c == 0) g_part2[(m0 + r) * 10 + blockIdx.x] = make_float2(s, q);
      }
    }
  } else {
    const int r0 = wg * 64 + (warp & 3) * 16 + g;
    const float2* s_st = (const float2*)(sptr + STAGES * Cfg::STAGE_BYTES + 256);
    const float* s_cs = (const float*)(sptr + STAGES * Cfg::STAGE_BYTES + 256 + 1024);
    named_bar(2, 352);
    float2 st[2] = {s_st[r0], s_st[r0 + 8]};
#pragma unroll
    for (int j = 0; j < BN / 8; j++) {
      const float2 cg = *(const float2*)&s_cs[j * 8 + 2 * t], cu = *(const float2*)&s_cs[BN + j * 8 + 2 * t];
      const float* a = &acc[0][0][4 * j];
      const float* b = &acc[0][1][4 * j];
#pragma unroll
      for (int e = 0; e < 2; e++) {
        const float2 s_ = st[e];
        const uint32_t gp = pack_bf16(fmaf(-s_.x, cg.x, a[2 * e]) * s_.y, fmaf(-s_.x, cg.y, a[2 * e + 1]) * s_.y);
        const uint32_t up = pack_bf16(fmaf(-s_.x, cu.x, b[2 * e]) * s_.y, fmaf(-s_.x, cu.y, b[2 * e + 1]) * s_.y);
        uint32_t r;
        asm("{\n.reg .b32 z;\nmax.bf16x2 z, %1, %3;\nmul.rn.bf16x2 %0, z, %2;\n}" : "=r"(r) : "r"(gp), "r"(up), "r"(0u));
        *(uint32_t*)(sptr + (r0 + 8 * e) * LDS + j * 16 + t * 4) = r;
      }
    }
    named_bar(1, 256);
#pragma unroll
    for (int i = 0; i < BM * (BN / 8) / 256; i++) {
      const int idx = i * 256 + ctid, r = idx / (BN / 8), c = idx % (BN / 8);
      st_g16(out + (size_t)(m0 + r) * DFF + n0 + c * 8, *(const uint4*)(sptr + r * LDS + c * 16));
    }
  }
  if constexpr (CN * CM > 1) cluster_wait();
  TS_END(EPI == EPI_QKV ? 1 : EPI + 2);
}

constexpr int R_STAGES = 8;
constexpr int R_STAGE_BYTES = 16384 + 5 * 2048;
constexpr int R_BAR_OFF = R_STAGES * R_STAGE_BYTES;
constexpr int R_SMEM = R_BAR_OFF + 256 + 1024;
template <int KDIM, bool STATS>
__global__ void __launch_bounds__(288, 1) gemm_res_kernel(const __grid_constant__ CUtensorMap tmA, const __grid_constant__ CUtensorMap tmB,
                                                          const __nv_bfloat16* resid, __nv_bfloat16* out) {
  constexpr int KT = KDIM / 64;
  extern __shared__ uint8_t smem_raw[];
  const uint32_t sbase = (smem_u32(smem_raw) + 1023u) & ~1023u;
  uint8_t* sptr = smem_raw + (sbase - smem_u32(smem_raw));
  const uint32_t sbar = sbase + R_BAR_OFF;
  const int tid = threadIdx.x, warp = tid >> 5, lane = tid & 31;
  const int n0 = blockIdx.x * 80, m0 = blockIdx.y * 128;
  TS_BEGIN(STATS ? 3 : 5);
  if (tid == 0) {
    for (int i = 0; i < R_STAGES; i++) { mbar_init(sbar + 8 * i, 1); mbar_init(sbar + 8 * (R_STAGES + i), 2); }
    asm volatile("fence.mbarrier_init.release.cluster;" ::: "memory");
  }
  __syncthreads();
  pdl_launch();
  if (warp == 8) {
    if (lane == 0) {
      auto load_b = [&](int kt, int s) { tma_3d(sbase + s * R_STAGE_BYTES + 16384, &tmB, 0, kt * 64, blockIdx.x * 5, sbar + 8 * s); };
      for (int s = 0; s < R_STAGES; s++) { mbar_expect_tx(sbar + 8 * s, R_STAGE_BYTES); if (s < 3) load_b(s, s); }
      pdl_wait();
      for (int s = 0; s < R_STAGES; s++) { tma_2d(sbase + s * R_STAGE_BYTES, &tmA, s * 64, m0, sbar + 8 * s); if (s >= 3) load_b(s, s); }
      for (int kt = R_STAGES; kt < KT; kt++) {
        const int s = kt % R_STAGES;
        mbar_wait(sbar + 8 * (R_STAGES + s), ((kt / R_STAGES) - 1) & 1);
        mbar_expect_tx(sbar + 8 * s, R_STAGE_BYTES);
        tma_2d(sbase + s * R_STAGE_BYTES, &tmA, kt * 64, m0, sbar + 8 * s);
        load_b(kt, s);
      }
    }
    return;
  }
  const int wg = warp >> 2, g = lane >> 2, t = lane & 3;
  pdl_wait();
  uint4 rv[5];
#pragma unroll
  for (int i = 0; i < 5; i++) {
    const int idx = i * 256 + tid, r = idx / 10, c = idx % 10;
    rv[i] = ld_g16(resid + (size_t)(m0 + r) * DM + n0 + c * 8);
  }
  float acc[40];
#pragma unroll
  for (int i = 0; i < 40; i++) acc[i] = 0.f;
  for (int kt = 0; kt < KT; kt++) {
    const int s = kt % R_STAGES;
    mbar_wait(sbar + 8 * s, (kt / R_STAGES) & 1);
    if (kt == 0) TS_MID(STATS ? 3 : 5, 0);
    const uint32_t sa = sbase + s * R_STAGE_BYTES + wg * 8192;
    const uint32_t sb = sbase + s * R_STAGE_BYTES + 16384;
    wgmma_fence();
#pragma unroll
    for (int ks = 0; ks < 4; ks++)
      wgmma_ss_n80(acc, make_desc(sa + ks * 32, 16, 1024, 1), make_desc(sb + ks * 512, 2048, 256, 3), 1);
    wgmma_commit();
    wgmma_wait<1>();
    if (kt > 0 && kt - 1 + R_STAGES < KT && (tid & 127) == 0) mbar_arrive(sbar + 8 * (R_STAGES + (kt - 1) % R_STAGES));
  }
  wgmma_wait<0>();
#pragma unroll
  for (int i = 0; i < 40; i++) asm volatile("" : "+f"(acc[i]) :: "memory");
  TS_MID(STATS ? 3 : 5, 1);
  named_bar(1, 256);
  constexpr int LDS = 176;
  const int r0 = wg * 64 + (warp & 3) * 16 + g;
#pragma unroll
  for (int i = 0; i < 10; i++) {
    *(uint32_t*)(sptr + r0 * LDS + i * 16 + t * 4) = pack_bf16(acc[4 * i], acc[4 * i + 1]);
    *(uint32_t*)(sptr + (r0 + 8) * LDS + i * 16 + t * 4) = pack_bf16(acc[4 * i + 2], acc[4 * i + 3]);
  }
  named_bar(1, 256);
  TS_MID(STATS ? 3 : 5, 2);
#pragma unroll
  for (int i = 0; i < 5; i++) {
    const int idx = i * 256 + tid, r = idx / 10, c = idx % 10;
    const uint4 a = *(const uint4*)(sptr + r * LDS + c * 16);
    const uint4 b = rv[i];
    uint4 o;
    o.x = pack_bf16(bf_lo(a.x) + bf_lo(b.x), bf_hi(a.x) + bf_hi(b.x));
    o.y = pack_bf16(bf_lo(a.y) + bf_lo(b.y), bf_hi(a.y) + bf_hi(b.y));
    o.z = pack_bf16(bf_lo(a.z) + bf_lo(b.z), bf_hi(a.z) + bf_hi(b.z));
    o.w = pack_bf16(bf_lo(a.w) + bf_lo(b.w), bf_hi(a.w) + bf_hi(b.w));
    st_g16(out + (size_t)(m0 + r) * DM + n0 + c * 8, o);
    if constexpr (STATS) *(uint4*)(sptr + r * LDS + c * 16) = o;
  }
  TS_MID(STATS ? 3 : 5, 3);
  if constexpr (STATS) {
    named_bar(1, 256);
    const int r = tid >> 1, hf = tid & 1;
    float f[40];
#pragma unroll
    for (int i = 0; i < 5; i++) {
      const uint4 v = *(const uint4*)(sptr + r * LDS + hf * 80 + i * 16);
      f[8 * i] = bf_lo(v.x); f[8 * i + 1] = bf_hi(v.x); f[8 * i + 2] = bf_lo(v.y); f[8 * i + 3] = bf_hi(v.y);
      f[8 * i + 4] = bf_lo(v.z); f[8 * i + 5] = bf_hi(v.z); f[8 * i + 6] = bf_lo(v.w); f[8 * i + 7] = bf_hi(v.w);
    }
    float s = 0.f;
#pragma unroll
    for (int i = 0; i < 40; i++) s += f[i];
    s += __shfl_xor_sync(~0u, s, 1);
    const float mu = s * (1.0f / 80.f);
    float q = 0.f;
#pragma unroll
    for (int i = 0; i < 40; i++) { const float d = f[i] - mu; q += d * d; }
    q += __shfl_xor_sync(~0u, q, 1);
    if (hf == 0) g_part2[(m0 + r) * 8 + blockIdx.x] = make_float2(s, q);
  }
  TS_END(STATS ? 3 : 5);
}

#define F_MC 0
constexpr int F_CST = 7, F_DST = 3, F_EST = 5;
constexpr int F_RS = 16384 + 5 * 2048;
constexpr int F_DS = 16384 + 6 * 8192;
constexpr int F_E_OFF = 53248;
constexpr int F_STG_OFF = F_DST * F_DS;
constexpr int F_BAR_OFF = F_STG_OFF + 128 * 176;
constexpr int F_VEC_OFF = F_BAR_OFF + 256;
constexpr int F_SMEM = F_VEC_OFF + 1024 + 1536 + 1024;

__device__ __forceinline__ void flag_wait(const unsigned int* f, unsigned int target) {
  unsigned int v, spins = 0;
  do { asm volatile("ld.acquire.gpu.global.u32 %0, [%1];" : "=r"(v) : "l"(f) : "memory"); } while (v < target && ++spins < (1u << 22));
  asm volatile("fence.proxy.async;" ::: "memory");
}
__device__ __forceinline__ void flag_signal(unsigned int* f) {
  asm volatile("fence.proxy.async;" ::: "memory");
  asm volatile("red.release.gpu.global.add.u32 [%0], 1;" :: "l"(f) : "memory");
}

template <bool STATS>
__device__ __forceinline__ void res_epilogue(float (&acc)[40], const uint4 (&rv)[5], uint8_t* stg, __nv_bfloat16* out, int m0, int n0, int tid, int bx) {
  constexpr int LDS = 176;
  const int warp = tid >> 5, lane = tid & 31;
  const int r0 = (warp >> 2) * 64 + (warp & 3) * 16 + (lane >> 2), t = lane & 3;
#pragma unroll
  for (int i = 0; i < 10; i++) {
    *(uint32_t*)(stg + r0 * LDS + i * 16 + t * 4) = pack_bf16(acc[4 * i], acc[4 * i + 1]);
    *(uint32_t*)(stg + (r0 + 8) * LDS + i * 16 + t * 4) = pack_bf16(acc[4 * i + 2], acc[4 * i + 3]);
  }
  named_bar(1, 256);
#pragma unroll
  for (int i = 0; i < 5; i++) {
    const int idx = i * 256 + tid, r = idx / 10, c = idx % 10;
    const uint4 a = *(const uint4*)(stg + r * LDS + c * 16);
    const uint4 b = rv[i];
    uint4 o;
    o.x = pack_bf16(bf_lo(a.x) + bf_lo(b.x), bf_hi(a.x) + bf_hi(b.x));
    o.y = pack_bf16(bf_lo(a.y) + bf_lo(b.y), bf_hi(a.y) + bf_hi(b.y));
    o.z = pack_bf16(bf_lo(a.z) + bf_lo(b.z), bf_hi(a.z) + bf_hi(b.z));
    o.w = pack_bf16(bf_lo(a.w) + bf_lo(b.w), bf_hi(a.w) + bf_hi(b.w));
    st_g16(out + (size_t)(m0 + r) * DM + n0 + c * 8, o);
    if constexpr (STATS) *(uint4*)(stg + r * LDS + c * 16) = o;
  }
  if constexpr (STATS) {
    named_bar(1, 256);
    const int r = tid >> 1, hf = tid & 1;
    float f[40];
#pragma unroll
    for (int i = 0; i < 5; i++) {
      const uint4 v = *(const uint4*)(stg + r * LDS + hf * 80 + i * 16);
      f[8 * i] = bf_lo(v.x); f[8 * i + 1] = bf_hi(v.x); f[8 * i + 2] = bf_lo(v.y); f[8 * i + 3] = bf_hi(v.y);
      f[8 * i + 4] = bf_lo(v.z); f[8 * i + 5] = bf_hi(v.z); f[8 * i + 6] = bf_lo(v.w); f[8 * i + 7] = bf_hi(v.w);
    }
    float s = 0.f;
#pragma unroll
    for (int i = 0; i < 40; i++) s += f[i];
    s += __shfl_xor_sync(~0u, s, 1);
    const float mu = s * (1.0f / 80.f);
    float q = 0.f;
#pragma unroll
    for (int i = 0; i < 40; i++) { const float d = f[i] - mu; q += d * d; }
    q += __shfl_xor_sync(~0u, q, 1);
    if (hf == 0) g_part2[(m0 + r) * 8 + bx] = make_float2(s, q);
  }
}

__global__ void __launch_bounds__(384, 1) post_kernel(const __grid_constant__ CUtensorMap tmO, const __grid_constant__ CUtensorMap tmWo,
                                                      const __grid_constant__ CUtensorMap tmH, const __grid_constant__ CUtensorMap tmWg,
                                                      const __grid_constant__ CUtensorMap tmWu, const __grid_constant__ CUtensorMap tmAct,
                                                      const __grid_constant__ CUtensorMap tmWd, const __nv_bfloat16* x, __nv_bfloat16* out) {
  extern __shared__ uint8_t smem_raw[];
  const uint32_t sbase = (smem_u32(smem_raw) + 1023u) & ~1023u;
  uint8_t* sptr = smem_raw + (sbase - smem_u32(smem_raw));
  const uint32_t bC = sbase + F_BAR_OFF, bD = bC + 16 * F_CST, bE = bD + 16 * F_DST;
  const int tid = threadIdx.x, warp = tid >> 5, lane = tid & 31;
  const int bx = blockIdx.x, rb = blockIdx.y, m0 = rb * 128, cx = bx & 1;
  TS_BEGIN(3);
  if (tid == 0) {
    for (int i = 0; i < F_CST; i++) { mbar_init(bC + 8 * i, 1); mbar_init(bC + 8 * (F_CST + i), F_MC ? 4 : 2); }
    for (int i = 0; i < F_DST; i++) { mbar_init(bD + 8 * i, 1); mbar_init(bD + 8 * (F_DST + i), F_MC ? 4 : 2); }
    for (int i = 0; i < F_EST; i++) { mbar_init(bE + 8 * i, 1); mbar_init(bE + 8 * (F_EST + i), F_MC ? 4 : 2); }
    asm volatile("fence.mbarrier_init.release.cluster;" ::: "memory");
  }
  __syncthreads();
  if (F_MC) { cluster_arrive(); cluster_wait(); }
  if (warp >= 8) {
    asm volatile("setmaxnreg.dec.sync.aligned.u32 40;");
    if (warp == 8) {
      if (lane == 0) {
        auto load_a = [&](const CUtensorMap* tm, uint32_t stage, int kt, uint32_t bar) {
          if (F_MC) tma_2d_mc(stage + cx * 8192, tm, kt * 64, m0 + cx * 64, bar, (uint16_t)3); else tma_2d(stage, tm, kt * 64, m0, bar);
        };
        for (int s = 0; s < F_CST; s++) { mbar_expect_tx(bC + 8 * s, F_RS); if (s < 3) tma_3d(sbase + s * F_RS + 16384, &tmWo, 0, s * 64, bx * 5, bC + 8 * s); }
        pdl_wait();
        for (int s = 0; s < F_CST; s++) { load_a(&tmO, sbase + s * F_RS, s, bC + 8 * s); if (s >= 3) tma_3d(sbase + s * F_RS + 16384, &tmWo, 0, s * 64, bx * 5, bC + 8 * s); }
        for (int kt = F_CST; kt < 10; kt++) {
          const int s = kt - F_CST;
          mbar_wait(bC + 8 * (F_CST + s), 0);
          mbar_expect_tx(bC + 8 * s, F_RS);
          load_a(&tmO, sbase + s * F_RS, kt, bC + 8 * s);
          tma_3d(sbase + s * F_RS + 16384, &tmWo, 0, kt * 64, bx * 5, bC + 8 * s);
        }
        auto load_bd = [&](int kt, int s) {
          tma_3d(sbase + s * F_DS + 16384, &tmWg, 0, kt * 64, bx * 3, bD + 8 * s);
          tma_3d(sbase + s * F_DS + 16384 + 3 * 8192, &tmWu, 0, kt * 64, bx * 3, bD + 8 * s);
        };
        for (int s = 0; s < F_DST; s++) { mbar_wait(bD + 8 * (F_DST + s), 0); mbar_expect_tx(bD + 8 * s, F_DS); load_bd(s, s); }
        flag_wait(&g_flag[rb], 8);
        for (int s = 0; s < F_DST; s++) load_a(&tmH, sbase + s * F_DS, s, bD + 8 * s);
        for (int kt = F_DST; kt < 10; kt++) {
          const int s = kt % F_DST;
          mbar_wait(bD + 8 * (F_DST + s), (kt / F_DST) & 1);
          mbar_expect_tx(bD + 8 * s, F_DS);
          load_a(&tmH, sbase + s * F_DS, kt, bD + 8 * s);
          load_bd(kt, s);
        }
        const uint32_t eb = sbase + F_E_OFF;
        for (int s = 0; s < F_EST; s++) { mbar_wait(bE + 8 * (F_EST + s), 0); mbar_expect_tx(bE + 8 * s, F_RS); tma_3d(eb + s * F_RS + 16384, &tmWd, 0, s * 64, bx * 5, bE + 8 * s); }
        flag_wait(&g_flag[16 + rb], 8);
        for (int s = 0; s < F_EST; s++) load_a(&tmAct, eb + s * F_RS, s, bE + 8 * s);
        for (int kt = F_EST; kt < 24; kt++) {
          const int s = kt % F_EST;
          mbar_wait(bE + 8 * (F_EST + s), (kt / F_EST) & 1);
          mbar_expect_tx(bE + 8 * s, F_RS);
          load_a(&tmAct, eb + s * F_RS, kt, bE + 8 * s);
          tma_3d(eb + s * F_RS + 16384, &tmWd, 0, kt * 64, bx * 5, bE + 8 * s);
        }
      }
    } else {
      float2* s_st = (float2*)(sptr + F_VEC_OFF);
      float* s_cs = (float*)(sptr + F_VEC_OFF + 1024);
      pdl_wait();
      for (int c = tid - 288; c < 192; c += 96) { s_cs[c] = g_cs_g[bx * 192 + c]; s_cs[192 + c] = g_cs_u[bx * 192 + c]; }
      flag_wait(&g_flag[rb], 8);
      for (int r = tid - 288; r < 128; r += 96) {
        const float2* pp = &g_part2[(m0 + r) * 8];
        float2 p[8];
        float s = 0.f;
#pragma unroll
        for (int i = 0; i < 8; i++) { asm volatile("ld.global.v2.f32 {%0, %1}, [%2];" : "=f"(p[i].x), "=f"(p[i].y) : "l"(pp + i) : "memory"); s += p[i].x; }
        const float mean = s * (1.0f / DM);
        float q = 0.f;
#pragma unroll
        for (int i = 0; i < 8; i++) { const float d = p[i].x * (1.0f / 80.f) - mean; q += p[i].y + 80.f * d * d; }
        s_st[r] = ln_finish(mean, q * (1.0f / DM));
      }
      __threadfence_block();
      asm volatile("bar.arrive 2, 352;" ::: "memory");
    }
    if (F_MC) { __syncwarp(); cluster_arrive(); cluster_wait(); }
    return;
  }
  asm volatile("setmaxnreg.inc.sync.aligned.u32 232;");
  const int wg = warp >> 2, g = lane >> 2, t = lane & 3;
  auto release = [&](uint32_t bar) { if (F_MC) { if ((tid & 127) < 2) mbar_arrive_remote(bar, (tid & 127) ^ cx); } else if ((tid & 127) == 0) mbar_arrive(bar); };
  const int n0 = bx * 80;
  uint4 rv[5];
  pdl_wait();
  {
#pragma unroll
    for (int i = 0; i < 5; i++) { const int idx = i * 256 + tid, r = idx / 10, c = idx % 10; rv[i] = ld_g16(x + (size_t)(m0 + r) * DM + n0 + c * 8); }
    float acc[40];
#pragma unroll
    for (int i = 0; i < 40; i++) acc[i] = 0.f;
    for (int kt = 0; kt < 10; kt++) {
      const int s = kt % F_CST;
      mbar_wait(bC + 8 * s, kt / F_CST);
      if (kt == 0) TS_MID(3, 0);
      const uint32_t sa = sbase + s * F_RS + wg * 8192, sb = sbase + s * F_RS + 16384;
      wgmma_fence();
#pragma unroll
      for (int ks = 0; ks < 4; ks++) wgmma_ss_n80(acc, make_desc(sa + ks * 32, 16, 1024, 1), make_desc(sb + ks * 512, 2048, 256, 3), 1);
      wgmma_commit();
      wgmma_wait<1>();
      if (kt > 0 && kt - 1 + F_CST < 10) release(bC + 8 * (F_CST + kt - 1));
    }
    wgmma_wait<0>();
#pragma unroll
    for (int i = 0; i < 40; i++) asm volatile("" : "+f"(acc[i]) :: "memory");
    for (int s = 0; s < F_DST; s++) release(bD + 8 * (F_DST + s));
    TS_MID(3, 1);
    res_epilogue<true>(acc, rv, sptr + F_STG_OFF, g_h, m0, n0, tid, bx);
    __threadfence();
    named_bar(1, 256);
    if (tid == 0) flag_signal(&g_flag[rb]);
    TS_END(3);
  }
  {
    float acc[2][96];
#pragma unroll
    for (int i = 0; i < 96; i++) { acc[0][i] = 0.f; acc[1][i] = 0.f; }
    for (int kt = 0; kt < 10; kt++) {
      const int s = kt % F_DST;
      mbar_wait(bD + 8 * s, (kt / F_DST) & 1);
      if (kt == 0) TS_MID(4, 0);
      const uint32_t sa = sbase + s * F_DS + wg * 8192, sb = sbase + s * F_DS + 16384;
      wgmma_fence();
#pragma unroll
      for (int ks = 0; ks < 4; ks++) {
        const uint64_t da = make_desc(sa + ks * 32, 16, 1024, 1);
        wgmma_ss_n192(acc[0], da, make_desc(sb + ks * 2048, 8192, 1024, 1), 1);
        wgmma_ss_n192(acc[1], da, make_desc(sb + 3 * 8192 + ks * 2048, 8192, 1024, 1), 1);
      }
      wgmma_commit();
      wgmma_wait<1>();
      if (kt > 0 && kt - 1 + F_DST < 10) release(bD + 8 * (F_DST + (kt - 1) % F_DST));
    }
    wgmma_wait<0>();
#pragma unroll
    for (int i = 0; i < 96; i++) { asm volatile("" : "+f"(acc[0][i]) :: "memory"); asm volatile("" : "+f"(acc[1][i]) :: "memory"); }
    for (int s = 0; s < F_EST; s++) release(bE + 8 * (F_EST + s));
    TS_MID(4, 1);
    named_bar(1, 256);
    named_bar(2, 352);
    constexpr int LDS = 400;
    const float2* s_st = (const float2*)(sptr + F_VEC_OFF);
    const float* s_cs = (const float*)(sptr + F_VEC_OFF + 1024);
    const int r0 = wg * 64 + (warp & 3) * 16 + g;
    const float2 st[2] = {s_st[r0], s_st[r0 + 8]};
#pragma unroll
    for (int j = 0; j < 24; j++) {
      const float2 cg = *(const float2*)&s_cs[j * 8 + 2 * t], cu = *(const float2*)&s_cs[192 + j * 8 + 2 * t];
      const float* a = &acc[0][4 * j];
      const float* b = &acc[1][4 * j];
#pragma unroll
      for (int e = 0; e < 2; e++) {
        const float2 s_ = st[e];
        const uint32_t gp = pack_bf16(fmaf(-s_.x, cg.x, a[2 * e]) * s_.y, fmaf(-s_.x, cg.y, a[2 * e + 1]) * s_.y);
        const uint32_t up = pack_bf16(fmaf(-s_.x, cu.x, b[2 * e]) * s_.y, fmaf(-s_.x, cu.y, b[2 * e + 1]) * s_.y);
        uint32_t r;
        asm("{\n.reg .b32 z;\nmax.bf16x2 z, %1, %3;\nmul.rn.bf16x2 %0, z, %2;\n}" : "=r"(r) : "r"(gp), "r"(up), "r"(0u));
        *(uint32_t*)(sptr + (r0 + 8 * e) * LDS + j * 16 + t * 4) = r;
      }
    }
    named_bar(1, 256);
#pragma unroll
    for (int i = 0; i < 12; i++) {
      const int idx = i * 256 + tid, r = idx / 24, c = idx % 24;
      st_g16(g_act + (size_t)(m0 + r) * DFF + bx * 192 + c * 8, *(const uint4*)(sptr + r * LDS + c * 16));
    }
    __threadfence();
    named_bar(1, 256);
    if (tid == 0) flag_signal(&g_flag[16 + rb]);
    TS_END(4);
  }
  {
#pragma unroll
    for (int i = 0; i < 5; i++) { const int idx = i * 256 + tid, r = idx / 10, c = idx % 10; rv[i] = ld_g16(g_h + (size_t)(m0 + r) * DM + n0 + c * 8); }
    float acc[40];
#pragma unroll
    for (int i = 0; i < 40; i++) acc[i] = 0.f;
    const uint32_t eb = sbase + F_E_OFF;
    for (int kt = 0; kt < 24; kt++) {
      const int s = kt % F_EST;
      mbar_wait(bE + 8 * s, (kt / F_EST) & 1);
      if (kt == 0) TS_MID(5, 0);
      const uint32_t sa = eb + s * F_RS + wg * 8192, sb = eb + s * F_RS + 16384;
      wgmma_fence();
#pragma unroll
      for (int ks = 0; ks < 4; ks++) wgmma_ss_n80(acc, make_desc(sa + ks * 32, 16, 1024, 1), make_desc(sb + ks * 512, 2048, 256, 3), 1);
      wgmma_commit();
      wgmma_wait<1>();
      if (kt > 0 && kt - 1 + F_EST < 24) release(bE + 8 * (F_EST + (kt - 1) % F_EST));
    }
    wgmma_wait<0>();
#pragma unroll
    for (int i = 0; i < 40; i++) asm volatile("" : "+f"(acc[i]) :: "memory");
    if (F_MC) cluster_arrive();
    TS_MID(5, 1);
    res_epilogue<false>(acc, rv, sptr + F_STG_OFF, out, m0, n0, tid, bx);
    if (F_MC) cluster_wait();
    TS_END(5);
  }
}

#define POLY_NUM 5
__device__ __forceinline__ float ex2_poly(float x, int shl23) {
  const float MAGIC = 12582912.f;
  const float tt = x + MAGIC;
  const float f = x - (tt - MAGIC);
  float p = fmaf(0.0013276472454890609f, f, 0.009675540961325169f);
  p = fmaf(p, f, 0.05550713092088699f);
  p = fmaf(p, f, 0.24022120237350464f);
  p = fmaf(p, f, 0.6931469440460205f);
  p = fmaf(p, f, 1.0000001192092896f);
  return __int_as_float(__float_as_int(tt) * shl23 + __float_as_int(p));
}
constexpr int KV_BYTES = S_LEN * 48;
constexpr int ATT_SMEM = 2 * KV_BYTES + 256 + 32768;
constexpr int ATT_BODY = 8;

__global__ void __launch_bounds__(512, 1) attn_kernel(int shl23, const __nv_bfloat16* __restrict__ wg_, const __nv_bfloat16* __restrict__ wu_,
                                                      const __nv_bfloat16* __restrict__ wo_, const __nv_bfloat16* __restrict__ wd_) {
  extern __shared__ __align__(1024) uint8_t smem[];
  if (blockIdx.x >= 128) {
    pdl_launch();
    const int e = blockIdx.x - 128, half = threadIdx.x >> 8;
    if (threadIdx.x == 0) {
      for (int i = 0; i < 13; i++) asm volatile("cp.async.bulk.prefetch.L2.global [%0], %1;" :: "l"((const uint8_t*)wo_ + (e * 13 + i) * 16384 * 0 + (size_t)(e * 13 + i >= 50 ? 0 : (e * 13 + i)) * 16384), "r"(16384));
      for (int i = 0; i < 30; i++) asm volatile("cp.async.bulk.prefetch.L2.global [%0], %1;" :: "l"((const uint8_t*)wd_ + (size_t)(e * 30 + i) * 16384), "r"(16384));
    }
    float (*red)[65] = (float (*)[65])(smem + half * 16384);
    for (int b = e * 12 + half; b < e * 12 + 12; b += 2) {
      if (b < 24) colsum64(wg_, DFF, b * 64, g_cs_g, red, threadIdx.x & 255, 1 + half);
      else colsum64(wu_, DFF, (b - 24) * 64, g_cs_u, red, threadIdx.x & 255, 1 + half);
    }
    return;
  }
  const int h = blockIdx.x >> 2, qb = blockIdx.x & 3;
  const uint32_t sK = smem_u32(smem), sV = sK + KV_BYTES, sBar = sV + KV_BYTES;
  const int tid = threadIdx.x;
  TS_BEGIN(2);
  if (tid == 0) {
    for (int i = 0; i < 9; i++) mbar_init(sBar + 8 * i, 1);
    asm volatile("fence.mbarrier_init.release.cluster;" ::: "memory");
  }
  __syncthreads();
  pdl_launch();
  pdl_wait();
  TS_MID(2, 0);
  const uint8_t* gk = (const uint8_t*)(g_k + (size_t)h * S_LEN * 24);
  const uint8_t* gv = (const uint8_t*)(g_v + (size_t)h * S_LEN * 24);
  auto load_kv = [&](int i0, int i1) {
    for (int i = i0; i < i1; i++) {
      mbar_expect_tx(sBar + 8 * i, 2 * 12288);
      bulk_g2s(sK + i * 12288, gk + i * 12288, 12288, sBar + 8 * i);
      bulk_g2s(sV + i * 12288, gv + i * 12288, 12288, sBar + 8 * i);
    }
  };
  if (tid == 0) {
    mbar_expect_tx(sBar + 64, 32768);
    bulk_g2s(sBar + 256, (const uint8_t*)g_q + ((size_t)h * S_LEN + qb * 512) * 64, 32768, sBar + 64);
    load_kv(0, 2);
  }
  float ka = 0.f, kb = 0.f;
#pragma unroll
  for (int i = 0; i < 8; i++) {
    const float2 v = *(const float2*)&g_kn[(i * NH + h) * 2];
    ka = (v.x > ka || v.x != v.x) ? v.x : ka;
    kb = (v.y > kb || v.y != v.y) ? v.y : kb;
  }
  bool fast;
  {
    const float kn = sqrtf(ka + kb);
    mbar_wait(sBar + 64, 0);
    if (tid == 0) load_kv(2, 8);
    uint8_t* qrow = smem + 2 * KV_BYTES + 256 + (tid >> 3) * 512 + (tid & 7) * 16;
    const uint4 c0 = *(const uint4*)qrow, c1 = *(const uint4*)(qrow + 128);
    const uint2 c2 = *(const uint2*)(qrow + 256);
    auto sq = [](uint32_t u) { const float a = bf_lo(u), b = bf_hi(u); return a * a + b * b; };
    const float n2 = sq(c0.x) + sq(c0.y) + sq(c0.z) + sq(c0.w) + sq(c1.x) + sq(c1.y) + sq(c1.z) + sq(c1.w) + sq(c2.x) + sq(c2.y);
    const float m = ceilf(sqrtf(n2) * kn * 1.001f) + 1.f;
    fast = __syncthreads_or(!(m <= 62.f)) == 0;
    if (fast) *(uint32_t*)(qrow + 256 + 8) = pack_bf16(-m, 0.f);
    asm volatile("fence.proxy.async.shared::cta;" ::: "memory");
    __syncthreads();
  }
  auto write_out = [&](float (&O)[12], int it) {
    uint32_t tid2;
    asm volatile("mov.u32 %0, %%tid.x;" : "=r"(tid2));
    const int lane2 = tid2 & 31, t2 = lane2 & 3;
    const int qq = (blockIdx.x & 3) * 512 + (it * 4 + (tid2 >> 7)) * 64 + ((tid2 >> 5) & 3) * 16 + (lane2 >> 2);
    const float l0 = __shfl_sync(~0u, O[8], (lane2 & ~3) | 2), l1 = __shfl_sync(~0u, O[10], (lane2 & ~3) | 2);
    const float r0 = 1.f / l0, r1 = 1.f / l1;
    uint32_t* o0 = (uint32_t*)(g_o + (size_t)qq * DM + (blockIdx.x >> 2) * DH);
    uint32_t* o1 = o0 + 8 * DM / 2;
    o0[t2] = pack_bf16(O[0] * r0, O[1] * r0); o1[t2] = pack_bf16(O[2] * r1, O[3] * r1);
    o0[t2 + 4] = pack_bf16(O[4] * r0, O[5] * r0); o1[t2 + 4] = pack_bf16(O[6] * r1, O[7] * r1);
    if (t2 < 2) { o0[t2 + 8] = pack_bf16(O[8] * r0, O[9] * r0); o1[t2 + 8] = pack_bf16(O[10] * r1, O[11] * r1); }
  };
  TS_MID(2, 1);
  if (fast) {
#pragma unroll 1
    for (int it = 0; it < 2; it++) {
      const uint64_t dq = make_desc(sBar + 256 + (it * 4 + (tid >> 7)) * 4096, 128, 512, 0);
      float O[12];
#pragma unroll
      for (int i = 0; i < 12; i++) { O[i] = 0.f; asm volatile("" : "+f"(O[i]) :: "memory"); }
      float S[2][32];
      uint32_t P[16];
#pragma unroll 1
      for (int jb = 0; jb < 32 / ATT_BODY; jb++) {
        if (it == 0) { for (int c = 0; c < ATT_BODY / 4; c++) mbar_wait(sBar + 8 * (jb * (ATT_BODY / 4) + c), 0); }
        const uint64_t dk0 = make_desc(sK + jb * ATT_BODY * 8 * 384, 128, 384, 0);
        const uint64_t dv0 = make_desc(sV + jb * ATT_BODY * 8 * 384, 384, 128, 0);
        wgmma_fence();
        wgmma_ss_n64_k(S[0], dq, dk0, 0);
        wgmma_ss_n64_k(S[0], dq + (256 >> 4), dk0 + (256 >> 4), 1);
        wgmma_commit();
#pragma unroll
        for (int u = 0; u < ATT_BODY; u++) {
          if (u + 1 < ATT_BODY) {
            const uint64_t dk = dk0 + (((u + 1) * 8 * 384) >> 4);
            wgmma_fence();
            wgmma_ss_n64_k(S[(u + 1) & 1], dq, dk, 0);
            wgmma_ss_n64_k(S[(u + 1) & 1], dq + (256 >> 4), dk + (256 >> 4), 1);
            wgmma_commit();
          }
          if (u == 0 || u == ATT_BODY - 1) wgmma_wait<1>(); else wgmma_wait<2>();
#pragma unroll
          for (int i = 0; i < 32; i++) asm volatile("" : "+f"(S[u & 1][i]) :: "memory");
          const uint64_t dv = dv0 + ((u * 8 * 384) >> 4);
#pragma unroll
          for (int hf = 0; hf < 2; hf++) {
            if (hf == 1 && u > 0) { if (u == ATT_BODY - 1) wgmma_wait<1>(); else wgmma_wait<2>(); }
#pragma unroll
            for (int i = hf * 8; i < hf * 8 + 8; i++) {
              const bool usepoly = ((i + 1) * POLY_NUM / 16) != (i * POLY_NUM / 16);
              float a, b;
              if (usepoly) { a = ex2_poly(S[u & 1][2 * i], shl23); b = ex2_poly(S[u & 1][2 * i + 1], shl23); }
              else { a = ex2_mufu(S[u & 1][2 * i]); b = ex2_mufu(S[u & 1][2 * i + 1]); }
              P[i] = pack_bf16(a, b);
            }
            wgmma_fence();
#pragma unroll
            for (int ks = hf * 2; ks < hf * 2 + 2; ks++)
              wgmma_rs_n24_tb(O, P[4 * ks], P[4 * ks + 1], P[4 * ks + 2], P[4 * ks + 3], dv + ((ks * 768) >> 4), 1);
            wgmma_commit();
          }
        }
        wgmma_wait<0>();
      }
#pragma unroll
      for (int i = 0; i < 12; i++) asm volatile("" : "+f"(O[i]) :: "memory");
      write_out(O, it);
      if (it == 0) TS_MID(2, 2);
    }
  } else {
#pragma unroll 1
    for (int it = 0; it < 2; it++) {
      const uint64_t dq = make_desc(sBar + 256 + (it * 4 + (tid >> 7)) * 4096, 128, 512, 0);
      float O[12];
#pragma unroll
      for (int i = 0; i < 12; i++) { O[i] = 0.f; asm volatile("" : "+f"(O[i]) :: "memory"); }
      float S[32];
      float mx0 = -INFINITY, mx1 = -INFINITY;
#pragma unroll 1
      for (int j = 0; j < 32; j++) {
        if (it == 0 && (j & 3) == 0) mbar_wait(sBar + 8 * (j >> 2), 0);
        const uint64_t dk = make_desc(sK + j * 8 * 384, 128, 384, 0);
        wgmma_fence();
        wgmma_ss_n64_k(S, dq, dk, 0);
        wgmma_ss_n64_k(S, dq + (256 >> 4), dk + (256 >> 4), 1);
        wgmma_commit();
        wgmma_wait<0>();
#pragma unroll
        for (int i = 0; i < 8; i++) {
          mx0 = fmaxf(mx0, fmaxf(S[4 * i], S[4 * i + 1]));
          mx1 = fmaxf(mx1, fmaxf(S[4 * i + 2], S[4 * i + 3]));
        }
      }
      mx0 = fmaxf(mx0, __shfl_xor_sync(~0u, mx0, 1)); mx0 = fmaxf(mx0, __shfl_xor_sync(~0u, mx0, 2));
      mx1 = fmaxf(mx1, __shfl_xor_sync(~0u, mx1, 1)); mx1 = fmaxf(mx1, __shfl_xor_sync(~0u, mx1, 2));
#pragma unroll 1
      for (int j = 0; j < 32; j++) {
        const uint64_t dk = make_desc(sK + j * 8 * 384, 128, 384, 0);
        wgmma_fence();
        wgmma_ss_n64_k(S, dq, dk, 0);
        wgmma_ss_n64_k(S, dq + (256 >> 4), dk + (256 >> 4), 1);
        wgmma_commit();
        wgmma_wait<0>();
        uint32_t P[16];
#pragma unroll
        for (int i = 0; i < 8; i++) {
          P[2 * i] = pack_bf16(ex2_mufu(S[4 * i] - mx0), ex2_mufu(S[4 * i + 1] - mx0));
          P[2 * i + 1] = pack_bf16(ex2_mufu(S[4 * i + 2] - mx1), ex2_mufu(S[4 * i + 3] - mx1));
        }
        wgmma_fence();
        const uint64_t dv = make_desc(sV + j * 8 * 384, 384, 128, 0);
#pragma unroll
        for (int ks = 0; ks < 4; ks++)
          wgmma_rs_n24_tb(O, P[4 * ks], P[4 * ks + 1], P[4 * ks + 2], P[4 * ks + 3], dv + ((ks * 768) >> 4), 1);
        wgmma_commit();
        wgmma_wait<0>();
      }
#pragma unroll
      for (int i = 0; i < 12; i++) asm volatile("" : "+f"(O[i]) :: "memory");
      write_out(O, it);
    }
  }
  TS_END(2);
}

typedef CUresult (*EncodeFn)(CUtensorMap*, CUtensorMapDataType, cuuint32_t, void*, const cuuint64_t*, const cuuint64_t*, const cuuint32_t*,
                             const cuuint32_t*, CUtensorMapInterleave, CUtensorMapSwizzle, CUtensorMapL2promotion, CUtensorMapFloatOOBfill);
static EncodeFn get_encode() {
  static EncodeFn fn = nullptr;
  if (!fn) {
    void* p = nullptr; cudaDriverEntryPointQueryResult st;
    cudaGetDriverEntryPoint("cuTensorMapEncodeTiled", &p, cudaEnableDefault, &st);
    fn = (EncodeFn)p;
  }
  return fn;
}
static CUtensorMap make_map(const void* ptr, int rows, int cols, int box_rows, int box_cols = 64) {
  CUtensorMap m;
  cuuint64_t dims[2] = {(cuuint64_t)cols, (cuuint64_t)rows};
  cuuint64_t strides[1] = {(cuuint64_t)cols * 2};
  cuuint32_t box[2] = {(cuuint32_t)box_cols, (cuuint32_t)box_rows};
  cuuint32_t es[2] = {1, 1};
  get_encode()(&m, CU_TENSOR_MAP_DATA_TYPE_BFLOAT16, 2, const_cast<void*>(ptr), dims, strides, box, es, CU_TENSOR_MAP_INTERLEAVE_NONE,
               box_cols == 64 ? CU_TENSOR_MAP_SWIZZLE_128B : (box_cols == 32 ? CU_TENSOR_MAP_SWIZZLE_64B : CU_TENSOR_MAP_SWIZZLE_32B), CU_TENSOR_MAP_L2_PROMOTION_L2_128B, CU_TENSOR_MAP_FLOAT_OOB_FILL_NONE);
  return m;
}
static CUtensorMap make_map_w(const void* ptr, int rows, int cols, int bc, int nblk) {
  CUtensorMap m;
  cuuint64_t dims[3] = {(cuuint64_t)bc, (cuuint64_t)rows, (cuuint64_t)(cols / bc)};
  cuuint64_t strides[2] = {(cuuint64_t)cols * 2, (cuuint64_t)bc * 2};
  cuuint32_t box[3] = {(cuuint32_t)bc, 64, (cuuint32_t)nblk};
  cuuint32_t es[3] = {1, 1, 1};
  get_encode()(&m, CU_TENSOR_MAP_DATA_TYPE_BFLOAT16, 3, const_cast<void*>(ptr), dims, strides, box, es, CU_TENSOR_MAP_INTERLEAVE_NONE,
               bc == 64 ? CU_TENSOR_MAP_SWIZZLE_128B : (bc == 32 ? CU_TENSOR_MAP_SWIZZLE_64B : CU_TENSOR_MAP_SWIZZLE_32B),
               CU_TENSOR_MAP_L2_PROMOTION_L2_128B, CU_TENSOR_MAP_FLOAT_OOB_FILL_NONE);
  return m;
}
template <typename... KArgs, typename... Args>
static void launch(void (*kern)(KArgs...), dim3 grid, dim3 block, size_t smem, bool pdl, dim3 cluster, Args... args) {
  cudaLaunchConfig_t cfg = {};
  cfg.gridDim = grid; cfg.blockDim = block; cfg.dynamicSmemBytes = smem; cfg.stream = cudaStreamPerThread;
  cudaLaunchAttribute at[2];
  int na = 0;
  if (pdl) { at[na].id = cudaLaunchAttributeProgrammaticStreamSerialization; at[na].val.programmaticStreamSerializationAllowed = 1; na++; }
  if (cluster.x * cluster.y > 1) { at[na].id = cudaLaunchAttributeClusterDimension; at[na].val.clusterDim.x = cluster.x; at[na].val.clusterDim.y = cluster.y; at[na].val.clusterDim.z = 1; na++; }
  cfg.attrs = at; cfg.numAttrs = na;
  cudaLaunchKernelEx(&cfg, kern, KArgs(args)...);
}

extern "C" void kernel_launch(void* const* d_in, const int* in_sizes, int n_in, void* d_out, int out_size) {
  const __nv_bfloat16* x = (const __nv_bfloat16*)d_in[0];
  const __nv_bfloat16* wqkv = (const __nv_bfloat16*)d_in[1];
  const __nv_bfloat16* wo = (const __nv_bfloat16*)d_in[2];
  const __nv_bfloat16* wgate = (const __nv_bfloat16*)d_in[4];
  const __nv_bfloat16* wup = (const __nv_bfloat16*)d_in[5];
  const __nv_bfloat16* wdown = (const __nv_bfloat16*)d_in[6];
  __nv_bfloat16* out = (__nv_bfloat16*)d_out;
  void *p_o, *p_h, *p_act;
  cudaGetSymbolAddress(&p_o, g_o); cudaGetSymbolAddress(&p_h, g_h); cudaGetSymbolAddress(&p_act, g_act);

#define A_CN 1
#define A_CM 1
#define D_CN 1
#define D_CM 1
  auto kA = gemm_kernel<256, 128, 1, DM, 4, EPI_QKV, 1, A_CN, A_CM>;
  auto kC = gemm_res_kernel<DM, true>;
  auto kD = gemm_kernel<128, 192, 2, DM, 3, EPI_GLU, 1, D_CN, D_CM>;
  auto kE = gemm_res_kernel<DFF, false>;
  constexpr int smA = GemmCfg<256, 128, 1, 4>::SMEM, smC = R_SMEM, smD = GemmCfg<128, 192, 2, 3>::SMEM;
  cudaFuncSetAttribute(kA, cudaFuncAttributeMaxDynamicSharedMemorySize, smA);
  cudaFuncSetAttribute(kC, cudaFuncAttributeMaxDynamicSharedMemorySize, smC);
  cudaFuncSetAttribute(kD, cudaFuncAttributeMaxDynamicSharedMemorySize, smD);
  cudaFuncSetAttribute(kE, cudaFuncAttributeMaxDynamicSharedMemorySize, smC);
  cudaFuncSetAttribute(attn_kernel, cudaFuncAttributeMaxDynamicSharedMemorySize, ATT_SMEM);

  const CUtensorMap tm_x = make_map(x, S_LEN, DM, 256), tm_wqkv = make_map_w(wqkv, DM, 3 * DM, 64, 2);
  const CUtensorMap tm_o = make_map(p_o, S_LEN, DM, 128), tm_wo = make_map_w(wo, DM, DM, 16, 5);
  const CUtensorMap tm_h = make_map(p_h, S_LEN, DM, 128), tm_wg = make_map_w(wgate, DM, DFF, 64, 3), tm_wu = make_map_w(wup, DM, DFF, 64, 3);
  const CUtensorMap tm_act = make_map(p_act, S_LEN, DFF, 128), tm_wd = make_map_w(wdown, DFF, DM, 16, 5);

  launch(pre_kernel, dim3(12), dim3(1024), 0, false, dim3(1, 1), x, wqkv);
  launch(kA, dim3(15, 8), dim3(288), smA, true, dim3(A_CN, A_CM), tm_x, tm_wqkv, tm_wqkv, x, (__nv_bfloat16*)wqkv);
  launch(attn_kernel, dim3(132), dim3(512), ATT_SMEM, true, dim3(1, 1), 0x800000, wgate, wup, wo, wdown);
  cudaFuncSetAttribute(post_kernel, cudaFuncAttributeMaxDynamicSharedMemorySize, F_SMEM);
  const CUtensorMap tm_o2 = make_map(p_o, S_LEN, DM, F_MC ? 64 : 128), tm_h2 = make_map(p_h, S_LEN, DM, F_MC ? 64 : 128), tm_act2 = make_map(p_act, S_LEN, DFF, F_MC ? 64 : 128);
  launch(post_kernel, dim3(8, 16), dim3(384), F_SMEM, true, dim3(F_MC ? 2 : 1, 1), tm_o2, tm_wo, tm_h2, tm_wg, tm_wu, tm_act2, tm_wd, x, out);
}
```

```cpp
#include <cuda_runtime.h>
#include <cuda_bf16.h>
#include <cuda.h>
#include <stdint.h>

constexpr int S_LEN = 2048, DM = 640, NH = 32, DH = 20, DFF = 1536;

__device__ __align__(1024) __nv_bfloat16 g_q[NH * S_LEN * 32];
__device__ __align__(1024) __nv_bfloat16 g_k[NH * S_LEN * 24];
__device__ __align__(1024) __nv_bfloat16 g_v[NH * S_LEN * 24];
__device__ __align__(1024) __nv_bfloat16 g_o[S_LEN * DM];
__device__ __align__(1024) __nv_bfloat16 g_h[S_LEN * DM];
__device__ __align__(1024) __nv_bfloat16 g_act[S_LEN * DFF];
__device__ __align__(1024) __nv_bfloat16 g_wo_t[DM * DM];
__device__ __align__(1024) __nv_bfloat16 g_wd_t[DFF * DM];
__device__ float g_kn[8 * NH * 2];
__device__ float2 g_stat1[S_LEN];
__device__ float g_cs_qkv[3 * DM];
__device__ float g_cs_g[DFF];
__device__ float g_cs_u[DFF];
__device__ unsigned int g_flag[32];
__device__ float2 g_part2[S_LEN * 10];

#define TS_BEGIN(k)
#define TS_END(k)
#define TS_MID(k, i)
__device__ __forceinline__ uint32_t smem_u32(const void* p) { return (uint32_t)__cvta_generic_to_shared(p); }
__device__ __forceinline__ void mbar_init(uint32_t bar, uint32_t cnt) { asm volatile("mbarrier.init.shared::cta.b64 [%0], %1;" :: "r"(bar), "r"(cnt)); }
__device__ __forceinline__ void mbar_expect_tx(uint32_t bar, uint32_t bytes) { asm volatile("mbarrier.arrive.expect_tx.shared::cta.b64 _, [%0], %1;" :: "r"(bar), "r"(bytes) : "memory"); }
__device__ __forceinline__ void mbar_arrive(uint32_t bar) { asm volatile("mbarrier.arrive.shared::cta.b64 _, [%0];" :: "r"(bar) : "memory"); }
__device__ __forceinline__ void mbar_wait(uint32_t bar, uint32_t parity) {
  uint32_t done;
  uint32_t spins = 0;
  do {
    asm volatile("{\n.reg .pred P1;\nmbarrier.try_wait.parity.shared::cta.b64 P1, [%1], %2;\nselp.u32 %0, 1, 0, P1;\n}" : "=r"(done) : "r"(bar), "r"(parity) : "memory");
  } while (!done && ++spins < (1u << 24));
}
__device__ __forceinline__ void bulk_g2s(uint32_t dst, const void* src, uint32_t bytes, uint32_t bar) {
  asm volatile("cp.async.bulk.shared::cluster.global.mbarrier::complete_tx::bytes [%0], [%1], %2, [%3];" :: "r"(dst), "l"(src), "r"(bytes), "r"(bar) : "memory");
}
__device__ __forceinline__ void tma_2d(uint32_t dst, const CUtensorMap* tm, int c0, int c1, uint32_t bar) {
  asm volatile("cp.async.bulk.tensor.2d.shared::cluster.global.mbarrier::complete_tx::bytes [%0], [%1, {%3, %4}], [%2];"
               :: "r"(dst), "l"(tm), "r"(bar), "r"(c0), "r"(c1) : "memory");
}
__device__ __forceinline__ void tma_3d(uint32_t dst, const CUtensorMap* tm, int c0, int c1, int c2, uint32_t bar) {
  asm volatile("cp.async.bulk.tensor.3d.shared::cluster.global.mbarrier::complete_tx::bytes [%0], [%1, {%3, %4, %5}], [%2];"
               :: "r"(dst), "l"(tm), "r"(bar), "r"(c0), "r"(c1), "r"(c2) : "memory");
}
__device__ __forceinline__ void tma_2d_mc(uint32_t dst, const CUtensorMap* tm, int c0, int c1, uint32_t bar, uint16_t mask) {
  asm volatile("cp.async.bulk.tensor.2d.shared::cluster.global.mbarrier::complete_tx::bytes.multicast::cluster [%0], [%1, {%3, %4}], [%2], %5;"
               :: "r"(dst), "l"(tm), "r"(bar), "r"(c0), "r"(c1), "h"(mask) : "memory");
}
__device__ __forceinline__ void mbar_arrive_remote(uint32_t bar, uint32_t rank) {
  asm volatile("{\n.reg .b32 ra;\nmapa.shared::cluster.u32 ra, %0, %1;\nmbarrier.arrive.release.cluster.shared::cluster.b64 _, [ra];\n}" :: "r"(bar), "r"(rank) : "memory");
}
__device__ __forceinline__ void cluster_arrive() { asm volatile("barrier.cluster.arrive.release.aligned;" ::: "memory"); }
__device__ __forceinline__ void cluster_wait() { asm volatile("barrier.cluster.wait.acquire.aligned;" ::: "memory"); }
__device__ __forceinline__ void wgmma_fence() { asm volatile("wgmma.fence.sync.aligned;" ::: "memory"); }
__device__ __forceinline__ void wgmma_commit() { asm volatile("wgmma.commit_group.sync.aligned;" ::: "memory"); }
template <int N> __device__ __forceinline__ void wgmma_wait() { asm volatile("wgmma.wait_group.sync.aligned %0;" :: "n"(N) : "memory"); }
__device__ __forceinline__ void pdl_wait() { asm volatile("griddepcontrol.wait;" ::: "memory"); }
__device__ __forceinline__ void pdl_launch() { asm volatile("griddepcontrol.launch_dependents;" ::: "memory"); }
__device__ __forceinline__ void named_bar(int id, int n) { asm volatile("bar.sync %0, %1;" :: "r"(id), "r"(n) : "memory"); }
__device__ __forceinline__ uint64_t make_desc(uint32_t addr, uint32_t lbo, uint32_t sbo, uint32_t swz) {
  return (uint64_t)((addr & 0x3FFFF) >> 4) | ((uint64_t)(lbo >> 4) << 16) | ((uint64_t)(sbo >> 4) << 32) | ((uint64_t)swz << 62);
}
__device__ __forceinline__ void st_g16(void* p, uint4 v) { asm volatile("st.global.v4.b32 [%0], {%1, %2, %3, %4};" :: "l"(p), "r"(v.x), "r"(v.y), "r"(v.z), "r"(v.w) : "memory"); }
__device__ __forceinline__ void st_g8(void* p, uint2 v) { asm volatile("st.global.v2.b32 [%0], {%1, %2};" :: "l"(p), "r"(v.x), "r"(v.y) : "memory"); }
__device__ __forceinline__ uint4 ld_g16(const void* p) { uint4 v; asm volatile("ld.global.v4.b32 {%0, %1, %2, %3}, [%4];" : "=r"(v.x), "=r"(v.y), "=r"(v.z), "=r"(v.w) : "l"(p) : "memory"); return v; }
__device__ __forceinline__ uint32_t pack_bf16(float lo, float hi) { uint32_t r; asm("cvt.rn.bf16x2.f32 %0, %1, %2;" : "=r"(r) : "f"(hi), "f"(lo)); return r; }
__device__ __forceinline__ float bf_lo(uint32_t u) { return __uint_as_float(u << 16); }
__device__ __forceinline__ float bf_hi(uint32_t u) { return __uint_as_float(u & 0xffff0000u); }
__device__ __forceinline__ float bf_round(float x) { return __bfloat162float(__float2bfloat16_rn(x)); }
__device__ __forceinline__ float ex2_mufu(float x) { float y; asm("ex2.approx.ftz.f32 %0, %1;" : "=f"(y) : "f"(x)); return y; }

__device__ __forceinline__ void wgmma_ss_n80(float (&d)[40], uint64_t da, uint64_t db, int scale_d) {
  asm volatile("{\n.reg .pred p;\nsetp.ne.b32 p, %42, 0;\n"
    "wgmma.mma_async.sync.aligned.m64n80k16.f32.bf16.bf16 {%0,%1,%2,%3,%4,%5,%6,%7,%8,%9,%10,%11,%12,%13,%14,%15,%16,%17,%18,%19,%20,%21,%22,%23,%24,%25,%26,%27,%28,%29,%30,%31,%32,%33,%34,%35,%36,%37,%38,%39}, %40, %41, p, 1, 1, 0, 1;\n}\n"
    : "+f"(d[0]),"+f"(d[1]),"+f"(d[2]),"+f"(d[3]),"+f"(d[4]),"+f"(d[5]),"+f"(d[6]),"+f"(d[7]),"+f"(d[8]),"+f"(d[9]),"+f"(d[10]),"+f"(d[11]),"+f"(d[12]),"+f"(d[13]),"+f"(d[14]),"+f"(d[15]),"+f"(d[16]),"+f"(d[17]),"+f"(d[18]),"+f"(d[19]),"+f"(d[20]),"+f"(d[21]),"+f"(d[22]),"+f"(d[23]),"+f"(d[24]),"+f"(d[25]),"+f"(d[26]),"+f"(d[27]),"+f"(d[28]),"+f"(d[29]),"+f"(d[30]),"+f"(d[31]),"+f"(d[32]),"+f"(d[33]),"+f"(d[34]),"+f"(d[35]),"+f"(d[36]),"+f"(d[37]),"+f"(d[38]),"+f"(d[39])
    : "l"(da), "l"(db), "r"(scale_d));
}
__device__ __forceinline__ void wgmma_ss_n128(float (&d)[64], uint64_t da, uint64_t db, int scale_d) {
  asm volatile("{\n.reg .pred p;\nsetp.ne.b32 p, %66, 0;\n"
    "wgmma.mma_async.sync.aligned.m64n128k16.f32.bf16.bf16 {%0,%1,%2,%3,%4,%5,%6,%7,%8,%9,%10,%11,%12,%13,%14,%15,%16,%17,%18,%19,%20,%21,%22,%23,%24,%25,%26,%27,%28,%29,%30,%31,%32,%33,%34,%35,%36,%37,%38,%39,%40,%41,%42,%43,%44,%45,%46,%47,%48,%49,%50,%51,%52,%53,%54,%55,%56,%57,%58,%59,%60,%61,%62,%63}, %64, %65, p, 1, 1, 0, 1;\n}\n"
    : "+f"(d[0]),"+f"(d[1]),"+f"(d[2]),"+f"(d[3]),"+f"(d[4]),"+f"(d[5]),"+f"(d[6]),"+f"(d[7]),"+f"(d[8]),"+f"(d[9]),"+f"(d[10]),"+f"(d[11]),"+f"(d[12]),"+f"(d[13]),"+f"(d[14]),"+f"(d[15]),"+f"(d[16]),"+f"(d[17]),"+f"(d[18]),"+f"(d[19]),"+f"(d[20]),"+f"(d[21]),"+f"(d[22]),"+f"(d[23]),"+f"(d[24]),"+f"(d[25]),"+f"(d[26]),"+f"(d[27]),"+f"(d[28]),"+f"(d[29]),"+f"(d[30]),"+f"(d[31]),"+f"(d[32]),"+f"(d[33]),"+f"(d[34]),"+f"(d[35]),"+f"(d[36]),"+f"(d[37]),"+f"(d[38]),"+f"(d[39]),"+f"(d[40]),"+f"(d[41]),"+f"(d[42]),"+f"(d[43]),"+f"(d[44]),"+f"(d[45]),"+f"(d[46]),"+f"(d[47]),"+f"(d[48]),"+f"(d[49]),"+f"(d[50]),"+f"(d[51]),"+f"(d[52]),"+f"(d[53]),"+f"(d[54]),"+f"(d[55]),"+f"(d[56]),"+f"(d[57]),"+f"(d[58]),"+f"(d[59]),"+f"(d[60]),"+f"(d[61]),"+f"(d[62]),"+f"(d[63])
    : "l"(da), "l"(db), "r"(scale_d));
}
__device__ __forceinline__ void wgmma_ss_n192(float (&d)[96], uint64_t da, uint64_t db, int scale_d) {
  asm volatile("{\n.reg .pred p;\nsetp.ne.b32 p, %98, 0;\n"
    "wgmma.mma_async.sync.aligned.m64n192k16.f32.bf16.bf16 {%0,%1,%2,%3,%4,%5,%6,%7,%8,%9,%10,%11,%12,%13,%14,%15,%16,%17,%18,%19,%20,%21,%22,%23,%24,%25,%26,%27,%28,%29,%30,%31,%32,%33,%34,%35,%36,%37,%38,%39,%40,%41,%42,%43,%44,%45,%46,%47,%48,%49,%50,%51,%52,%53,%54,%55,%56,%57,%58,%59,%60,%61,%62,%63,%64,%65,%66,%67,%68,%69,%70,%71,%72,%73,%74,%75,%76,%77,%78,%79,%80,%81,%82,%83,%84,%85,%86,%87,%88,%89,%90,%91,%92,%93,%94,%95}, %96, %97, p, 1, 1, 0, 1;\n}\n"
    : "+f"(d[0]),"+f"(d[1]),"+f"(d[2]),"+f"(d[3]),"+f"(d[4]),"+f"(d[5]),"+f"(d[6]),"+f"(d[7]),"+f"(d[8]),"+f"(d[9]),"+f"(d[10]),"+f"(d[11]),"+f"(d[12]),"+f"(d[13]),"+f"(d[14]),"+f"(d[15]),"+f"(d[16]),"+f"(d[17]),"+f"(d[18]),"+f"(d[19]),"+f"(d[20]),"+f"(d[21]),"+f"(d[22]),"+f"(d[23]),"+f"(d[24]),"+f"(d[25]),"+f"(d[26]),"+f"(d[27]),"+f"(d[28]),"+f"(d[29]),"+f"(d[30]),"+f"(d[31]),"+f"(d[32]),"+f"(d[33]),"+f"(d[34]),"+f"(d[35]),"+f"(d[36]),"+f"(d[37]),"+f"(d[38]),"+f"(d[39]),"+f"(d[40]),"+f"(d[41]),"+f"(d[42]),"+f"(d[43]),"+f"(d[44]),"+f"(d[45]),"+f"(d[46]),"+f"(d[47]),"+f"(d[48]),"+f"(d[49]),"+f"(d[50]),"+f"(d[51]),"+f"(d[52]),"+f"(d[53]),"+f"(d[54]),"+f"(d[55]),"+f"(d[56]),"+f"(d[57]),"+f"(d[58]),"+f"(d[59]),"+f"(d[60]),"+f"(d[61]),"+f"(d[62]),"+f"(d[63]),"+f"(d[64]),"+f"(d[65]),"+f"(d[66]),"+f"(d[67]),"+f"(d[68]),"+f"(d[69]),"+f"(d[70]),"+f"(d[71]),"+f"(d[72]),"+f"(d[73]),"+f"(d[74]),"+f"(d[75]),"+f"(d[76]),"+f"(d[77]),"+f"(d[78]),"+f"(d[79]),"+f"(d[80]),"+f"(d[81]),"+f"(d[82]),"+f"(d[83]),"+f"(d[84]),"+f"(d[85]),"+f"(d[86]),"+f"(d[87]),"+f"(d[88]),"+f"(d[89]),"+f"(d[90]),"+f"(d[91]),"+f"(d[92]),"+f"(d[93]),"+f"(d[94]),"+f"(d[95])
    : "l"(da), "l"(db), "r"(scale_d));
}
__device__ __forceinline__ void wgmma_ss_n64_k(float (&d)[32], uint64_t da, uint64_t db, int scale_d) {
  asm volatile("{\n.reg .pred p;\nsetp.ne.b32 p, %34, 0;\n"
    "wgmma.mma_async.sync.aligned.m64n64k16.f32.bf16.bf16 {%0,%1,%2,%3,%4,%5,%6,%7,%8,%9,%10,%11,%12,%13,%14,%15,%16,%17,%18,%19,%20,%21,%22,%23,%24,%25,%26,%27,%28,%29,%30,%31}, %32, %33, p, 1, 1, 0, 0;\n}\n"
    : "+f"(d[0]),"+f"(d[1]),"+f"(d[2]),"+f"(d[3]),"+f"(d[4]),"+f"(d[5]),"+f"(d[6]),"+f"(d[7]),"+f"(d[8]),"+f"(d[9]),"+f"(d[10]),"+f"(d[11]),"+f"(d[12]),"+f"(d[13]),"+f"(d[14]),"+f"(d[15]),"+f"(d[16]),"+f"(d[17]),"+f"(d[18]),"+f"(d[19]),"+f"(d[20]),"+f"(d[21]),"+f"(d[22]),"+f"(d[23]),"+f"(d[24]),"+f"(d[25]),"+f"(d[26]),"+f"(d[27]),"+f"(d[28]),"+f"(d[29]),"+f"(d[30]),"+f"(d[31])
    : "l"(da), "l"(db), "r"(scale_d));
}
__device__ __forceinline__ void wgmma_rs_n24_tb(float (&d)[12], uint32_t a0, uint32_t a1, uint32_t a2, uint32_t a3, uint64_t db, int scale_d) {
  asm volatile("{\n.reg .pred p;\nsetp.ne.b32 p, %17, 0;\n"
    "wgmma.mma_async.sync.aligned.m64n24k16.f32.bf16.bf16 {%0,%1,%2,%3,%4,%5,%6,%7,%8,%9,%10,%11}, {%12,%13,%14,%15}, %16, p, 1, 1, 1;\n}\n"
    : "+f"(d[0]),"+f"(d[1]),"+f"(d[2]),"+f"(d[3]),"+f"(d[4]),"+f"(d[5]),"+f"(d[6]),"+f"(d[7]),"+f"(d[8]),"+f"(d[9]),"+f"(d[10]),"+f"(d[11])
    : "r"(a0), "r"(a1), "r"(a2), "r"(a3), "l"(db), "r"(scale_d));
}

constexpr int PRE_ROW_BLOCKS = 64;
constexpr int PRE_COL_BLOCKS = 3 * DM / 64;
__device__ __forceinline__ float2 ln_finish(float mean, float var) {
  float mb = bf_round(mean);
  float s = bf_round(sqrtf(bf_round(bf_round(var) + 1e-5f)));
  return make_float2(mb, 1.0f / s);
}
__device__ __forceinline__ void colsum64(const __nv_bfloat16* __restrict__ w, int ld, int c0, float* __restrict__ dst, float (*red)[65], int tid, int bar_id) {
  const int cg = tid & 7, r0 = tid >> 3;
  float acc[8];
#pragma unroll
  for (int i = 0; i < 8; i++) acc[i] = 0.f;
#pragma unroll 10
  for (int r = r0; r < DM; r += 32) {
    uint4 v = __ldg((const uint4*)(w + (size_t)r * ld + c0 + cg * 8));
    acc[0] += bf_lo(v.x); acc[1] += bf_hi(v.x); acc[2] += bf_lo(v.y); acc[3] += bf_hi(v.y);
    acc[4] += bf_lo(v.z); acc[5] += bf_hi(v.z); acc[6] += bf_lo(v.w); acc[7] += bf_hi(v.w);
  }
#pragma unroll
  for (int i = 0; i < 8; i++) red[r0][cg * 8 + i] = acc[i];
  named_bar(bar_id, 256);
  if (tid < 64) {
    float s = 0.f;
#pragma unroll
    for (int r = 0; r < 32; r++) s += red[r][tid];
    dst[c0 + tid] = s;
  }
  named_bar(bar_id, 256);
}
__global__ void __launch_bounds__(1024) pre_kernel(const __nv_bfloat16* __restrict__ x, const __nv_bfloat16* __restrict__ wqkv) {
  TS_BEGIN(0);
  pdl_launch();
  __shared__ float red[51][161];
  const int tid = threadIdx.x, lane = tid & 31, warp = tid >> 5;
  {
    const int ch = tid % 20, rl = tid / 20;
    if (rl < 51) {
      const __nv_bfloat16* w = wqkv + blockIdx.x * 160 + ch * 8;
      uint4 v[13];
#pragma unroll
      for (int i = 0; i < 13; i++) { const int r = rl + i * 51; v[i] = r < DM ? __ldg((const uint4*)(w + (size_t)r * (3 * DM))) : make_uint4(0, 0, 0, 0); }
      float acc[8];
#pragma unroll
      for (int i = 0; i < 8; i++) acc[i] = 0.f;
#pragma unroll
      for (int i = 0; i < 13; i++) {
        acc[0] += bf_lo(v[i].x); acc[1] += bf_hi(v[i].x); acc[2] += bf_lo(v[i].y); acc[3] += bf_hi(v[i].y);
        acc[4] += bf_lo(v[i].z); acc[5] += bf_hi(v[i].z); acc[6] += bf_lo(v[i].w); acc[7] += bf_hi(v[i].w);
      }
#pragma unroll
      for (int i = 0; i < 8; i++) red[rl][ch * 8 + i] = acc[i];
    }
  }
  const int rbeg = blockIdx.x * 171, rend = min(rbeg + 171, S_LEN);
  for (int row0 = rbeg + warp * 2; row0 < rend; row0 += 64) {
    uint4 v[2][3];
#pragma unroll
    for (int k = 0; k < 2; k++) {
      const int row = min(row0 + k, rend - 1);
      const uint4* p = (const uint4*)(x + (size_t)row * DM);
      v[k][0] = __ldg(p + lane); v[k][1] = __ldg(p + 32 + lane);
      v[k][2] = lane < 16 ? __ldg(p + 64 + lane) : make_uint4(0, 0, 0, 0);
    }
#pragma unroll
    for (int k = 0; k < 2; k++) {
      float f[24];
      const uint32_t u[12] = {v[k][0].x, v[k][0].y, v[k][0].z, v[k][0].w, v[k][1].x, v[k][1].y, v[k][1].z, v[k][1].w, v[k][2].x, v[k][2].y, v[k][2].z, v[k][2].w};
#pragma unroll
      for (int j = 0; j < 12; j++) { f[2 * j] = bf_lo(u[j]); f[2 * j + 1] = bf_hi(u[j]); }
      float s = 0.f;
#pragma unroll
      for (int j = 0; j < 24; j++) s += f[j];
#pragma unroll
      for (int o = 16; o; o >>= 1) s += __shfl_xor_sync(~0u, s, o);
      const float mean = s * (1.0f / DM);
      float q = 0.f;
#pragma unroll
      for (int j = 0; j < 16; j++) { const float d = f[j] - mean; q += d * d; }
      if (lane < 16) {
#pragma unroll
        for (int j = 16; j < 24; j++) { const float d = f[j] - mean; q += d * d; }
      }
#pragma unroll
      for (int o = 16; o; o >>= 1) q += __shfl_xor_sync(~0u, q, o);
      if (lane == 0 && row0 + k < rend) g_stat1[row0 + k] = ln_finish(mean, q * (1.0f / DM));
    }
  }
  __syncthreads();
  if (tid < 160) {
    float s = 0.f;
#pragma unroll 17
    for (int r = 0; r < 51; r++) s += red[r][tid];
    g_cs_qkv[blockIdx.x * 160 + tid] = s;
  }
  TS_END(0);
}

enum { EPI_QKV = 0, EPI_WO = 1, EPI_GLU = 2, EPI_DOWN = 3 };
template <int N> struct WG;
template <> struct WG<128> { static __device__ __forceinline__ void mma(float (&d)[64], uint64_t a, uint64_t b, int s) { wgmma_ss_n128(d, a, b, s); } };
template <> struct WG<192> { static __device__ __forceinline__ void mma(float (&d)[96], uint64_t a, uint64_t b, int s) { wgmma_ss_n192(d, a, b, s); } };

template <int BM, int BN, int NB, int STAGES> struct GemmCfg {
  static constexpr int A_BYTES = BM * 128;
  static constexpr int B_BYTES = NB * (BN / 64) * 8192;
  static constexpr int STAGE_BYTES = A_BYTES + B_BYTES;
  static constexpr int SMEM = STAGES * STAGE_BYTES + 1024   + 256   + 4096  ;
};

constexpr float QSCALE = 0.22360679774997896f * 1.4426950408889634f;

template <int BM, int BN, int NB, int KDIM, int STAGES, int EPI, int MINB, int CN, int CM>
__global__ void __launch_bounds__(EPI == EPI_GLU ? 384 : 288, MINB) gemm_kernel(const __grid_constant__ CUtensorMap tmA, const __grid_constant__ CUtensorMap tmB0,
                                                         const __grid_constant__ CUtensorMap tmB1,
                                                         const __nv_bfloat16* resid, __nv_bfloat16* out) {
  using Cfg = GemmCfg<BM, BN, NB, STAGES>;
  constexpr int MB = BM / 128;
  constexpr int KT = KDIM / 64;
  extern __shared__ uint8_t smem_raw[];
  const uint32_t sbase = (smem_u32(smem_raw) + 1023u) & ~1023u;
  uint8_t* sptr = smem_raw + (sbase - smem_u32(smem_raw));
  const uint32_t sbar = sbase + STAGES * Cfg::STAGE_BYTES;
  const int tid = threadIdx.x, warp = tid >> 5, lane = tid & 31;
  const int n0 = blockIdx.x * BN, m0 = blockIdx.y * BM;
  TS_BEGIN(EPI == EPI_QKV ? 1 : EPI + 2);
  TS_MID(EPI == EPI_QKV ? 1 : EPI + 2, 3);
  constexpr int NCL = CN + CM - 1;
  const int cx = blockIdx.x % CN, cy = blockIdx.y % CM;
  if (tid == 0) {
    for (int i = 0; i < STAGES; i++) { mbar_init(sbar + 8 * i, 1); mbar_init(sbar + 8 * (STAGES + i), 2 * NCL); }
    asm volatile("fence.mbarrier_init.release.cluster;" ::: "memory");
  }
  __syncthreads();
  if constexpr (CN * CM > 1) { cluster_arrive(); cluster_wait(); }
  pdl_launch();
  if (warp >= 8) {
    if constexpr (EPI == EPI_GLU) asm volatile("setmaxnreg.dec.sync.aligned.u32 40;");
    if (warp == 8 && lane == 0) {
      auto load_a = [&](int kt, int s) { tma_2d(sbase + s * Cfg::STAGE_BYTES, &tmA, kt * 64, m0, sbar + 8 * s); };
      auto load_b = [&](int kt, int s) {
        const uint32_t sb = sbase + s * Cfg::STAGE_BYTES + Cfg::A_BYTES;
        tma_3d(sb, &tmB0, 0, kt * 64, blockIdx.x * (BN / 64), sbar + 8 * s);
        if constexpr (NB == 2) tma_3d(sb + (BN / 64) * 8192, &tmB1, 0, kt * 64, blockIdx.x * (BN / 64), sbar + 8 * s);
      };
      if constexpr (EPI == EPI_QKV) {
        const int cta = blockIdx.y * gridDim.x + blockIdx.x;
        const uint32_t xb = S_LEN * DM * 2, xs = 21888;
        if (cta * xs < xb) asm volatile("cp.async.bulk.prefetch.L2.global [%0], %1;" :: "l"((const uint8_t*)resid + (size_t)cta * xs), "r"(min(xs, xb - cta * xs)));
        asm volatile("cp.async.bulk.prefetch.L2.global [%0], %1;" :: "l"((const uint8_t*)out + (size_t)cta * 20480), "r"(20480));
      }
      for (int s = 0; s < STAGES; s++) { mbar_expect_tx(sbar + 8 * s, Cfg::STAGE_BYTES); if (EPI != EPI_QKV || s == 0) load_b(s, s); }
      if (EPI != EPI_QKV) pdl_wait();
      for (int s = 0; s < STAGES; s++) { load_a(s, s); if (EPI == EPI_QKV && s > 0) load_b(s, s); }
      for (int kt = STAGES; kt < KT; kt++) {
        const int s = kt % STAGES;
        mbar_wait(sbar + 8 * (STAGES + s), ((kt / STAGES) - 1) & 1);
        mbar_expect_tx(sbar + 8 * s, Cfg::STAGE_BYTES);
        load_a(kt, s);
        load_b(kt, s);
      }
    }
    if constexpr (EPI == EPI_GLU) {
      if (warp > 8) {
        float2* s_st = (float2*)(sptr + STAGES * Cfg::STAGE_BYTES + 256);
        float* s_cs = (float*)(sptr + STAGES * Cfg::STAGE_BYTES + 256 + 1024);
        pdl_wait();
        for (int r = tid - 288; r < BM; r += 96) {
          const float2* pp = &g_part2[(m0 + r) * 8];
          float s = 0.f;
#pragma unroll
          for (int i = 0; i < 8; i++) s += pp[i].x;
          const float mean = s * (1.0f / DM);
          float q = 0.f;
#pragma unroll
          for (int i = 0; i < 8; i++) { const float2 p = pp[i]; const float d = p.x * (1.0f / 80.f) - mean; q += p.y + 80.f * d * d; }
          s_st[r] = ln_finish(mean, q * (1.0f / DM));
        }
        for (int c = tid - 288; c < BN; c += 96) { s_cs[c] = g_cs_g[n0 + c]; s_cs[BN + c] = g_cs_u[n0 + c]; }
        __threadfence_block();
        asm volatile("bar.arrive 2, 352;" ::: "memory");
      }
    }
    if constexpr (CN * CM > 1) { __syncwarp(); cluster_arrive(); cluster_wait(); }
    return;
  }
  if constexpr (EPI == EPI_GLU) asm volatile("setmaxnreg.inc.sync.aligned.u32 232;");
  const int wg = warp >> 2, g = lane >> 2, t = lane & 3;
  float acc[MB][NB][BN / 2];
#pragma unroll
  for (int mb = 0; mb < MB; mb++)
#pragma unroll
    for (int nb = 0; nb < NB; nb++)
#pragma unroll
      for (int i = 0; i < BN / 2; i++) acc[mb][nb][i] = 0.f;
  for (int kt = 0; kt < KT; kt++) {
    const int s = kt % STAGES;
    mbar_wait(sbar + 8 * s, (kt / STAGES) & 1);
    if (kt == 0) TS_MID(EPI == EPI_QKV ? 1 : EPI + 2, 0);
    const uint32_t sa = sbase + s * Cfg::STAGE_BYTES + wg * (MB * 64 * 128);
    const uint32_t sb = sbase + s * Cfg::STAGE_BYTES + Cfg::A_BYTES;
    wgmma_fence();
#pragma unroll
    for (int ks = 0; ks < 4; ks++) {
#pragma unroll
      for (int mb = 0; mb < MB; mb++) {
        const uint64_t da = make_desc(sa + mb * 8192 + ks * 32, 16, 1024, 1);
#pragma unroll
        for (int nb = 0; nb < NB; nb++) {
          const uint64_t db = make_desc(sb + nb * (BN / 64) * 8192 + ks * 2048, 8192, 1024, 1);
          WG<BN>::mma(acc[mb][nb], da, db, 1);
        }
      }
    }
    wgmma_commit();
    wgmma_wait<1>();
    if (kt > 0 && kt - 1 + STAGES < KT && (tid & 127) < NCL) {
      const uint32_t eb = sbar + 8 * (STAGES + (kt - 1) % STAGES);
      if constexpr (CN * CM > 1) {
        const int i = tid & 127;
        const uint32_t rank = i < CN ? cy * CN + i : ((i - CN + (i - CN >= cy ? 1 : 0)) * CN + cx);
        mbar_arrive_remote(eb, rank);
      } else mbar_arrive(eb);
    }
  }
  wgmma_wait<0>();
#pragma unroll
  for (int mb = 0; mb < MB; mb++)
#pragma unroll
    for (int nb = 0; nb < NB; nb++)
#pragma unroll
      for (int i = 0; i < BN / 2; i++) asm volatile("" : "+f"(acc[mb][nb][i]) :: "memory");
  if constexpr (CN * CM > 1) cluster_arrive();
  TS_MID(EPI == EPI_QKV ? 1 : EPI + 2, 1);
  pdl_wait();
  TS_MID(EPI == EPI_QKV ? 1 : EPI + 2, 2);
  named_bar(1, 256);
  constexpr int LDS = BN * 2 + 16;
  const int ctid = tid;

  if constexpr (EPI == EPI_QKV) {
    const int sec = n0 / DM;
    constexpr int lds = 264;
    __shared__ unsigned int s_kn[8];
    if (ctid < 8) s_kn[ctid] = 0u;
    if (blockIdx.x == 0 && blockIdx.y == 0 && ctid < 32) g_flag[ctid] = 0u;
    float2 cs[BN / 8];
#pragma unroll
    for (int j = 0; j < BN / 8; j++) cs[j] = *(const float2*)&g_cs_qkv[n0 + j * 8 + 2 * t];
#pragma unroll
    for (int mb = 0; mb < MB; mb++) {
      const int r0 = wg * (MB * 64) + mb * 64 + (warp & 3) * 16 + g;
      const float2 st0 = g_stat1[m0 + r0], st1 = g_stat1[m0 + r0 + 8];
      const float sc0 = sec == 0 ? st0.y * QSCALE : st0.y, sc1 = sec == 0 ? st1.y * QSCALE : st1.y;
#pragma unroll
      for (int j = 0; j < BN / 8; j++) {
        const float* a = &acc[mb][0][4 * j];
        *(uint32_t*)(sptr + r0 * lds + j * 16 + t * 4) = pack_bf16(fmaf(-st0.x, cs[j].x, a[0]) * sc0, fmaf(-st0.x, cs[j].y, a[1]) * sc0);
        *(uint32_t*)(sptr + (r0 + 8) * lds + j * 16 + t * 4) = pack_bf16(fmaf(-st1.x, cs[j].x, a[2]) * sc1, fmaf(-st1.x, cs[j].y, a[3]) * sc1);
      }
    }
    named_bar(1, 256);
    {
      const int cbase = n0 - sec * DM;
      const int hfirst = cbase / DH;
      const int j = m0 + ctid;
      uint8_t* dst = (uint8_t*)(sec == 0 ? g_q : (sec == 1 ? g_k : g_v)) + (size_t)(j >> 3) * (sec == 0 ? 512 : 384) + (j & 7) * 16;
      const uint8_t* row = sptr + ctid * 264;
#pragma unroll
      for (int i = 0; i < 8; i++) {
        const int hh = hfirst + i;
        const int cr = hh * DH - cbase;
        if (cr < BN) {
          uint2 v[5];
          bool in[5];
          float s = 0.f;
#pragma unroll
          for (int qd = 0; qd < 5; qd++) {
            const int c = cr + 4 * qd;
            in[qd] = c >= 0 && c < BN;
            v[qd] = in[qd] ? *(const uint2*)(row + c * 2) : make_uint2(0u, 0u);
            s += bf_lo(v[qd].x) * bf_lo(v[qd].x) + bf_hi(v[qd].x) * bf_hi(v[qd].x) + bf_lo(v[qd].y) * bf_lo(v[qd].y) + bf_hi(v[qd].y) * bf_hi(v[qd].y);
          }
          uint8_t* p = dst + (size_t)hh * (sec == 0 ? S_LEN * 64 : S_LEN * 48);
          if (in[0] && in[1]) st_g16(p, make_uint4(v[0].x, v[0].y, v[1].x, v[1].y));
          else if (in[0]) st_g8(p, v[0]);
          else if (in[1]) st_g8(p + 8, v[1]);
          if (in[2] && in[3]) st_g16(p + 128, make_uint4(v[2].x, v[2].y, v[3].x, v[3].y));
          else if (in[2]) st_g8(p + 128, v[2]);
          else if (in[3]) st_g8(p + 136, v[3]);
          if (in[4]) {
            st_g16(p + 256, make_uint4(v[4].x, v[4].y, sec == 0 ? 0u : 0x00003f80u, 0u));
            if (sec == 0) st_g16(p + 384, make_uint4(0u, 0u, 0u, 0u));
          }
          if (sec == 1) {
            const unsigned int mxb = __reduce_max_sync(~0u, __float_as_uint(s) & 0x7fffffffu);
            if (lane == 0) atomicMax(&s_kn[i], mxb);
          }
        }
      }
      if (sec == 1) {
        named_bar(1, 256);
        const int hh = hfirst + ctid;
        if (ctid < 8 && hh * DH < cbase + BN) {
          const bool starts_here = hh * DH >= cbase, ends_here = hh * DH + DH <= cbase + BN;
          const float v = __uint_as_float(s_kn[ctid]);
          float* o = &g_kn[(blockIdx.y * NH + hh) * 2];
          if (starts_here) { o[0] = v; if (ends_here) o[1] = 0.f; }
          else o[1] = v;
        }
      }
    }
  } else if constexpr (EPI == EPI_WO || EPI == EPI_DOWN) {
    const int r0 = wg * 64 + (warp & 3) * 16 + g;
#pragma unroll
    for (int j = 0; j < BN / 8; j++) {
      const float* a = &acc[0][0][4 * j];
      *(uint32_t*)(sptr + r0 * LDS + j * 16 + t * 4) = pack_bf16(a[0], a[1]);
      *(uint32_t*)(sptr + (r0 + 8) * LDS + j * 16 + t * 4) = pack_bf16(a[2], a[3]);
    }
    named_bar(1, 256);
#pragma unroll
    for (int i = 0; i < BM * (BN / 8) / 256; i++) {
      const int idx = i * 256 + ctid, r = idx / (BN / 8), c = idx % (BN / 8);
      const uint4 a = *(const uint4*)(sptr + r * LDS + c * 16);
      const size_t go = (size_t)(m0 + r) * DM + n0 + c * 8;
      const uint4 b = ld_g16(resid + go);
      uint4 o;
      o.x = pack_bf16(bf_lo(a.x) + bf_lo(b.x), bf_hi(a.x) + bf_hi(b.x));
      o.y = pack_bf16(bf_lo(a.y) + bf_lo(b.y), bf_hi(a.y) + bf_hi(b.y));
      o.z = pack_bf16(bf_lo(a.z) + bf_lo(b.z), bf_hi(a.z) + bf_hi(b.z));
      o.w = pack_bf16(bf_lo(a.w) + bf_lo(b.w), bf_hi(a.w) + bf_hi(b.w));
      st_g16(out + go, o);
      if constexpr (EPI == EPI_WO) {
        static_assert(BN == 64, "stats assume 8 lanes per row");
        const float f[8] = {bf_lo(o.x), bf_hi(o.x), bf_lo(o.y), bf_hi(o.y), bf_lo(o.z), bf_hi(o.z), bf_lo(o.w), bf_hi(o.w)};
        float s = 0.f;
#pragma unroll
        for (int k = 0; k < 8; k++) s += f[k];
        s += __shfl_xor_sync(~0u, s, 1); s += __shfl_xor_sync(~0u, s, 2); s += __shfl_xor_sync(~0u, s, 4);
        const float mu = s * (1.0f / 64.f);
        float q = 0.f;
#pragma unroll
        for (int k = 0; k < 8; k++) { const float d = f[k] - mu; q += d * d; }
        q += __shfl_xor_sync(~0u, q, 1); q += __shfl_xor_sync(~0u, q, 2); q += __shfl_xor_sync(~0u, q, 4);
        if (c == 0) g_part2[(m0 + r) * 10 + blockIdx.x] = make_float2(s, q);
      }
    }
  } else {
    const int r0 = wg * 64 + (warp & 3) * 16 + g;
    const float2* s_st = (const float2*)(sptr + STAGES * Cfg::STAGE_BYTES + 256);
    const float* s_cs = (const float*)(sptr + STAGES * Cfg::STAGE_BYTES + 256 + 1024);
    named_bar(2, 352);
    float2 st[2] = {s_st[r0], s_st[r0 + 8]};
#pragma unroll
    for (int j = 0; j < BN / 8; j++) {
      const float2 cg = *(const float2*)&s_cs[j * 8 + 2 * t], cu = *(const float2*)&s_cs[BN + j * 8 + 2 * t];
      const float* a = &acc[0][0][4 * j];
      const float* b = &acc[0][1][4 * j];
#pragma unroll
      for (int e = 0; e < 2; e++) {
        const float2 s_ = st[e];
        const uint32_t gp = pack_bf16(fmaf(-s_.x, cg.x, a[2 * e]) * s_.y, fmaf(-s_.x, cg.y, a[2 * e + 1]) * s_.y);
        const uint32_t up = pack_bf16(fmaf(-s_.x, cu.x, b[2 * e]) * s_.y, fmaf(-s_.x, cu.y, b[2 * e + 1]) * s_.y);
        uint32_t r;
        asm("{\n.reg .b32 z;\nmax.bf16x2 z, %1, %3;\nmul.rn.bf16x2 %0, z, %2;\n}" : "=r"(r) : "r"(gp), "r"(up), "r"(0u));
        *(uint32_t*)(sptr + (r0 + 8 * e) * LDS + j * 16 + t * 4) = r;
      }
    }
    named_bar(1, 256);
#pragma unroll
    for (int i = 0; i < BM * (BN / 8) / 256; i++) {
      const int idx = i * 256 + ctid, r = idx / (BN / 8), c = idx % (BN / 8);
      st_g16(out + (size_t)(m0 + r) * DFF + n0 + c * 8, *(const uint4*)(sptr + r * LDS + c * 16));
    }
  }
  if constexpr (CN * CM > 1) cluster_wait();
  TS_END(EPI == EPI_QKV ? 1 : EPI + 2);
}

constexpr int R_STAGES = 8;
constexpr int R_STAGE_BYTES = 16384 + 5 * 2048;
constexpr int R_BAR_OFF = R_STAGES * R_STAGE_BYTES;
constexpr int R_SMEM = R_BAR_OFF + 256 + 1024;
template <int KDIM, bool STATS>
__global__ void __launch_bounds__(288, 1) gemm_res_kernel(const __grid_constant__ CUtensorMap tmA, const __grid_constant__ CUtensorMap tmB,
                                                          const __nv_bfloat16* resid, __nv_bfloat16* out) {
  constexpr int KT = KDIM / 64;
  extern __shared__ uint8_t smem_raw[];
  const uint32_t sbase = (smem_u32(smem_raw) + 1023u) & ~1023u;
  uint8_t* sptr = smem_raw + (sbase - smem_u32(smem_raw));
  const uint32_t sbar = sbase + R_BAR_OFF;
  const int tid = threadIdx.x, warp = tid >> 5, lane = tid & 31;
  const int n0 = blockIdx.x * 80, m0 = blockIdx.y * 128;
  TS_BEGIN(STATS ? 3 : 5);
  if (tid == 0) {
    for (int i = 0; i < R_STAGES; i++) { mbar_init(sbar + 8 * i, 1); mbar_init(sbar + 8 * (R_STAGES + i), 2); }
    asm volatile("fence.mbarrier_init.release.cluster;" ::: "memory");
  }
  __syncthreads();
  pdl_launch();
  if (warp == 8) {
    if (lane == 0) {
      const uint8_t* wt = (const uint8_t*)(STATS ? g_wo_t : g_wd_t) + (size_t)blockIdx.x * KT * 10240;
      auto load_b = [&](int kt, int s) { bulk_g2s(sbase + s * R_STAGE_BYTES + 16384, wt + kt * 10240, 10240, sbar + 8 * s); };
      pdl_wait();
      for (int s = 0; s < R_STAGES; s++) { mbar_expect_tx(sbar + 8 * s, R_STAGE_BYTES); tma_2d(sbase + s * R_STAGE_BYTES, &tmA, s * 64, m0, sbar + 8 * s); load_b(s, s); }
      for (int kt = R_STAGES; kt < KT; kt++) {
        const int s = kt % R_STAGES;
        mbar_wait(sbar + 8 * (R_STAGES + s), ((kt / R_STAGES) - 1) & 1);
        mbar_expect_tx(sbar + 8 * s, R_STAGE_BYTES);
        tma_2d(sbase + s * R_STAGE_BYTES, &tmA, kt * 64, m0, sbar + 8 * s);
        load_b(kt, s);
      }
    }
    return;
  }
  const int wg = warp >> 2, g = lane >> 2, t = lane & 3;
  pdl_wait();
  uint4 rv[5];
#pragma unroll
  for (int i = 0; i < 5; i++) {
    const int idx = i * 256 + tid, r = idx / 10, c = idx % 10;
    rv[i] = ld_g16(resid + (size_t)(m0 + r) * DM + n0 + c * 8);
  }
  float acc[40];
#pragma unroll
  for (int i = 0; i < 40; i++) acc[i] = 0.f;
  for (int kt = 0; kt < KT; kt++) {
    const int s = kt % R_STAGES;
    mbar_wait(sbar + 8 * s, (kt / R_STAGES) & 1);
    if (kt == 0) TS_MID(STATS ? 3 : 5, 0);
    const uint32_t sa = sbase + s * R_STAGE_BYTES + wg * 8192;
    const uint32_t sb = sbase + s * R_STAGE_BYTES + 16384;
    wgmma_fence();
#pragma unroll
    for (int ks = 0; ks < 4; ks++)
      wgmma_ss_n80(acc, make_desc(sa + ks * 32, 16, 1024, 1), make_desc(sb + ks * 2560, 1280, 128, 0), 1);
    wgmma_commit();
    wgmma_wait<1>();
    if (kt > 0 && kt - 1 + R_STAGES < KT && (tid & 127) == 0) mbar_arrive(sbar + 8 * (R_STAGES + (kt - 1) % R_STAGES));
  }
  wgmma_wait<0>();
#pragma unroll
  for (int i = 0; i < 40; i++) asm volatile("" : "+f"(acc[i]) :: "memory");
  TS_MID(STATS ? 3 : 5, 1);
  named_bar(1, 256);
  constexpr int LDS = 176;
  const int r0 = wg * 64 + (warp & 3) * 16 + g;
#pragma unroll
  for (int i = 0; i < 10; i++) {
    *(uint32_t*)(sptr + r0 * LDS + i * 16 + t * 4) = pack_bf16(acc[4 * i], acc[4 * i + 1]);
    *(uint32_t*)(sptr + (r0 + 8) * LDS + i * 16 + t * 4) = pack_bf16(acc[4 * i + 2], acc[4 * i + 3]);
  }
  named_bar(1, 256);
  TS_MID(STATS ? 3 : 5, 2);
#pragma unroll
  for (int i = 0; i < 5; i++) {
    const int idx = i * 256 + tid, r = idx / 10, c = idx % 10;
    const uint4 a = *(const uint4*)(sptr + r * LDS + c * 16);
    const uint4 b = rv[i];
    uint4 o;
    o.x = pack_bf16(bf_lo(a.x) + bf_lo(b.x), bf_hi(a.x) + bf_hi(b.x));
    o.y = pack_bf16(bf_lo(a.y) + bf_lo(b.y), bf_hi(a.y) + bf_hi(b.y));
    o.z = pack_bf16(bf_lo(a.z) + bf_lo(b.z), bf_hi(a.z) + bf_hi(b.z));
    o.w = pack_bf16(bf_lo(a.w) + bf_lo(b.w), bf_hi(a.w) + bf_hi(b.w));
    st_g16(out + (size_t)(m0 + r) * DM + n0 + c * 8, o);
    if constexpr (STATS) *(uint4*)(sptr + r * LDS + c * 16) = o;
  }
  TS_MID(STATS ? 3 : 5, 3);
  if constexpr (STATS) {
    named_bar(1, 256);
    const int r = tid >> 1, hf = tid & 1;
    float f[40];
#pragma unroll
    for (int i = 0; i < 5; i++) {
      const uint4 v = *(const uint4*)(sptr + r * LDS + hf * 80 + i * 16);
      f[8 * i] = bf_lo(v.x); f[8 * i + 1] = bf_hi(v.x); f[8 * i + 2] = bf_lo(v.y); f[8 * i + 3] = bf_hi(v.y);
      f[8 * i + 4] = bf_lo(v.z); f[8 * i + 5] = bf_hi(v.z); f[8 * i + 6] = bf_lo(v.w); f[8 * i + 7] = bf_hi(v.w);
    }
    float s = 0.f;
#pragma unroll
    for (int i = 0; i < 40; i++) s += f[i];
    s += __shfl_xor_sync(~0u, s, 1);
    const float mu = s * (1.0f / 80.f);
    float q = 0.f;
#pragma unroll
    for (int i = 0; i < 40; i++) { const float d = f[i] - mu; q += d * d; }
    q += __shfl_xor_sync(~0u, q, 1);
    if (hf == 0) g_part2[(m0 + r) * 8 + blockIdx.x] = make_float2(s, q);
  }
  TS_END(STATS ? 3 : 5);
}

#define F_MC 0
constexpr int F_CST = 7, F_DST = 3, F_EST = 5;
constexpr int F_RS = 16384 + 5 * 2048;
constexpr int F_DS = 16384 + 6 * 8192;
constexpr int F_E_OFF = 53248;
constexpr int F_STG_OFF = F_DST * F_DS;
constexpr int F_BAR_OFF = F_STG_OFF + 128 * 176;
constexpr int F_VEC_OFF = F_BAR_OFF + 256;
constexpr int F_SMEM = F_VEC_OFF + 1024 + 1536 + 1024;

__device__ __forceinline__ void flag_wait(const unsigned int* f, unsigned int target) {
  unsigned int v, spins = 0;
  do { asm volatile("ld.acquire.gpu.global.u32 %0, [%1];" : "=r"(v) : "l"(f) : "memory"); } while (v < target && ++spins < (1u << 22));
  asm volatile("fence.proxy.async;" ::: "memory");
}
__device__ __forceinline__ void flag_signal(unsigned int* f) {
  asm volatile("fence.proxy.async;" ::: "memory");
  asm volatile("red.release.gpu.global.add.u32 [%0], 1;" :: "l"(f) : "memory");
}

template <bool STATS>
__device__ __forceinline__ void res_epilogue(float (&acc)[40], const uint4 (&rv)[5], uint8_t* stg, __nv_bfloat16* out, int m0, int n0, int tid, int bx) {
  constexpr int LDS = 176;
  const int warp = tid >> 5, lane = tid & 31;
  const int r0 = (warp >> 2) * 64 + (warp & 3) * 16 + (lane >> 2), t = lane & 3;
#pragma unroll
  for (int i = 0; i < 10; i++) {
    *(uint32_t*)(stg + r0 * LDS + i * 16 + t * 4) = pack_bf16(acc[4 * i], acc[4 * i + 1]);
    *(uint32_t*)(stg + (r0 + 8) * LDS + i * 16 + t * 4) = pack_bf16(acc[4 * i + 2], acc[4 * i + 3]);
  }
  named_bar(1, 256);
#pragma unroll
  for (int i = 0; i < 5; i++) {
    const int idx = i * 256 + tid, r = idx / 10, c = idx % 10;
    const uint4 a = *(const uint4*)(stg + r * LDS + c * 16);
    const uint4 b = rv[i];
    uint4 o;
    o.x = pack_bf16(bf_lo(a.x) + bf_lo(b.x), bf_hi(a.x) + bf_hi(b.x));
    o.y = pack_bf16(bf_lo(a.y) + bf_lo(b.y), bf_hi(a.y) + bf_hi(b.y));
    o.z = pack_bf16(bf_lo(a.z) + bf_lo(b.z), bf_hi(a.z) + bf_hi(b.z));
    o.w = pack_bf16(bf_lo(a.w) + bf_lo(b.w), bf_hi(a.w) + bf_hi(b.w));
    st_g16(out + (size_t)(m0 + r) * DM + n0 + c * 8, o);
    if constexpr (STATS) *(uint4*)(stg + r * LDS + c * 16) = o;
  }
  if constexpr (STATS) {
    named_bar(1, 256);
    const int r = tid >> 1, hf = tid & 1;
    float f[40];
#pragma unroll
    for (int i = 0; i < 5; i++) {
      const uint4 v = *(const uint4*)(stg + r * LDS + hf * 80 + i * 16);
      f[8 * i] = bf_lo(v.x); f[8 * i + 1] = bf_hi(v.x); f[8 * i + 2] = bf_lo(v.y); f[8 * i + 3] = bf_hi(v.y);
      f[8 * i + 4] = bf_lo(v.z); f[8 * i + 5] = bf_hi(v.z); f[8 * i + 6] = bf_lo(v.w); f[8 * i + 7] = bf_hi(v.w);
    }
    float s = 0.f;
#pragma unroll
    for (int i = 0; i < 40; i++) s += f[i];
    s += __shfl_xor_sync(~0u, s, 1);
    const float mu = s * (1.0f / 80.f);
    float q = 0.f;
#pragma unroll
    for (int i = 0; i < 40; i++) { const float d = f[i] - mu; q += d * d; }
    q += __shfl_xor_sync(~0u, q, 1);
    if (hf == 0) g_part2[(m0 + r) * 8 + bx] = make_float2(s, q);
  }
}

__global__ void __launch_bounds__(384, 1) post_kernel(const __grid_constant__ CUtensorMap tmO, const __grid_constant__ CUtensorMap tmWo,
                                                      const __grid_constant__ CUtensorMap tmH, const __grid_constant__ CUtensorMap tmWg,
                                                      const __grid_constant__ CUtensorMap tmWu, const __grid_constant__ CUtensorMap tmAct,
                                                      const __grid_constant__ CUtensorMap tmWd, const __nv_bfloat16* x, __nv_bfloat16* out) {
  extern __shared__ uint8_t smem_raw[];
  const uint32_t sbase = (smem_u32(smem_raw) + 1023u) & ~1023u;
  uint8_t* sptr = smem_raw + (sbase - smem_u32(smem_raw));
  const uint32_t bC = sbase + F_BAR_OFF, bD = bC + 16 * F_CST, bE = bD + 16 * F_DST;
  const int tid = threadIdx.x, warp = tid >> 5, lane = tid & 31;
  const int bx = blockIdx.x, rb = blockIdx.y, m0 = rb * 128, cx = bx & 1;
  TS_BEGIN(3);
  if (tid == 0) {
    for (int i = 0; i < F_CST; i++) { mbar_init(bC + 8 * i, 1); mbar_init(bC + 8 * (F_CST + i), F_MC ? 4 : 2); }
    for (int i = 0; i < F_DST; i++) { mbar_init(bD + 8 * i, 1); mbar_init(bD + 8 * (F_DST + i), F_MC ? 4 : 2); }
    for (int i = 0; i < F_EST; i++) { mbar_init(bE + 8 * i, 1); mbar_init(bE + 8 * (F_EST + i), F_MC ? 4 : 2); }
    asm volatile("fence.mbarrier_init.release.cluster;" ::: "memory");
  }
  __syncthreads();
  if (F_MC) { cluster_arrive(); cluster_wait(); }
  if (warp >= 8) {
    asm volatile("setmaxnreg.dec.sync.aligned.u32 40;");
    if (warp == 8) {
      if (lane == 0) {
        auto load_a = [&](const CUtensorMap* tm, uint32_t stage, int kt, uint32_t bar) {
          if (F_MC) tma_2d_mc(stage + cx * 8192, tm, kt * 64, m0 + cx * 64, bar, (uint16_t)3); else tma_2d(stage, tm, kt * 64, m0, bar);
        };
        for (int s = 0; s < F_CST; s++) { mbar_expect_tx(bC + 8 * s, F_RS); if (s < 3) tma_3d(sbase + s * F_RS + 16384, &tmWo, 0, s * 64, bx * 5, bC + 8 * s); }
        pdl_wait();
        for (int s = 0; s < F_CST; s++) { load_a(&tmO, sbase + s * F_RS, s, bC + 8 * s); if (s >= 3) tma_3d(sbase + s * F_RS + 16384, &tmWo, 0, s * 64, bx * 5, bC + 8 * s); }
        for (int kt = F_CST; kt < 10; kt++) {
          const int s = kt - F_CST;
          mbar_wait(bC + 8 * (F_CST + s), 0);
          mbar_expect_tx(bC + 8 * s, F_RS);
          load_a(&tmO, sbase + s * F_RS, kt, bC + 8 * s);
          tma_3d(sbase + s * F_RS + 16384, &tmWo, 0, kt * 64, bx * 5, bC + 8 * s);
        }
        auto load_bd = [&](int kt, int s) {
          tma_3d(sbase + s * F_DS + 16384, &tmWg, 0, kt * 64, bx * 3, bD + 8 * s);
          tma_3d(sbase + s * F_DS + 16384 + 3 * 8192, &tmWu, 0, kt * 64, bx * 3, bD + 8 * s);
        };
        for (int s = 0; s < F_DST; s++) { mbar_wait(bD + 8 * (F_DST + s), 0); mbar_expect_tx(bD + 8 * s, F_DS); load_bd(s, s); }
        flag_wait(&g_flag[rb], 8);
        for (int s = 0; s < F_DST; s++) load_a(&tmH, sbase + s * F_DS, s, bD + 8 * s);
        for (int kt = F_DST; kt < 10; kt++) {
          const int s = kt % F_DST;
          mbar_wait(bD + 8 * (F_DST + s), (kt / F_DST) & 1);
          mbar_expect_tx(bD + 8 * s, F_DS);
          load_a(&tmH, sbase + s * F_DS, kt, bD + 8 * s);
          load_bd(kt, s);
        }
        const uint32_t eb = sbase + F_E_OFF;
        for (int s = 0; s < F_EST; s++) { mbar_wait(bE + 8 * (F_EST + s), 0); mbar_expect_tx(bE + 8 * s, F_RS); tma_3d(eb + s * F_RS + 16384, &tmWd, 0, s * 64, bx * 5, bE + 8 * s); }
        flag_wait(&g_flag[16 + rb], 8);
        for (int s = 0; s < F_EST; s++) load_a(&tmAct, eb + s * F_RS, s, bE + 8 * s);
        for (int kt = F_EST; kt < 24; kt++) {
          const int s = kt % F_EST;
          mbar_wait(bE + 8 * (F_EST + s), (kt / F_EST) & 1);
          mbar_expect_tx(bE + 8 * s, F_RS);
          load_a(&tmAct, eb + s * F_RS, kt, bE + 8 * s);
          tma_3d(eb + s * F_RS + 16384, &tmWd, 0, kt * 64, bx * 5, bE + 8 * s);
        }
      }
    } else {
      float2* s_st = (float2*)(sptr + F_VEC_OFF);
      float* s_cs = (float*)(sptr + F_VEC_OFF + 1024);
      pdl_wait();
      for (int c = tid - 288; c < 192; c += 96) { s_cs[c] = g_cs_g[bx * 192 + c]; s_cs[192 + c] = g_cs_u[bx * 192 + c]; }
      flag_wait(&g_flag[rb], 8);
      for (int r = tid - 288; r < 128; r += 96) {
        const float2* pp = &g_part2[(m0 + r) * 8];
        float2 p[8];
        float s = 0.f;
#pragma unroll
        for (int i = 0; i < 8; i++) { asm volatile("ld.global.v2.f32 {%0, %1}, [%2];" : "=f"(p[i].x), "=f"(p[i].y) : "l"(pp + i) : "memory"); s += p[i].x; }
        const float mean = s * (1.0f / DM);
        float q = 0.f;
#pragma unroll
        for (int i = 0; i < 8; i++) { const float d = p[i].x * (1.0f / 80.f) - mean; q += p[i].y + 80.f * d * d; }
        s_st[r] = ln_finish(mean, q * (1.0f / DM));
      }
      __threadfence_block();
      asm volatile("bar.arrive 2, 352;" ::: "memory");
    }
    if (F_MC) { __syncwarp(); cluster_arrive(); cluster_wait(); }
    return;
  }
  asm volatile("setmaxnreg.inc.sync.aligned.u32 232;");
  const int wg = warp >> 2, g = lane >> 2, t = lane & 3;
  auto release = [&](uint32_t bar) { if (F_MC) { if ((tid & 127) < 2) mbar_arrive_remote(bar, (tid & 127) ^ cx); } else if ((tid & 127) == 0) mbar_arrive(bar); };
  const int n0 = bx * 80;
  uint4 rv[5];
  pdl_wait();
  {
#pragma unroll
    for (int i = 0; i < 5; i++) { const int idx = i * 256 + tid, r = idx / 10, c = idx % 10; rv[i] = ld_g16(x + (size_t)(m0 + r) * DM + n0 + c * 8); }
    float acc[40];
#pragma unroll
    for (int i = 0; i < 40; i++) acc[i] = 0.f;
    for (int kt = 0; kt < 10; kt++) {
      const int s = kt % F_CST;
      mbar_wait(bC + 8 * s, kt / F_CST);
      if (kt == 0) TS_MID(3, 0);
      const uint32_t sa = sbase + s * F_RS + wg * 8192, sb = sbase + s * F_RS + 16384;
      wgmma_fence();
#pragma unroll
      for (int ks = 0; ks < 4; ks++) wgmma_ss_n80(acc, make_desc(sa + ks * 32, 16, 1024, 1), make_desc(sb + ks * 512, 2048, 256, 3), 1);
      wgmma_commit();
      wgmma_wait<1>();
      if (kt > 0 && kt - 1 + F_CST < 10) release(bC + 8 * (F_CST + kt - 1));
    }
    wgmma_wait<0>();
#pragma unroll
    for (int i = 0; i < 40; i++) asm volatile("" : "+f"(acc[i]) :: "memory");
    for (int s = 0; s < F_DST; s++) release(bD + 8 * (F_DST + s));
    TS_MID(3, 1);
    res_epilogue<true>(acc, rv, sptr + F_STG_OFF, g_h, m0, n0, tid, bx);
    __threadfence();
    named_bar(1, 256);
    if (tid == 0) flag_signal(&g_flag[rb]);
    TS_END(3);
  }
  {
    float acc[2][96];
#pragma unroll
    for (int i = 0; i < 96; i++) { acc[0][i] = 0.f; acc[1][i] = 0.f; }
    for (int kt = 0; kt < 10; kt++) {
      const int s = kt % F_DST;
      mbar_wait(bD + 8 * s, (kt / F_DST) & 1);
      if (kt == 0) TS_MID(4, 0);
      const uint32_t sa = sbase + s * F_DS + wg * 8192, sb = sbase + s * F_DS + 16384;
      wgmma_fence();
#pragma unroll
      for (int ks = 0; ks < 4; ks++) {
        const uint64_t da = make_desc(sa + ks * 32, 16, 1024, 1);
        wgmma_ss_n192(acc[0], da, make_desc(sb + ks * 2048, 8192, 1024, 1), 1);
        wgmma_ss_n192(acc[1], da, make_desc(sb + 3 * 8192 + ks * 2048, 8192, 1024, 1), 1);
      }
      wgmma_commit();
      wgmma_wait<1>();
      if (kt > 0 && kt - 1 + F_DST < 10) release(bD + 8 * (F_DST + (kt - 1) % F_DST));
    }
    wgmma_wait<0>();
#pragma unroll
    for (int i = 0; i < 96; i++) { asm volatile("" : "+f"(acc[0][i]) :: "memory"); asm volatile("" : "+f"(acc[1][i]) :: "memory"); }
    for (int s = 0; s < F_EST; s++) release(bE + 8 * (F_EST + s));
    TS_MID(4, 1);
    named_bar(1, 256);
    named_bar(2, 352);
    constexpr int LDS = 400;
    const float2* s_st = (const float2*)(sptr + F_VEC_OFF);
    const float* s_cs = (const float*)(sptr + F_VEC_OFF + 1024);
    const int r0 = wg * 64 + (warp & 3) * 16 + g;
    const float2 st[2] = {s_st[r0], s_st[r0 + 8]};
#pragma unroll
    for (int j = 0; j < 24; j++) {
      const float2 cg = *(const float2*)&s_cs[j * 8 + 2 * t], cu = *(const float2*)&s_cs[192 + j * 8 + 2 * t];
      const float* a = &acc[0][4 * j];
      const float* b = &acc[1][4 * j];
#pragma unroll
      for (int e = 0; e < 2; e++) {
        const float2 s_ = st[e];
        const uint32_t gp = pack_bf16(fmaf(-s_.x, cg.x, a[2 * e]) * s_.y, fmaf(-s_.x, cg.y, a[2 * e + 1]) * s_.y);
        const uint32_t up = pack_bf16(fmaf(-s_.x, cu.x, b[2 * e]) * s_.y, fmaf(-s_.x, cu.y, b[2 * e + 1]) * s_.y);
        uint32_t r;
        asm("{\n.reg .b32 z;\nmax.bf16x2 z, %1, %3;\nmul.rn.bf16x2 %0, z, %2;\n}" : "=r"(r) : "r"(gp), "r"(up), "r"(0u));
        *(uint32_t*)(sptr + (r0 + 8 * e) * LDS + j * 16 + t * 4) = r;
      }
    }
    named_bar(1, 256);
#pragma unroll
    for (int i = 0; i < 12; i++) {
      const int idx = i * 256 + tid, r = idx / 24, c = idx % 24;
      st_g16(g_act + (size_t)(m0 + r) * DFF + bx * 192 + c * 8, *(const uint4*)(sptr + r * LDS + c * 16));
    }
    __threadfence();
    named_bar(1, 256);
    if (tid == 0) flag_signal(&g_flag[16 + rb]);
    TS_END(4);
  }
  {
#pragma unroll
    for (int i = 0; i < 5; i++) { const int idx = i * 256 + tid, r = idx / 10, c = idx % 10; rv[i] = ld_g16(g_h + (size_t)(m0 + r) * DM + n0 + c * 8); }
    float acc[40];
#pragma unroll
    for (int i = 0; i < 40; i++) acc[i] = 0.f;
    const uint32_t eb = sbase + F_E_OFF;
    for (int kt = 0; kt < 24; kt++) {
      const int s = kt % F_EST;
      mbar_wait(bE + 8 * s, (kt / F_EST) & 1);
      if (kt == 0) TS_MID(5, 0);
      const uint32_t sa = eb + s * F_RS + wg * 8192, sb = eb + s * F_RS + 16384;
      wgmma_fence();
#pragma unroll
      for (int ks = 0; ks < 4; ks++) wgmma_ss_n80(acc, make_desc(sa + ks * 32, 16, 1024, 1), make_desc(sb + ks * 512, 2048, 256, 3), 1);
      wgmma_commit();
      wgmma_wait<1>();
      if (kt > 0 && kt - 1 + F_EST < 24) release(bE + 8 * (F_EST + (kt - 1) % F_EST));
    }
    wgmma_wait<0>();
#pragma unroll
    for (int i = 0; i < 40; i++) asm volatile("" : "+f"(acc[i]) :: "memory");
    if (F_MC) cluster_arrive();
    TS_MID(5, 1);
    res_epilogue<false>(acc, rv, sptr + F_STG_OFF, out, m0, n0, tid, bx);
    if (F_MC) cluster_wait();
    TS_END(5);
  }
}

#define POLY_NUM 5
__device__ __forceinline__ float ex2_poly(float x, int shl23) {
  const float MAGIC = 12582912.f;
  const float tt = x + MAGIC;
  const float f = x - (tt - MAGIC);
  float p = fmaf(0.0013276472454890609f, f, 0.009675540961325169f);
  p = fmaf(p, f, 0.05550713092088699f);
  p = fmaf(p, f, 0.24022120237350464f);
  p = fmaf(p, f, 0.6931469440460205f);
  p = fmaf(p, f, 1.0000001192092896f);
  return __int_as_float(__float_as_int(tt) * shl23 + __float_as_int(p));
}
constexpr int KV_BYTES = S_LEN * 48;
constexpr int ATT_SMEM = 2 * KV_BYTES + 256 + 32768;
constexpr int ATT_BODY = 8;

__global__ void __launch_bounds__(512, 1) attn_kernel(int shl23, const __nv_bfloat16* __restrict__ wg_, const __nv_bfloat16* __restrict__ wu_,
                                                      const __nv_bfloat16* __restrict__ wo_, const __nv_bfloat16* __restrict__ wd_) {
  extern __shared__ __align__(1024) uint8_t smem[];
  if (blockIdx.x >= 128) {
    pdl_launch();
    const int e = blockIdx.x - 128, half = threadIdx.x >> 8;
    for (int c = e * 512 + threadIdx.x; c < (DM + DFF) * (DM / 8); c += 2048) {
      const bool isd = c >= DM * (DM / 8);
      const int cc = isd ? c - DM * (DM / 8) : c;
      const int k = cc / (DM / 8), nc = cc % (DM / 8);
      const uint4 v = __ldg((const uint4*)((isd ? wd_ : wo_) + (size_t)k * DM + nc * 8));
      const int j = nc / 10, kt = k >> 6;
      st_g16((uint8_t*)(isd ? g_wd_t : g_wo_t) + (size_t)(j * (isd ? DFF / 64 : DM / 64) + kt) * 10240 + ((k & 63) >> 3) * 1280 + (nc % 10) * 128 + (k & 7) * 16, v);
    }
    float (*red)[65] = (float (*)[65])(smem + half * 16384);
    for (int b = e * 12 + half; b < e * 12 + 12; b += 2) {
      if (b < 24) colsum64(wg_, DFF, b * 64, g_cs_g, red, threadIdx.x & 255, 1 + half);
      else colsum64(wu_, DFF, (b - 24) * 64, g_cs_u, red, threadIdx.x & 255, 1 + half);
    }
    return;
  }
  const int h = blockIdx.x >> 2, qb = blockIdx.x & 3;
  const uint32_t sK = smem_u32(smem), sV = sK + KV_BYTES, sBar = sV + KV_BYTES;
  const int tid = threadIdx.x;
  TS_BEGIN(2);
  if (tid == 0) {
    for (int i = 0; i < 9; i++) mbar_init(sBar + 8 * i, 1);
    asm volatile("fence.mbarrier_init.release.cluster;" ::: "memory");
  }
  __syncthreads();
  pdl_launch();
  pdl_wait();
  TS_MID(2, 0);
  const uint8_t* gk = (const uint8_t*)(g_k + (size_t)h * S_LEN * 24);
  const uint8_t* gv = (const uint8_t*)(g_v + (size_t)h * S_LEN * 24);
  auto load_kv = [&](int i0, int i1) {
    for (int i = i0; i < i1; i++) {
      mbar_expect_tx(sBar + 8 * i, 2 * 12288);
      bulk_g2s(sK + i * 12288, gk + i * 12288, 12288, sBar + 8 * i);
      bulk_g2s(sV + i * 12288, gv + i * 12288, 12288, sBar + 8 * i);
    }
  };
  if (tid == 0) {
    mbar_expect_tx(sBar + 64, 32768);
    bulk_g2s(sBar + 256, (const uint8_t*)g_q + ((size_t)h * S_LEN + qb * 512) * 64, 32768, sBar + 64);
    load_kv(0, 2);
  }
  float ka = 0.f, kb = 0.f;
#pragma unroll
  for (int i = 0; i < 8; i++) {
    const float2 v = *(const float2*)&g_kn[(i * NH + h) * 2];
    ka = (v.x > ka || v.x != v.x) ? v.x : ka;
    kb = (v.y > kb || v.y != v.y) ? v.y : kb;
  }
  bool fast;
  {
    const float kn = sqrtf(ka + kb);
    mbar_wait(sBar + 64, 0);
    if (tid == 0) load_kv(2, 8);
    uint8_t* qrow = smem + 2 * KV_BYTES + 256 + (tid >> 3) * 512 + (tid & 7) * 16;
    const uint4 c0 = *(const uint4*)qrow, c1 = *(const uint4*)(qrow + 128);
    const uint2 c2 = *(const uint2*)(qrow + 256);
    auto sq = [](uint32_t u) { const float a = bf_lo(u), b = bf_hi(u); return a * a + b * b; };
    const float n2 = sq(c0.x) + sq(c0.y) + sq(c0.z) + sq(c0.w) + sq(c1.x) + sq(c1.y) + sq(c1.z) + sq(c1.w) + sq(c2.x) + sq(c2.y);
    const float m = ceilf(sqrtf(n2) * kn * 1.001f) + 1.f;
    fast = __syncthreads_or(!(m <= 62.f)) == 0;
    if (fast) *(uint32_t*)(qrow + 256 + 8) = pack_bf16(-m, 0.f);
    asm volatile("fence.proxy.async.shared::cta;" ::: "memory");
    __syncthreads();
  }
  auto write_out = [&](float (&O)[12], int it) {
    uint32_t tid2;
    asm volatile("mov.u32 %0, %%tid.x;" : "=r"(tid2));
    const int lane2 = tid2 & 31, t2 = lane2 & 3;
    const int qq = (blockIdx.x & 3) * 512 + (it * 4 + (tid2 >> 7)) * 64 + ((tid2 >> 5) & 3) * 16 + (lane2 >> 2);
    const float l0 = __shfl_sync(~0u, O[8], (lane2 & ~3) | 2), l1 = __shfl_sync(~0u, O[10], (lane2 & ~3) | 2);
    const float r0 = 1.f / l0, r1 = 1.f / l1;
    uint32_t* o0 = (uint32_t*)(g_o + (size_t)qq * DM + (blockIdx.x >> 2) * DH);
    uint32_t* o1 = o0 + 8 * DM / 2;
    o0[t2] = pack_bf16(O[0] * r0, O[1] * r0); o1[t2] = pack_bf16(O[2] * r1, O[3] * r1);
    o0[t2 + 4] = pack_bf16(O[4] * r0, O[5] * r0); o1[t2 + 4] = pack_bf16(O[6] * r1, O[7] * r1);
    if (t2 < 2) { o0[t2 + 8] = pack_bf16(O[8] * r0, O[9] * r0); o1[t2 + 8] = pack_bf16(O[10] * r1, O[11] * r1); }
  };
  TS_MID(2, 1);
  if (fast) {
#pragma unroll 1
    for (int it = 0; it < 2; it++) {
      const uint64_t dq = make_desc(sBar + 256 + (it * 4 + (tid >> 7)) * 4096, 128, 512, 0);
      float O[12];
#pragma unroll
      for (int i = 0; i < 12; i++) { O[i] = 0.f; asm volatile("" : "+f"(O[i]) :: "memory"); }
      float S[2][32];
      uint32_t P[16];
#pragma unroll 1
      for (int jb = 0; jb < 32 / ATT_BODY; jb++) {
        if (it == 0) { for (int c = 0; c < ATT_BODY / 4; c++) mbar_wait(sBar + 8 * (jb * (ATT_BODY / 4) + c), 0); }
        const uint64_t dk0 = make_desc(sK + jb * ATT_BODY * 8 * 384, 128, 384, 0);
        const uint64_t dv0 = make_desc(sV + jb * ATT_BODY * 8 * 384, 384, 128, 0);
        wgmma_fence();
        wgmma_ss_n64_k(S[0], dq, dk0, 0);
        wgmma_ss_n64_k(S[0], dq + (256 >> 4), dk0 + (256 >> 4), 1);
        wgmma_commit();
#pragma unroll
        for (int u = 0; u < ATT_BODY; u++) {
          if (u + 1 < ATT_BODY) {
            const uint64_t dk = dk0 + (((u + 1) * 8 * 384) >> 4);
            wgmma_fence();
            wgmma_ss_n64_k(S[(u + 1) & 1], dq, dk, 0);
            wgmma_ss_n64_k(S[(u + 1) & 1], dq + (256 >> 4), dk + (256 >> 4), 1);
            wgmma_commit();
          }
          if (u == 0 || u == ATT_BODY - 1) wgmma_wait<1>(); else wgmma_wait<2>();
#pragma unroll
          for (int i = 0; i < 32; i++) asm volatile("" : "+f"(S[u & 1][i]) :: "memory");
          const uint64_t dv = dv0 + ((u * 8 * 384) >> 4);
#pragma unroll
          for (int hf = 0; hf < 2; hf++) {
            if (hf == 1 && u > 0) { if (u == ATT_BODY - 1) wgmma_wait<1>(); else wgmma_wait<2>(); }
#pragma unroll
            for (int i = hf * 8; i < hf * 8 + 8; i++) {
              const bool usepoly = ((i + 1) * POLY_NUM / 16) != (i * POLY_NUM / 16);
              float a, b;
              if (usepoly) { a = ex2_poly(S[u & 1][2 * i], shl23); b = ex2_poly(S[u & 1][2 * i + 1], shl23); }
              else { a = ex2_mufu(S[u & 1][2 * i]); b = ex2_mufu(S[u & 1][2 * i + 1]); }
              P[i] = pack_bf16(a, b);
            }
            wgmma_fence();
#pragma unroll
            for (int ks = hf * 2; ks < hf * 2 + 2; ks++)
              wgmma_rs_n24_tb(O, P[4 * ks], P[4 * ks + 1], P[4 * ks + 2], P[4 * ks + 3], dv + ((ks * 768) >> 4), 1);
            wgmma_commit();
          }
        }
        wgmma_wait<0>();
      }
#pragma unroll
      for (int i = 0; i < 12; i++) asm volatile("" : "+f"(O[i]) :: "memory");
      write_out(O, it);
      if (it == 0) TS_MID(2, 2);
    }
  } else {
#pragma unroll 1
    for (int it = 0; it < 2; it++) {
      const uint64_t dq = make_desc(sBar + 256 + (it * 4 + (tid >> 7)) * 4096, 128, 512, 0);
      float O[12];
#pragma unroll
      for (int i = 0; i < 12; i++) { O[i] = 0.f; asm volatile("" : "+f"(O[i]) :: "memory"); }
      float S[32];
      float mx0 = -INFINITY, mx1 = -INFINITY;
#pragma unroll 1
      for (int j = 0; j < 32; j++) {
        if (it == 0 && (j & 3) == 0) mbar_wait(sBar + 8 * (j >> 2), 0);
        const uint64_t dk = make_desc(sK + j * 8 * 384, 128, 384, 0);
        wgmma_fence();
        wgmma_ss_n64_k(S, dq, dk, 0);
        wgmma_ss_n64_k(S, dq + (256 >> 4), dk + (256 >> 4), 1);
        wgmma_commit();
        wgmma_wait<0>();
#pragma unroll
        for (int i = 0; i < 8; i++) {
          mx0 = fmaxf(mx0, fmaxf(S[4 * i], S[4 * i + 1]));
          mx1 = fmaxf(mx1, fmaxf(S[4 * i + 2], S[4 * i + 3]));
        }
      }
      mx0 = fmaxf(mx0, __shfl_xor_sync(~0u, mx0, 1)); mx0 = fmaxf(mx0, __shfl_xor_sync(~0u, mx0, 2));
      mx1 = fmaxf(mx1, __shfl_xor_sync(~0u, mx1, 1)); mx1 = fmaxf(mx1, __shfl_xor_sync(~0u, mx1, 2));
#pragma unroll 1
      for (int j = 0; j < 32; j++) {
        const uint64_t dk = make_desc(sK + j * 8 * 384, 128, 384, 0);
        wgmma_fence();
        wgmma_ss_n64_k(S, dq, dk, 0);
        wgmma_ss_n64_k(S, dq + (256 >> 4), dk + (256 >> 4), 1);
        wgmma_commit();
        wgmma_wait<0>();
        uint32_t P[16];
#pragma unroll
        for (int i = 0; i < 8; i++) {
          P[2 * i] = pack_bf16(ex2_mufu(S[4 * i] - mx0), ex2_mufu(S[4 * i + 1] - mx0));
          P[2 * i + 1] = pack_bf16(ex2_mufu(S[4 * i + 2] - mx1), ex2_mufu(S[4 * i + 3] - mx1));
        }
        wgmma_fence();
        const uint64_t dv = make_desc(sV + j * 8 * 384, 384, 128, 0);
#pragma unroll
        for (int ks = 0; ks < 4; ks++)
          wgmma_rs_n24_tb(O, P[4 * ks], P[4 * ks + 1], P[4 * ks + 2], P[4 * ks + 3], dv + ((ks * 768) >> 4), 1);
        wgmma_commit();
        wgmma_wait<0>();
      }
#pragma unroll
      for (int i = 0; i < 12; i++) asm volatile("" : "+f"(O[i]) :: "memory");
      write_out(O, it);
    }
  }
  TS_END(2);
}

typedef CUresult (*EncodeFn)(CUtensorMap*, CUtensorMapDataType, cuuint32_t, void*, const cuuint64_t*, const cuuint64_t*, const cuuint32_t*,
                             const cuuint32_t*, CUtensorMapInterleave, CUtensorMapSwizzle, CUtensorMapL2promotion, CUtensorMapFloatOOBfill);
static EncodeFn get_encode() {
  static EncodeFn fn = nullptr;
  if (!fn) {
    void* p = nullptr; cudaDriverEntryPointQueryResult st;
    cudaGetDriverEntryPoint("cuTensorMapEncodeTiled", &p, cudaEnableDefault, &st);
    fn = (EncodeFn)p;
  }
  return fn;
}
static CUtensorMap make_map(const void* ptr, int rows, int cols, int box_rows, int box_cols = 64) {
  CUtensorMap m;
  cuuint64_t dims[2] = {(cuuint64_t)cols, (cuuint64_t)rows};
  cuuint64_t strides[1] = {(cuuint64_t)cols * 2};
  cuuint32_t box[2] = {(cuuint32_t)box_cols, (cuuint32_t)box_rows};
  cuuint32_t es[2] = {1, 1};
  get_encode()(&m, CU_TENSOR_MAP_DATA_TYPE_BFLOAT16, 2, const_cast<void*>(ptr), dims, strides, box, es, CU_TENSOR_MAP_INTERLEAVE_NONE,
               box_cols == 64 ? CU_TENSOR_MAP_SWIZZLE_128B : (box_cols == 32 ? CU_TENSOR_MAP_SWIZZLE_64B : CU_TENSOR_MAP_SWIZZLE_32B), CU_TENSOR_MAP_L2_PROMOTION_L2_128B, CU_TENSOR_MAP_FLOAT_OOB_FILL_NONE);
  return m;
}
static CUtensorMap make_map_w(const void* ptr, int rows, int cols, int bc, int nblk) {
  CUtensorMap m;
  cuuint64_t dims[3] = {(cuuint64_t)bc, (cuuint64_t)rows, (cuuint64_t)(cols / bc)};
  cuuint64_t strides[2] = {(cuuint64_t)cols * 2, (cuuint64_t)bc * 2};
  cuuint32_t box[3] = {(cuuint32_t)bc, 64, (cuuint32_t)nblk};
  cuuint32_t es[3] = {1, 1, 1};
  get_encode()(&m, CU_TENSOR_MAP_DATA_TYPE_BFLOAT16, 3, const_cast<void*>(ptr), dims, strides, box, es, CU_TENSOR_MAP_INTERLEAVE_NONE,
               bc == 64 ? CU_TENSOR_MAP_SWIZZLE_128B : (bc == 32 ? CU_TENSOR_MAP_SWIZZLE_64B : CU_TENSOR_MAP_SWIZZLE_32B),
               CU_TENSOR_MAP_L2_PROMOTION_L2_128B, CU_TENSOR_MAP_FLOAT_OOB_FILL_NONE);
  return m;
}
template <typename... KArgs, typename... Args>
static void launch(void (*kern)(KArgs...), dim3 grid, dim3 block, size_t smem, bool pdl, dim3 cluster, Args... args) {
  cudaLaunchConfig_t cfg = {};
  cfg.gridDim = grid; cfg.blockDim = block; cfg.dynamicSmemBytes = smem; cfg.stream = cudaStreamPerThread;
  cudaLaunchAttribute at[2];
  int na = 0;
  if (pdl) { at[na].id = cudaLaunchAttributeProgrammaticStreamSerialization; at[na].val.programmaticStreamSerializationAllowed = 1; na++; }
  if (cluster.x * cluster.y > 1) { at[na].id = cudaLaunchAttributeClusterDimension; at[na].val.clusterDim.x = cluster.x; at[na].val.clusterDim.y = cluster.y; at[na].val.clusterDim.z = 1; na++; }
  cfg.attrs = at; cfg.numAttrs = na;
  cudaLaunchKernelEx(&cfg, kern, KArgs(args)...);
}

extern "C" void kernel_launch(void* const* d_in, const int* in_sizes, int n_in, void* d_out, int out_size) {
  const __nv_bfloat16* x = (const __nv_bfloat16*)d_in[0];
  const __nv_bfloat16* wqkv = (const __nv_bfloat16*)d_in[1];
  const __nv_bfloat16* wo = (const __nv_bfloat16*)d_in[2];
  const __nv_bfloat16* wgate = (const __nv_bfloat16*)d_in[4];
  const __nv_bfloat16* wup = (const __nv_bfloat16*)d_in[5];
  const __nv_bfloat16* wdown = (const __nv_bfloat16*)d_in[6];
  __nv_bfloat16* out = (__nv_bfloat16*)d_out;
  void *p_o, *p_h, *p_act;
  cudaGetSymbolAddress(&p_o, g_o); cudaGetSymbolAddress(&p_h, g_h); cudaGetSymbolAddress(&p_act, g_act);

#define A_CN 1
#define A_CM 1
#define D_CN 1
#define D_CM 1
  auto kA = gemm_kernel<256, 128, 1, DM, 4, EPI_QKV, 1, A_CN, A_CM>;
  auto kC = gemm_res_kernel<DM, true>;
  auto kD = gemm_kernel<128, 192, 2, DM, 3, EPI_GLU, 1, D_CN, D_CM>;
  auto kE = gemm_res_kernel<DFF, false>;
  constexpr int smA = GemmCfg<256, 128, 1, 4>::SMEM, smC = R_SMEM, smD = GemmCfg<128, 192, 2, 3>::SMEM;
  cudaFuncSetAttribute(kA, cudaFuncAttributeMaxDynamicSharedMemorySize, smA);
  cudaFuncSetAttribute(kC, cudaFuncAttributeMaxDynamicSharedMemorySize, smC);
  cudaFuncSetAttribute(kD, cudaFuncAttributeMaxDynamicSharedMemorySize, smD);
  cudaFuncSetAttribute(kE, cudaFuncAttributeMaxDynamicSharedMemorySize, smC);
  cudaFuncSetAttribute(attn_kernel, cudaFuncAttributeMaxDynamicSharedMemorySize, ATT_SMEM);

  const CUtensorMap tm_x = make_map(x, S_LEN, DM, 256), tm_wqkv = make_map_w(wqkv, DM, 3 * DM, 64, 2);
  const CUtensorMap tm_o = make_map(p_o, S_LEN, DM, 128), tm_wo = make_map_w(wo, DM, DM, 16, 5);
  const CUtensorMap tm_h = make_map(p_h, S_LEN, DM, 128), tm_wg = make_map_w(wgate, DM, DFF, 64, 3), tm_wu = make_map_w(wup, DM, DFF, 64, 3);
  const CUtensorMap tm_act = make_map(p_act, S_LEN, DFF, 128), tm_wd = make_map_w(wdown, DFF, DM, 16, 5);

  launch(pre_kernel, dim3(12), dim3(1024), 0, false, dim3(1, 1), x, wqkv);
  launch(kA, dim3(15, 8), dim3(288), smA, true, dim3(A_CN, A_CM), tm_x, tm_wqkv, tm_wqkv, x, (__nv_bfloat16*)wqkv);
  launch(attn_kernel, dim3(132), dim3(512), ATT_SMEM, true, dim3(1, 1), 0x800000, wgate, wup, wo, wdown);
  launch(kC, dim3(8, 16), dim3(288), smC, true, dim3(1, 1), tm_o, tm_wo, x, (__nv_bfloat16*)p_h);
  launch(kD, dim3(8, 16), dim3(384), smD, true, dim3(D_CN, D_CM), tm_h, tm_wg, tm_wu, (const __nv_bfloat16*)nullptr, (__nv_bfloat16*)p_act);
  launch(kE, dim3(8, 16), dim3(288), smC, true, dim3(1, 1), tm_act, tm_wd, (const __nv_bfloat16*)p_h, out);
}
```

```cpp
#include <cuda_runtime.h>
#include <cuda_bf16.h>
#include <cuda.h>
#include <stdint.h>

constexpr int S_LEN = 2048, DM = 640, NH = 32, DH = 20, DFF = 1536;

__device__ __align__(1024) __nv_bfloat16 g_q[NH * S_LEN * 32];
__device__ __align__(1024) __nv_bfloat16 g_k[NH * S_LEN * 24];
__device__ __align__(1024) __nv_bfloat16 g_v[NH * S_LEN * 24];
__device__ __align__(1024) __nv_bfloat16 g_o[S_LEN * DM];
__device__ __align__(1024) __nv_bfloat16 g_h[S_LEN * DM];
__device__ __align__(1024) __nv_bfloat16 g_act[S_LEN * DFF];
__device__ __align__(1024) __nv_bfloat16 g_wo_t[DM * DM];
__device__ __align__(1024) __nv_bfloat16 g_wd_t[DFF * DM];
__device__ float g_kn[8 * NH * 2];
__device__ float2 g_stat1[S_LEN];
__device__ float g_cs_qkv[3 * DM];
__device__ float g_cs_g[DFF];
__device__ float g_cs_u[DFF];
__device__ unsigned int g_flag[32];
__device__ float2 g_part2[S_LEN * 10];

#define TS_BEGIN(k)
#define TS_END(k)
#define TS_MID(k, i)
__device__ __forceinline__ uint32_t smem_u32(const void* p) { return (uint32_t)__cvta_generic_to_shared(p); }
__device__ __forceinline__ void mbar_init(uint32_t bar, uint32_t cnt) { asm volatile("mbarrier.init.shared::cta.b64 [%0], %1;" :: "r"(bar), "r"(cnt)); }
__device__ __forceinline__ void mbar_expect_tx(uint32_t bar, uint32_t bytes) { asm volatile("mbarrier.arrive.expect_tx.shared::cta.b64 _, [%0], %1;" :: "r"(bar), "r"(bytes) : "memory"); }
__device__ __forceinline__ void mbar_arrive(uint32_t bar) { asm volatile("mbarrier.arrive.shared::cta.b64 _, [%0];" :: "r"(bar) : "memory"); }
__device__ __forceinline__ void mbar_wait(uint32_t bar, uint32_t parity) {
  uint32_t done;
  uint32_t spins = 0;
  do {
    asm volatile("{\n.reg .pred P1;\nmbarrier.try_wait.parity.shared::cta.b64 P1, [%1], %2;\nselp.u32 %0, 1, 0, P1;\n}" : "=r"(done) : "r"(bar), "r"(parity) : "memory");
  } while (!done && ++spins < (1u << 24));
}
__device__ __forceinline__ void bulk_g2s(uint32_t dst, const void* src, uint32_t bytes, uint32_t bar) {
  asm volatile("cp.async.bulk.shared::cluster.global.mbarrier::complete_tx::bytes [%0], [%1], %2, [%3];" :: "r"(dst), "l"(src), "r"(bytes), "r"(bar) : "memory");
}
__device__ __forceinline__ void tma_2d(uint32_t dst, const CUtensorMap* tm, int c0, int c1, uint32_t bar) {
  asm volatile("cp.async.bulk.tensor.2d.shared::cluster.global.mbarrier::complete_tx::bytes [%0], [%1, {%3, %4}], [%2];"
               :: "r"(dst), "l"(tm), "r"(bar), "r"(c0), "r"(c1) : "memory");
}
__device__ __forceinline__ void tma_3d(uint32_t dst, const CUtensorMap* tm, int c0, int c1, int c2, uint32_t bar) {
  asm volatile("cp.async.bulk.tensor.3d.shared::cluster.global.mbarrier::complete_tx::bytes [%0], [%1, {%3, %4, %5}], [%2];"
               :: "r"(dst), "l"(tm), "r"(bar), "r"(c0), "r"(c1), "r"(c2) : "memory");
}
__device__ __forceinline__ void tma_2d_mc(uint32_t dst, const CUtensorMap* tm, int c0, int c1, uint32_t bar, uint16_t mask) {
  asm volatile("cp.async.bulk.tensor.2d.shared::cluster.global.mbarrier::complete_tx::bytes.multicast::cluster [%0], [%1, {%3, %4}], [%2], %5;"
               :: "r"(dst), "l"(tm), "r"(bar), "r"(c0), "r"(c1), "h"(mask) : "memory");
}
__device__ __forceinline__ void mbar_arrive_remote(uint32_t bar, uint32_t rank) {
  asm volatile("{\n.reg .b32 ra;\nmapa.shared::cluster.u32 ra, %0, %1;\nmbarrier.arrive.release.cluster.shared::cluster.b64 _, [ra];\n}" :: "r"(bar), "r"(rank) : "memory");
}
__device__ __forceinline__ void cluster_arrive() { asm volatile("barrier.cluster.arrive.release.aligned;" ::: "memory"); }
__device__ __forceinline__ void cluster_wait() { asm volatile("barrier.cluster.wait.acquire.aligned;" ::: "memory"); }
__device__ __forceinline__ void wgmma_fence() { asm volatile("wgmma.fence.sync.aligned;" ::: "memory"); }
__device__ __forceinline__ void wgmma_commit() { asm volatile("wgmma.commit_group.sync.aligned;" ::: "memory"); }
template <int N> __device__ __forceinline__ void wgmma_wait() { asm volatile("wgmma.wait_group.sync.aligned %0;" :: "n"(N) : "memory"); }
__device__ __forceinline__ void pdl_wait() { asm volatile("griddepcontrol.wait;" ::: "memory"); }
__device__ __forceinline__ void pdl_launch() { asm volatile("griddepcontrol.launch_dependents;" ::: "memory"); }
__device__ __forceinline__ void named_bar(int id, int n) { asm volatile("bar.sync %0, %1;" :: "r"(id), "r"(n) : "memory"); }
__device__ __forceinline__ uint64_t make_desc(uint32_t addr, uint32_t lbo, uint32_t sbo, uint32_t swz) {
  return (uint64_t)((addr & 0x3FFFF) >> 4) | ((uint64_t)(lbo >> 4) << 16) | ((uint64_t)(sbo >> 4) << 32) | ((uint64_t)swz << 62);
}
__device__ __forceinline__ void st_g16(void* p, uint4 v) { asm volatile("st.global.v4.b32 [%0], {%1, %2, %3, %4};" :: "l"(p), "r"(v.x), "r"(v.y), "r"(v.z), "r"(v.w) : "memory"); }
__device__ __forceinline__ void st_g8(void* p, uint2 v) { asm volatile("st.global.v2.b32 [%0], {%1, %2};" :: "l"(p), "r"(v.x), "r"(v.y) : "memory"); }
__device__ __forceinline__ uint4 ld_g16(const void* p) { uint4 v; asm volatile("ld.global.v4.b32 {%0, %1, %2, %3}, [%4];" : "=r"(v.x), "=r"(v.y), "=r"(v.z), "=r"(v.w) : "l"(p) : "memory"); return v; }
__device__ __forceinline__ uint32_t pack_bf16(float lo, float hi) { uint32_t r; asm("cvt.rn.bf16x2.f32 %0, %1, %2;" : "=r"(r) : "f"(hi), "f"(lo)); return r; }
__device__ __forceinline__ float bf_lo(uint32_t u) { return __uint_as_float(u << 16); }
__device__ __forceinline__ float bf_hi(uint32_t u) { return __uint_as_float(u & 0xffff0000u); }
__device__ __forceinline__ float bf_round(float x) { return __bfloat162float(__float2bfloat16_rn(x)); }
__device__ __forceinline__ float ex2_mufu(float x) { float y; asm("ex2.approx.ftz.f32 %0, %1;" : "=f"(y) : "f"(x)); return y; }

__device__ __forceinline__ void wgmma_ss_n80(float (&d)[40], uint64_t da, uint64_t db, int scale_d) {
  asm volatile("{\n.reg .pred p;\nsetp.ne.b32 p, %42, 0;\n"
    "wgmma.mma_async.sync.aligned.m64n80k16.f32.bf16.bf16 {%0,%1,%2,%3,%4,%5,%6,%7,%8,%9,%10,%11,%12,%13,%14,%15,%16,%17,%18,%19,%20,%21,%22,%23,%24,%25,%26,%27,%28,%29,%30,%31,%32,%33,%34,%35,%36,%37,%38,%39}, %40, %41, p, 1, 1, 0, 1;\n}\n"
    : "+f"(d[0]),"+f"(d[1]),"+f"(d[2]),"+f"(d[3]),"+f"(d[4]),"+f"(d[5]),"+f"(d[6]),"+f"(d[7]),"+f"(d[8]),"+f"(d[9]),"+f"(d[10]),"+f"(d[11]),"+f"(d[12]),"+f"(d[13]),"+f"(d[14]),"+f"(d[15]),"+f"(d[16]),"+f"(d[17]),"+f"(d[18]),"+f"(d[19]),"+f"(d[20]),"+f"(d[21]),"+f"(d[22]),"+f"(d[23]),"+f"(d[24]),"+f"(d[25]),"+f"(d[26]),"+f"(d[27]),"+f"(d[28]),"+f"(d[29]),"+f"(d[30]),"+f"(d[31]),"+f"(d[32]),"+f"(d[33]),"+f"(d[34]),"+f"(d[35]),"+f"(d[36]),"+f"(d[37]),"+f"(d[38]),"+f"(d[39])
    : "l"(da), "l"(db), "r"(scale_d));
}
__device__ __forceinline__ void wgmma_ss_n128(float (&d)[64], uint64_t da, uint64_t db, int scale_d) {
  asm volatile("{\n.reg .pred p;\nsetp.ne.b32 p, %66, 0;\n"
    "wgmma.mma_async.sync.aligned.m64n128k16.f32.bf16.bf16 {%0,%1,%2,%3,%4,%5,%6,%7,%8,%9,%10,%11,%12,%13,%14,%15,%16,%17,%18,%19,%20,%21,%22,%23,%24,%25,%26,%27,%28,%29,%30,%31,%32,%33,%34,%35,%36,%37,%38,%39,%40,%41,%42,%43,%44,%45,%46,%47,%48,%49,%50,%51,%52,%53,%54,%55,%56,%57,%58,%59,%60,%61,%62,%63}, %64, %65, p, 1, 1, 0, 1;\n}\n"
    : "+f"(d[0]),"+f"(d[1]),"+f"(d[2]),"+f"(d[3]),"+f"(d[4]),"+f"(d[5]),"+f"(d[6]),"+f"(d[7]),"+f"(d[8]),"+f"(d[9]),"+f"(d[10]),"+f"(d[11]),"+f"(d[12]),"+f"(d[13]),"+f"(d[14]),"+f"(d[15]),"+f"(d[16]),"+f"(d[17]),"+f"(d[18]),"+f"(d[19]),"+f"(d[20]),"+f"(d[21]),"+f"(d[22]),"+f"(d[23]),"+f"(d[24]),"+f"(d[25]),"+f"(d[26]),"+f"(d[27]),"+f"(d[28]),"+f"(d[29]),"+f"(d[30]),"+f"(d[31]),"+f"(d[32]),"+f"(d[33]),"+f"(d[34]),"+f"(d[35]),"+f"(d[36]),"+f"(d[37]),"+f"(d[38]),"+f"(d[39]),"+f"(d[40]),"+f"(d[41]),"+f"(d[42]),"+f"(d[43]),"+f"(d[44]),"+f"(d[45]),"+f"(d[46]),"+f"(d[47]),"+f"(d[48]),"+f"(d[49]),"+f"(d[50]),"+f"(d[51]),"+f"(d[52]),"+f"(d[53]),"+f"(d[54]),"+f"(d[55]),"+f"(d[56]),"+f"(d[57]),"+f"(d[58]),"+f"(d[59]),"+f"(d[60]),"+f"(d[61]),"+f"(d[62]),"+f"(d[63])
    : "l"(da), "l"(db), "r"(scale_d));
}
__device__ __forceinline__ void wgmma_ss_n192(float (&d)[96], uint64_t da, uint64_t db, int scale_d) {
  asm volatile("{\n.reg .pred p;\nsetp.ne.b32 p, %98, 0;\n"
    "wgmma.mma_async.sync.aligned.m64n192k16.f32.bf16.bf16 {%0,%1,%2,%3,%4,%5,%6,%7,%8,%9,%10,%11,%12,%13,%14,%15,%16,%17,%18,%19,%20,%21,%22,%23,%24,%25,%26,%27,%28,%29,%30,%31,%32,%33,%34,%35,%36,%37,%38,%39,%40,%41,%42,%43,%44,%45,%46,%47,%48,%49,%50,%51,%52,%53,%54,%55,%56,%57,%58,%59,%60,%61,%62,%63,%64,%65,%66,%67,%68,%69,%70,%71,%72,%73,%74,%75,%76,%77,%78,%79,%80,%81,%82,%83,%84,%85,%86,%87,%88,%89,%90,%91,%92,%93,%94,%95}, %96, %97, p, 1, 1, 0, 1;\n}\n"
    : "+f"(d[0]),"+f"(d[1]),"+f"(d[2]),"+f"(d[3]),"+f"(d[4]),"+f"(d[5]),"+f"(d[6]),"+f"(d[7]),"+f"(d[8]),"+f"(d[9]),"+f"(d[10]),"+f"(d[11]),"+f"(d[12]),"+f"(d[13]),"+f"(d[14]),"+f"(d[15]),"+f"(d[16]),"+f"(d[17]),"+f"(d[18]),"+f"(d[19]),"+f"(d[20]),"+f"(d[21]),"+f"(d[22]),"+f"(d[23]),"+f"(d[24]),"+f"(d[25]),"+f"(d[26]),"+f"(d[27]),"+f"(d[28]),"+f"(d[29]),"+f"(d[30]),"+f"(d[31]),"+f"(d[32]),"+f"(d[33]),"+f"(d[34]),"+f"(d[35]),"+f"(d[36]),"+f"(d[37]),"+f"(d[38]),"+f"(d[39]),"+f"(d[40]),"+f"(d[41]),"+f"(d[42]),"+f"(d[43]),"+f"(d[44]),"+f"(d[45]),"+f"(d[46]),"+f"(d[47]),"+f"(d[48]),"+f"(d[49]),"+f"(d[50]),"+f"(d[51]),"+f"(d[52]),"+f"(d[53]),"+f"(d[54]),"+f"(d[55]),"+f"(d[56]),"+f"(d[57]),"+f"(d[58]),"+f"(d[59]),"+f"(d[60]),"+f"(d[61]),"+f"(d[62]),"+f"(d[63]),"+f"(d[64]),"+f"(d[65]),"+f"(d[66]),"+f"(d[67]),"+f"(d[68]),"+f"(d[69]),"+f"(d[70]),"+f"(d[71]),"+f"(d[72]),"+f"(d[73]),"+f"(d[74]),"+f"(d[75]),"+f"(d[76]),"+f"(d[77]),"+f"(d[78]),"+f"(d[79]),"+f"(d[80]),"+f"(d[81]),"+f"(d[82]),"+f"(d[83]),"+f"(d[84]),"+f"(d[85]),"+f"(d[86]),"+f"(d[87]),"+f"(d[88]),"+f"(d[89]),"+f"(d[90]),"+f"(d[91]),"+f"(d[92]),"+f"(d[93]),"+f"(d[94]),"+f"(d[95])
    : "l"(da), "l"(db), "r"(scale_d));
}
__device__ __forceinline__ void wgmma_ss_n64_k(float (&d)[32], uint64_t da, uint64_t db, int scale_d) {
  asm volatile("{\n.reg .pred p;\nsetp.ne.b32 p, %34, 0;\n"
    "wgmma.mma_async.sync.aligned.m64n64k16.f32.bf16.bf16 {%0,%1,%2,%3,%4,%5,%6,%7,%8,%9,%10,%11,%12,%13,%14,%15,%16,%17,%18,%19,%20,%21,%22,%23,%24,%25,%26,%27,%28,%29,%30,%31}, %32, %33, p, 1, 1, 0, 0;\n}\n"
    : "+f"(d[0]),"+f"(d[1]),"+f"(d[2]),"+f"(d[3]),"+f"(d[4]),"+f"(d[5]),"+f"(d[6]),"+f"(d[7]),"+f"(d[8]),"+f"(d[9]),"+f"(d[10]),"+f"(d[11]),"+f"(d[12]),"+f"(d[13]),"+f"(d[14]),"+f"(d[15]),"+f"(d[16]),"+f"(d[17]),"+f"(d[18]),"+f"(d[19]),"+f"(d[20]),"+f"(d[21]),"+f"(d[22]),"+f"(d[23]),"+f"(d[24]),"+f"(d[25]),"+f"(d[26]),"+f"(d[27]),"+f"(d[28]),"+f"(d[29]),"+f"(d[30]),"+f"(d[31])
    : "l"(da), "l"(db), "r"(scale_d));
}
__device__ __forceinline__ void wgmma_rs_n24_tb(float (&d)[12], uint32_t a0, uint32_t a1, uint32_t a2, uint32_t a3, uint64_t db, int scale_d) {
  asm volatile("{\n.reg .pred p;\nsetp.ne.b32 p, %17, 0;\n"
    "wgmma.mma_async.sync.aligned.m64n24k16.f32.bf16.bf16 {%0,%1,%2,%3,%4,%5,%6,%7,%8,%9,%10,%11}, {%12,%13,%14,%15}, %16, p, 1, 1, 1;\n}\n"
    : "+f"(d[0]),"+f"(d[1]),"+f"(d[2]),"+f"(d[3]),"+f"(d[4]),"+f"(d[5]),"+f"(d[6]),"+f"(d[7]),"+f"(d[8]),"+f"(d[9]),"+f"(d[10]),"+f"(d[11])
    : "r"(a0), "r"(a1), "r"(a2), "r"(a3), "l"(db), "r"(scale_d));
}

constexpr int PRE_ROW_BLOCKS = 64;
constexpr int PRE_COL_BLOCKS = 3 * DM / 64;
__device__ __forceinline__ float2 ln_finish(float mean, float var) {
  float mb = bf_round(mean);
  float s = bf_round(sqrtf(bf_round(bf_round(var) + 1e-5f)));
  return make_float2(mb, 1.0f / s);
}
__device__ __forceinline__ void colsum64(const __nv_bfloat16* __restrict__ w, int ld, int c0, float* __restrict__ dst, float (*red)[65], int tid, int bar_id) {
  const int cg = tid & 7, r0 = tid >> 3;
  float acc[8];
#pragma unroll
  for (int i = 0; i < 8; i++) acc[i] = 0.f;
#pragma unroll 10
  for (int r = r0; r < DM; r += 32) {
    uint4 v = __ldg((const uint4*)(w + (size_t)r * ld + c0 + cg * 8));
    acc[0] += bf_lo(v.x); acc[1] += bf_hi(v.x); acc[2] += bf_lo(v.y); acc[3] += bf_hi(v.y);
    acc[4] += bf_lo(v.z); acc[5] += bf_hi(v.z); acc[6] += bf_lo(v.w); acc[7] += bf_hi(v.w);
  }
#pragma unroll
  for (int i = 0; i < 8; i++) red[r0][cg * 8 + i] = acc[i];
  named_bar(bar_id, 256);
  if (tid < 64) {
    float s = 0.f;
#pragma unroll
    for (int r = 0; r < 32; r++) s += red[r][tid];
    dst[c0 + tid] = s;
  }
  named_bar(bar_id, 256);
}
__global__ void __launch_bounds__(1024) pre_kernel(const __nv_bfloat16* __restrict__ x, const __nv_bfloat16* __restrict__ wqkv) {
  TS_BEGIN(0);
  pdl_launch();
  __shared__ float red[51][161];
  const int tid = threadIdx.x, lane = tid & 31, warp = tid >> 5;
  {
    const int ch = tid % 20, rl = tid / 20;
    if (rl < 51) {
      const __nv_bfloat16* w = wqkv + blockIdx.x * 160 + ch * 8;
      uint4 v[13];
#pragma unroll
      for (int i = 0; i < 13; i++) { const int r = rl + i * 51; v[i] = r < DM ? __ldg((const uint4*)(w + (size_t)r * (3 * DM))) : make_uint4(0, 0, 0, 0); }
      float acc[8];
#pragma unroll
      for (int i = 0; i < 8; i++) acc[i] = 0.f;
#pragma unroll
      for (int i = 0; i < 13; i++) {
        acc[0] += bf_lo(v[i].x); acc[1] += bf_hi(v[i].x); acc[2] += bf_lo(v[i].y); acc[3] += bf_hi(v[i].y);
        acc[4] += bf_lo(v[i].z); acc[5] += bf_hi(v[i].z); acc[6] += bf_lo(v[i].w); acc[7] += bf_hi(v[i].w);
      }
#pragma unroll
      for (int i = 0; i < 8; i++) red[rl][ch * 8 + i] = acc[i];
    }
  }
  const int rbeg = blockIdx.x * 171, rend = min(rbeg + 171, S_LEN);
  for (int row0 = rbeg + warp * 2; row0 < rend; row0 += 64) {
    uint4 v[2][3];
#pragma unroll
    for (int k = 0; k < 2; k++) {
      const int row = min(row0 + k, rend - 1);
      const uint4* p = (const uint4*)(x + (size_t)row * DM);
      v[k][0] = __ldg(p + lane); v[k][1] = __ldg(p + 32 + lane);
      v[k][2] = lane < 16 ? __ldg(p + 64 + lane) : make_uint4(0, 0, 0, 0);
    }
#pragma unroll
    for (int k = 0; k < 2; k++) {
      float f[24];
      const uint32_t u[12] = {v[k][0].x, v[k][0].y, v[k][0].z, v[k][0].w, v[k][1].x, v[k][1].y, v[k][1].z, v[k][1].w, v[k][2].x, v[k][2].y, v[k][2].z, v[k][2].w};
#pragma unroll
      for (int j = 0; j < 12; j++) { f[2 * j] = bf_lo(u[j]); f[2 * j + 1] = bf_hi(u[j]); }
      float s = 0.f;
#pragma unroll
      for (int j = 0; j < 24; j++) s += f[j];
#pragma unroll
      for (int o = 16; o; o >>= 1) s += __shfl_xor_sync(~0u, s, o);
      const float mean = s * (1.0f / DM);
      float q = 0.f;
#pragma unroll
      for (int j = 0; j < 16; j++) { const float d = f[j] - mean; q += d * d; }
      if (lane < 16) {
#pragma unroll
        for (int j = 16; j < 24; j++) { const float d = f[j] - mean; q += d * d; }
      }
#pragma unroll
      for (int o = 16; o; o >>= 1) q += __shfl_xor_sync(~0u, q, o);
      if (lane == 0 && row0 + k < rend) g_stat1[row0 + k] = ln_finish(mean, q * (1.0f / DM));
    }
  }
  __syncthreads();
  if (tid < 160) {
    float s = 0.f;
#pragma unroll 17
    for (int r = 0; r < 51; r++) s += red[r][tid];
    g_cs_qkv[blockIdx.x * 160 + tid] = s;
  }
  TS_END(0);
}

enum { EPI_QKV = 0, EPI_WO = 1, EPI_GLU = 2, EPI_DOWN = 3 };
template <int N> struct WG;
template <> struct WG<128> { static __device__ __forceinline__ void mma(float (&d)[64], uint64_t a, uint64_t b, int s) { wgmma_ss_n128(d, a, b, s); } };
template <> struct WG<192> { static __device__ __forceinline__ void mma(float (&d)[96], uint64_t a, uint64_t b, int s) { wgmma_ss_n192(d, a, b, s); } };

template <int BM, int BN, int NB, int STAGES> struct GemmCfg {
  static constexpr int A_BYTES = BM * 128;
  static constexpr int B_BYTES = NB * (BN / 64) * 8192;
  static constexpr int STAGE_BYTES = A_BYTES + B_BYTES;
  static constexpr int SMEM = STAGES * STAGE_BYTES + 1024   + 256   + 4096  ;
};

constexpr float QSCALE = 0.22360679774997896f * 1.4426950408889634f;

template <int BM, int BN, int NB, int KDIM, int STAGES, int EPI, int MINB, int CN, int CM>
__global__ void __launch_bounds__(EPI == EPI_GLU ? 384 : 288, MINB) gemm_kernel(const __grid_constant__ CUtensorMap tmA, const __grid_constant__ CUtensorMap tmB0,
                                                         const __grid_constant__ CUtensorMap tmB1,
                                                         const __nv_bfloat16* resid, __nv_bfloat16* out) {
  using Cfg = GemmCfg<BM, BN, NB, STAGES>;
  constexpr int MB = BM / 128;
  constexpr int KT = KDIM / 64;
  extern __shared__ uint8_t smem_raw[];
  const uint32_t sbase = (smem_u32(smem_raw) + 1023u) & ~1023u;
  uint8_t* sptr = smem_raw + (sbase - smem_u32(smem_raw));
  const uint32_t sbar = sbase + STAGES * Cfg::STAGE_BYTES;
  const int tid = threadIdx.x, warp = tid >> 5, lane = tid & 31;
  const int n0 = blockIdx.x * BN, m0 = blockIdx.y * BM;
  TS_BEGIN(EPI == EPI_QKV ? 1 : EPI + 2);
  TS_MID(EPI == EPI_QKV ? 1 : EPI + 2, 3);
  constexpr int NCL = CN + CM - 1;
  const int cx = blockIdx.x % CN, cy = blockIdx.y % CM;
  if (tid == 0) {
    for (int i = 0; i < STAGES; i++) { mbar_init(sbar + 8 * i, 1); mbar_init(sbar + 8 * (STAGES + i), 2 * NCL); }
    asm volatile("fence.mbarrier_init.release.cluster;" ::: "memory");
  }
  __syncthreads();
  if constexpr (CN * CM > 1) { cluster_arrive(); cluster_wait(); }
  pdl_launch();
  if (warp >= 8) {
    if constexpr (EPI == EPI_GLU) asm volatile("setmaxnreg.dec.sync.aligned.u32 40;");
    if (warp == 8 && lane == 0) {
      auto load_a = [&](int kt, int s) { tma_2d(sbase + s * Cfg::STAGE_BYTES, &tmA, kt * 64, m0, sbar + 8 * s); };
      auto load_b = [&](int kt, int s) {
        const uint32_t sb = sbase + s * Cfg::STAGE_BYTES + Cfg::A_BYTES;
        tma_3d(sb, &tmB0, 0, kt * 64, blockIdx.x * (BN / 64), sbar + 8 * s);
        if constexpr (NB == 2) tma_3d(sb + (BN / 64) * 8192, &tmB1, 0, kt * 64, blockIdx.x * (BN / 64), sbar + 8 * s);
      };
      if constexpr (EPI == EPI_QKV) {
        const int cta = blockIdx.y * gridDim.x + blockIdx.x;
        const uint32_t xb = S_LEN * DM * 2, xs = 21888;
        if (cta * xs < xb) asm volatile("cp.async.bulk.prefetch.L2.global [%0], %1;" :: "l"((const uint8_t*)resid + (size_t)cta * xs), "r"(min(xs, xb - cta * xs)));
        asm volatile("cp.async.bulk.prefetch.L2.global [%0], %1;" :: "l"((const uint8_t*)out + (size_t)cta * 20480), "r"(20480));
      }
      for (int s = 0; s < STAGES; s++) { mbar_expect_tx(sbar + 8 * s, Cfg::STAGE_BYTES); if (EPI != EPI_QKV || s == 0) load_b(s, s); }
      if (EPI != EPI_QKV) pdl_wait();
      for (int s = 0; s < STAGES; s++) { load_a(s, s); if (EPI == EPI_QKV && s > 0) load_b(s, s); }
      for (int kt = STAGES; kt < KT; kt++) {
        const int s = kt % STAGES;
        mbar_wait(sbar + 8 * (STAGES + s), ((kt / STAGES) - 1) & 1);
        mbar_expect_tx(sbar + 8 * s, Cfg::STAGE_BYTES);
        load_a(kt, s);
        load_b(kt, s);
      }
    }
    if constexpr (EPI == EPI_GLU) {
      if (warp > 8) {
        float2* s_st = (float2*)(sptr + STAGES * Cfg::STAGE_BYTES + 256);
        float* s_cs = (float*)(sptr + STAGES * Cfg::STAGE_BYTES + 256 + 1024);
        pdl_wait();
        for (int r = tid - 288; r < BM; r += 96) {
          const float2* pp = &g_part2[(m0 + r) * 8];
          float s = 0.f;
#pragma unroll
          for (int i = 0; i < 8; i++) s += pp[i].x;
          const float mean = s * (1.0f / DM);
          float q = 0.f;
#pragma unroll
          for (int i = 0; i < 8; i++) { const float2 p = pp[i]; const float d = p.x * (1.0f / 80.f) - mean; q += p.y + 80.f * d * d; }
          s_st[r] = ln_finish(mean, q * (1.0f / DM));
        }
        for (int c = tid - 288; c < BN; c += 96) { s_cs[c] = g_cs_g[n0 + c]; s_cs[BN + c] = g_cs_u[n0 + c]; }
        __threadfence_block();
        asm volatile("bar.arrive 2, 352;" ::: "memory");
      }
    }
    if constexpr (CN * CM > 1) { __syncwarp(); cluster_arrive(); cluster_wait(); }
    return;
  }
  if constexpr (EPI == EPI_GLU) asm volatile("setmaxnreg.inc.sync.aligned.u32 232;");
  const int wg = warp >> 2, g = lane >> 2, t = lane & 3;
  float acc[MB][NB][BN / 2];
#pragma unroll
  for (int mb = 0; mb < MB; mb++)
#pragma unroll
    for (int nb = 0; nb < NB; nb++)
#pragma unroll
      for (int i = 0; i < BN / 2; i++) acc[mb][nb][i] = 0.f;
  for (int kt = 0; kt < KT; kt++) {
    const int s = kt % STAGES;
    mbar_wait(sbar + 8 * s, (kt / STAGES) & 1);
    if (kt == 0) TS_MID(EPI == EPI_QKV ? 1 : EPI + 2, 0);
    const uint32_t sa = sbase + s * Cfg::STAGE_BYTES + wg * (MB * 64 * 128);
    const uint32_t sb = sbase + s * Cfg::STAGE_BYTES + Cfg::A_BYTES;
    wgmma_fence();
#pragma unroll
    for (int ks = 0; ks < 4; ks++) {
#pragma unroll
      for (int mb = 0; mb < MB; mb++) {
        const uint64_t da = make_desc(sa + mb * 8192 + ks * 32, 16, 1024, 1);
#pragma unroll
        for (int nb = 0; nb < NB; nb++) {
          const uint64_t db = make_desc(sb + nb * (BN / 64) * 8192 + ks * 2048, 8192, 1024, 1);
          WG<BN>::mma(acc[mb][nb], da, db, 1);
        }
      }
    }
    wgmma_commit();
    wgmma_wait<1>();
    if (kt > 0 && kt - 1 + STAGES < KT && (tid & 127) < NCL) {
      const uint32_t eb = sbar + 8 * (STAGES + (kt - 1) % STAGES);
      if constexpr (CN * CM > 1) {
        const int i = tid & 127;
        const uint32_t rank = i < CN ? cy * CN + i : ((i - CN + (i - CN >= cy ? 1 : 0)) * CN + cx);
        mbar_arrive_remote(eb, rank);
      } else mbar_arrive(eb);
    }
  }
  wgmma_wait<0>();
#pragma unroll
  for (int mb = 0; mb < MB; mb++)
#pragma unroll
    for (int nb = 0; nb < NB; nb++)
#pragma unroll
      for (int i = 0; i < BN / 2; i++) asm volatile("" : "+f"(acc[mb][nb][i]) :: "memory");
  if constexpr (CN * CM > 1) cluster_arrive();
  TS_MID(EPI == EPI_QKV ? 1 : EPI + 2, 1);
  pdl_wait();
  TS_MID(EPI == EPI_QKV ? 1 : EPI + 2, 2);
  named_bar(1, 256);
  constexpr int LDS = BN * 2 + 16;
  const int ctid = tid;

  if constexpr (EPI == EPI_QKV) {
    const int sec = n0 / DM;
    constexpr int lds = 264;
    __shared__ unsigned int s_kn[8];
    if (ctid < 8) s_kn[ctid] = 0u;
    if (blockIdx.x == 0 && blockIdx.y == 0 && ctid < 32) g_flag[ctid] = 0u;
    float2 cs[BN / 8];
#pragma unroll
    for (int j = 0; j < BN / 8; j++) cs[j] = *(const float2*)&g_cs_qkv[n0 + j * 8 + 2 * t];
#pragma unroll
    for (int mb = 0; mb < MB; mb++) {
      const int r0 = wg * (MB * 64) + mb * 64 + (warp & 3) * 16 + g;
      const float2 st0 = g_stat1[m0 + r0], st1 = g_stat1[m0 + r0 + 8];
      const float sc0 = sec == 0 ? st0.y * QSCALE : st0.y, sc1 = sec == 0 ? st1.y * QSCALE : st1.y;
#pragma unroll
      for (int j = 0; j < BN / 8; j++) {
        const float* a = &acc[mb][0][4 * j];
        *(uint32_t*)(sptr + r0 * lds + j * 16 + t * 4) = pack_bf16(fmaf(-st0.x, cs[j].x, a[0]) * sc0, fmaf(-st0.x, cs[j].y, a[1]) * sc0);
        *(uint32_t*)(sptr + (r0 + 8) * lds + j * 16 + t * 4) = pack_bf16(fmaf(-st1.x, cs[j].x, a[2]) * sc1, fmaf(-st1.x, cs[j].y, a[3]) * sc1);
      }
    }
    named_bar(1, 256);
    {
      const int cbase = n0 - sec * DM;
      const int hfirst = cbase / DH;
      const int j = m0 + ctid;
      uint8_t* dst = (uint8_t*)(sec == 0 ? g_q : (sec == 1 ? g_k : g_v)) + (size_t)(j >> 3) * (sec == 0 ? 512 : 384) + (j & 7) * 16;
      const uint8_t* row = sptr + ctid * 264;
#pragma unroll
      for (int i = 0; i < 8; i++) {
        const int hh = hfirst + i;
        const int cr = hh * DH - cbase;
        if (cr < BN) {
          uint2 v[5];
          bool in[5];
          float s = 0.f;
#pragma unroll
          for (int qd = 0; qd < 5; qd++) {
            const int c = cr + 4 * qd;
            in[qd] = c >= 0 && c < BN;
            v[qd] = in[qd] ? *(const uint2*)(row + c * 2) : make_uint2(0u, 0u);
            s += bf_lo(v[qd].x) * bf_lo(v[qd].x) + bf_hi(v[qd].x) * bf_hi(v[qd].x) + bf_lo(v[qd].y) * bf_lo(v[qd].y) + bf_hi(v[qd].y) * bf_hi(v[qd].y);
          }
          uint8_t* p = dst + (size_t)hh * (sec == 0 ? S_LEN * 64 : S_LEN * 48);
          if (in[0] && in[1]) st_g16(p, make_uint4(v[0].x, v[0].y, v[1].x, v[1].y));
          else if (in[0]) st_g8(p, v[0]);
          else if (in[1]) st_g8(p + 8, v[1]);
          if (in[2] && in[3]) st_g16(p + 128, make_uint4(v[2].x, v[2].y, v[3].x, v[3].y));
          else if (in[2]) st_g8(p + 128, v[2]);
          else if (in[3]) st_g8(p + 136, v[3]);
          if (in[4]) {
            st_g16(p + 256, make_uint4(v[4].x, v[4].y, sec == 0 ? 0u : 0x00003f80u, 0u));
            if (sec == 0) st_g16(p + 384, make_uint4(0u, 0u, 0u, 0u));
          }
          if (sec == 1) {
            const unsigned int mxb = __reduce_max_sync(~0u, __float_as_uint(s) & 0x7fffffffu);
            if (lane == 0) atomicMax(&s_kn[i], mxb);
          }
        }
      }
      if (sec == 1) {
        named_bar(1, 256);
        const int hh = hfirst + ctid;
        if (ctid < 8 && hh * DH < cbase + BN) {
          const bool starts_here = hh * DH >= cbase, ends_here = hh * DH + DH <= cbase + BN;
          const float v = __uint_as_float(s_kn[ctid]);
          float* o = &g_kn[(blockIdx.y * NH + hh) * 2];
          if (starts_here) { o[0] = v; if (ends_here) o[1] = 0.f; }
          else o[1] = v;
        }
      }
    }
  } else if constexpr (EPI == EPI_WO || EPI == EPI_DOWN) {
    const int r0 = wg * 64 + (warp & 3) * 16 + g;
#pragma unroll
    for (int j = 0; j < BN / 8; j++) {
      const float* a = &acc[0][0][4 * j];
      *(uint32_t*)(sptr + r0 * LDS + j * 16 + t * 4) = pack_bf16(a[0], a[1]);
      *(uint32_t*)(sptr + (r0 + 8) * LDS + j * 16 + t * 4) = pack_bf16(a[2], a[3]);
    }
    named_bar(1, 256);
#pragma unroll
    for (int i = 0; i < BM * (BN / 8) / 256; i++) {
      const int idx = i * 256 + ctid, r = idx / (BN / 8), c = idx % (BN / 8);
      const uint4 a = *(const uint4*)(sptr + r * LDS + c * 16);
      const size_t go = (size_t)(m0 + r) * DM + n0 + c * 8;
      const uint4 b = ld_g16(resid + go);
      uint4 o;
      o.x = pack_bf16(bf_lo(a.x) + bf_lo(b.x), bf_hi(a.x) + bf_hi(b.x));
      o.y = pack_bf16(bf_lo(a.y) + bf_lo(b.y), bf_hi(a.y) + bf_hi(b.y));
      o.z = pack_bf16(bf_lo(a.z) + bf_lo(b.z), bf_hi(a.z) + bf_hi(b.z));
      o.w = pack_bf16(bf_lo(a.w) + bf_lo(b.w), bf_hi(a.w) + bf_hi(b.w));
      st_g16(out + go, o);
      if constexpr (EPI == EPI_WO) {
        static_assert(BN == 64, "stats assume 8 lanes per row");
        const float f[8] = {bf_lo(o.x), bf_hi(o.x), bf_lo(o.y), bf_hi(o.y), bf_lo(o.z), bf_hi(o.z), bf_lo(o.w), bf_hi(o.w)};
        float s = 0.f;
#pragma unroll
        for (int k = 0; k < 8; k++) s += f[k];
        s += __shfl_xor_sync(~0u, s, 1); s += __shfl_xor_sync(~0u, s, 2); s += __shfl_xor_sync(~0u, s, 4);
        const float mu = s * (1.0f / 64.f);
        float q = 0.f;
#pragma unroll
        for (int k = 0; k < 8; k++) { const float d = f[k] - mu; q += d * d; }
        q += __shfl_xor_sync(~0u, q, 1); q += __shfl_xor_sync(~0u, q, 2); q += __shfl_xor_sync(~0u, q, 4);
        if (c == 0) g_part2[(m0 + r) * 10 + blockIdx.x] = make_float2(s, q);
      }
    }
  } else {
    const int r0 = wg * 64 + (warp & 3) * 16 + g;
    const float2* s_st = (const float2*)(sptr + STAGES * Cfg::STAGE_BYTES + 256);
    const float* s_cs = (const float*)(sptr + STAGES * Cfg::STAGE_BYTES + 256 + 1024);
    named_bar(2, 352);
    float2 st[2] = {s_st[r0], s_st[r0 + 8]};
#pragma unroll
    for (int j = 0; j < BN / 8; j++) {
      const float2 cg = *(const float2*)&s_cs[j * 8 + 2 * t], cu = *(const float2*)&s_cs[BN + j * 8 + 2 * t];
      const float* a = &acc[0][0][4 * j];
      const float* b = &acc[0][1][4 * j];
#pragma unroll
      for (int e = 0; e < 2; e++) {
        const float2 s_ = st[e];
        const uint32_t gp = pack_bf16(fmaf(-s_.x, cg.x, a[2 * e]) * s_.y, fmaf(-s_.x, cg.y, a[2 * e + 1]) * s_.y);
        const uint32_t up = pack_bf16(fmaf(-s_.x, cu.x, b[2 * e]) * s_.y, fmaf(-s_.x, cu.y, b[2 * e + 1]) * s_.y);
        uint32_t r;
        asm("{\n.reg .b32 z;\nmax.bf16x2 z, %1, %3;\nmul.rn.bf16x2 %0, z, %2;\n}" : "=r"(r) : "r"(gp), "r"(up), "r"(0u));
        *(uint32_t*)(sptr + (r0 + 8 * e) * LDS + j * 16 + t * 4) = r;
      }
    }
    named_bar(1, 256);
#pragma unroll
    for (int i = 0; i < BM * (BN / 8) / 256; i++) {
      const int idx = i * 256 + ctid, r = idx / (BN / 8), c = idx % (BN / 8);
      st_g16(out + (size_t)(m0 + r) * DFF + n0 + c * 8, *(const uint4*)(sptr + r * LDS + c * 16));
    }
  }
  if constexpr (CN * CM > 1) cluster_wait();
  TS_END(EPI == EPI_QKV ? 1 : EPI + 2);
}

constexpr int R_STAGES = 8;
constexpr int R_STAGE_BYTES = 16384 + 5 * 2048;
constexpr int R_BAR_OFF = R_STAGES * R_STAGE_BYTES;
constexpr int R_SMEM = R_BAR_OFF + 256 + 1024;
template <int KDIM, bool STATS>
__global__ void __launch_bounds__(288, 1) gemm_res_kernel(const __grid_constant__ CUtensorMap tmA, const __grid_constant__ CUtensorMap tmB,
                                                          const __nv_bfloat16* resid, __nv_bfloat16* out) {
  constexpr int KT = KDIM / 64;
  extern __shared__ uint8_t smem_raw[];
  const uint32_t sbase = (smem_u32(smem_raw) + 1023u) & ~1023u;
  uint8_t* sptr = smem_raw + (sbase - smem_u32(smem_raw));
  const uint32_t sbar = sbase + R_BAR_OFF;
  const int tid = threadIdx.x, warp = tid >> 5, lane = tid & 31;
  const int n0 = blockIdx.x * 80, m0 = blockIdx.y * 128;
  TS_BEGIN(STATS ? 3 : 5);
  if (tid == 0) {
    for (int i = 0; i < R_STAGES; i++) { mbar_init(sbar + 8 * i, 1); mbar_init(sbar + 8 * (R_STAGES + i), 2); }
    asm volatile("fence.mbarrier_init.release.cluster;" ::: "memory");
  }
  __syncthreads();
  pdl_launch();
  if (warp == 8) {
    if (lane == 0) {
      const uint8_t* wt = (const uint8_t*)(STATS ? g_wo_t : g_wd_t) + (size_t)blockIdx.x * KT * 10240;
      auto load_b = [&](int kt, int s) { bulk_g2s(sbase + s * R_STAGE_BYTES + 16384, wt + kt * 10240, 10240, sbar + 8 * s); };
      pdl_wait();
      for (int s = 0; s < R_STAGES; s++) { mbar_expect_tx(sbar + 8 * s, R_STAGE_BYTES); tma_2d(sbase + s * R_STAGE_BYTES, &tmA, s * 64, m0, sbar + 8 * s); load_b(s, s); }
      for (int kt = R_STAGES; kt < KT; kt++) {
        const int s = kt % R_STAGES;
        mbar_wait(sbar + 8 * (R_STAGES + s), ((kt / R_STAGES) - 1) & 1);
        mbar_expect_tx(sbar + 8 * s, R_STAGE_BYTES);
        tma_2d(sbase + s * R_STAGE_BYTES, &tmA, kt * 64, m0, sbar + 8 * s);
        load_b(kt, s);
      }
    }
    return;
  }
  const int wg = warp >> 2, g = lane >> 2, t = lane & 3;
  pdl_wait();
  uint4 rv[5];
#pragma unroll
  for (int i = 0; i < 5; i++) {
    const int idx = i * 256 + tid, r = idx / 10, c = idx % 10;
    rv[i] = ld_g16(resid + (size_t)(m0 + r) * DM + n0 + c * 8);
  }
  float acc[40];
#pragma unroll
  for (int i = 0; i < 40; i++) acc[i] = 0.f;
  for (int kt = 0; kt < KT; kt++) {
    const int s = kt % R_STAGES;
    mbar_wait(sbar + 8 * s, (kt / R_STAGES) & 1);
    if (kt == 0) TS_MID(STATS ? 3 : 5, 0);
    const uint32_t sa = sbase + s * R_STAGE_BYTES + wg * 8192;
    const uint32_t sb = sbase + s * R_STAGE_BYTES + 16384;
    wgmma_fence();
#pragma unroll
    for (int ks = 0; ks < 4; ks++)
      wgmma_ss_n80(acc, make_desc(sa + ks * 32, 16, 1024, 1), make_desc(sb + ks * 2560, 1280, 128, 0), 1);
    wgmma_commit();
    wgmma_wait<1>();
    if (kt > 0 && kt - 1 + R_STAGES < KT && (tid & 127) == 0) mbar_arrive(sbar + 8 * (R_STAGES + (kt - 1) % R_STAGES));
  }
  wgmma_wait<0>();
#pragma unroll
  for (int i = 0; i < 40; i++) asm volatile("" : "+f"(acc[i]) :: "memory");
  TS_MID(STATS ? 3 : 5, 1);
  named_bar(1, 256);
  constexpr int LDS = 176;
  const int r0 = wg * 64 + (warp & 3) * 16 + g;
#pragma unroll
  for (int i = 0; i < 10; i++) {
    *(uint32_t*)(sptr + r0 * LDS + i * 16 + t * 4) = pack_bf16(acc[4 * i], acc[4 * i + 1]);
    *(uint32_t*)(sptr + (r0 + 8) * LDS + i * 16 + t * 4) = pack_bf16(acc[4 * i + 2], acc[4 * i + 3]);
  }
  named_bar(1, 256);
  TS_MID(STATS ? 3 : 5, 2);
#pragma unroll
  for (int i = 0; i < 5; i++) {
    const int idx = i * 256 + tid, r = idx / 10, c = idx % 10;
    const uint4 a = *(const uint4*)(sptr + r * LDS + c * 16);
    const uint4 b = rv[i];
    uint4 o;
    o.x = pack_bf16(bf_lo(a.x) + bf_lo(b.x), bf_hi(a.x) + bf_hi(b.x));
    o.y = pack_bf16(bf_lo(a.y) + bf_lo(b.y), bf_hi(a.y) + bf_hi(b.y));
    o.z = pack_bf16(bf_lo(a.z) + bf_lo(b.z), bf_hi(a.z) + bf_hi(b.z));
    o.w = pack_bf16(bf_lo(a.w) + bf_lo(b.w), bf_hi(a.w) + bf_hi(b.w));
    st_g16(out + (size_t)(m0 + r) * DM + n0 + c * 8, o);
    if constexpr (STATS) *(uint4*)(sptr + r * LDS + c * 16) = o;
  }
  TS_MID(STATS ? 3 : 5, 3);
  if constexpr (STATS) {
    named_bar(1, 256);
    const int r = tid >> 1, hf = tid & 1;
    float f[40];
#pragma unroll
    for (int i = 0; i < 5; i++) {
      const uint4 v = *(const uint4*)(sptr + r * LDS + hf * 80 + i * 16);
      f[8 * i] = bf_lo(v.x); f[8 * i + 1] = bf_hi(v.x); f[8 * i + 2] = bf_lo(v.y); f[8 * i + 3] = bf_hi(v.y);
      f[8 * i + 4] = bf_lo(v.z); f[8 * i + 5] = bf_hi(v.z); f[8 * i + 6] = bf_lo(v.w); f[8 * i + 7] = bf_hi(v.w);
    }
    float s = 0.f;
#pragma unroll
    for (int i = 0; i < 40; i++) s += f[i];
    s += __shfl_xor_sync(~0u, s, 1);
    const float mu = s * (1.0f / 80.f);
    float q = 0.f;
#pragma unroll
    for (int i = 0; i < 40; i++) { const float d = f[i] - mu; q += d * d; }
    q += __shfl_xor_sync(~0u, q, 1);
    if (hf == 0) g_part2[(m0 + r) * 8 + blockIdx.x] = make_float2(s, q);
  }
  TS_END(STATS ? 3 : 5);
}

#define F_MC 0
constexpr int F_CST = 7, F_DST = 3, F_EST = 5;
constexpr int F_RS = 16384 + 5 * 2048;
constexpr int F_DS = 16384 + 6 * 8192;
constexpr int F_E_OFF = 53248;
constexpr int F_STG_OFF = F_DST * F_DS;
constexpr int F_BAR_OFF = F_STG_OFF + 128 * 176;
constexpr int F_VEC_OFF = F_BAR_OFF + 256;
constexpr int F_SMEM = F_VEC_OFF + 1024 + 1536 + 1024;

__device__ __forceinline__ void flag_wait(const unsigned int* f, unsigned int target) {
  unsigned int v, spins = 0;
  do { asm volatile("ld.acquire.gpu.global.u32 %0, [%1];" : "=r"(v) : "l"(f) : "memory"); } while (v < target && ++spins < (1u << 22));
  asm volatile("fence.proxy.async;" ::: "memory");
}
__device__ __forceinline__ void flag_signal(unsigned int* f) {
  asm volatile("fence.proxy.async;" ::: "memory");
  asm volatile("red.release.gpu.global.add.u32 [%0], 1;" :: "l"(f) : "memory");
}

template <bool STATS>
__device__ __forceinline__ void res_epilogue(float (&acc)[40], const uint4 (&rv)[5], uint8_t* stg, __nv_bfloat16* out, int m0, int n0, int tid, int bx) {
  constexpr int LDS = 176;
  const int warp = tid >> 5, lane = tid & 31;
  const int r0 = (warp >> 2) * 64 + (warp & 3) * 16 + (lane >> 2), t = lane & 3;
#pragma unroll
  for (int i = 0; i < 10; i++) {
    *(uint32_t*)(stg + r0 * LDS + i * 16 + t * 4) = pack_bf16(acc[4 * i], acc[4 * i + 1]);
    *(uint32_t*)(stg + (r0 + 8) * LDS + i * 16 + t * 4) = pack_bf16(acc[4 * i + 2], acc[4 * i + 3]);
  }
  named_bar(1, 256);
#pragma unroll
  for (int i = 0; i < 5; i++) {
    const int idx = i * 256 + tid, r = idx / 10, c = idx % 10;
    const uint4 a = *(const uint4*)(stg + r * LDS + c * 16);
    const uint4 b = rv[i];
    uint4 o;
    o.x = pack_bf16(bf_lo(a.x) + bf_lo(b.x), bf_hi(a.x) + bf_hi(b.x));
    o.y = pack_bf16(bf_lo(a.y) + bf_lo(b.y), bf_hi(a.y) + bf_hi(b.y));
    o.z = pack_bf16(bf_lo(a.z) + bf_lo(b.z), bf_hi(a.z) + bf_hi(b.z));
    o.w = pack_bf16(bf_lo(a.w) + bf_lo(b.w), bf_hi(a.w) + bf_hi(b.w));
    st_g16(out + (size_t)(m0 + r) * DM + n0 + c * 8, o);
    if constexpr (STATS) *(uint4*)(stg + r * LDS + c * 16) = o;
  }
  if constexpr (STATS) {
    named_bar(1, 256);
    const int r = tid >> 1, hf = tid & 1;
    float f[40];
#pragma unroll
    for (int i = 0; i < 5; i++) {
      const uint4 v = *(const uint4*)(stg + r * LDS + hf * 80 + i * 16);
      f[8 * i] = bf_lo(v.x); f[8 * i + 1] = bf_hi(v.x); f[8 * i + 2] = bf_lo(v.y); f[8 * i + 3] = bf_hi(v.y);
      f[8 * i + 4] = bf_lo(v.z); f[8 * i + 5] = bf_hi(v.z); f[8 * i + 6] = bf_lo(v.w); f[8 * i + 7] = bf_hi(v.w);
    }
    float s = 0.f;
#pragma unroll
    for (int i = 0; i < 40; i++) s += f[i];
    s += __shfl_xor_sync(~0u, s, 1);
    const float mu = s * (1.0f / 80.f);
    float q = 0.f;
#pragma unroll
    for (int i = 0; i < 40; i++) { const float d = f[i] - mu; q += d * d; }
    q += __shfl_xor_sync(~0u, q, 1);
    if (hf == 0) g_part2[(m0 + r) * 8 + bx] = make_float2(s, q);
  }
}

__global__ void __launch_bounds__(384, 1) post_kernel(const __grid_constant__ CUtensorMap tmO, const __grid_constant__ CUtensorMap tmWo,
                                                      const __grid_constant__ CUtensorMap tmH, const __grid_constant__ CUtensorMap tmWg,
                                                      const __grid_constant__ CUtensorMap tmWu, const __grid_constant__ CUtensorMap tmAct,
                                                      const __grid_constant__ CUtensorMap tmWd, const __nv_bfloat16* x, __nv_bfloat16* out) {
  extern __shared__ uint8_t smem_raw[];
  const uint32_t sbase = (smem_u32(smem_raw) + 1023u) & ~1023u;
  uint8_t* sptr = smem_raw + (sbase - smem_u32(smem_raw));
  const uint32_t bC = sbase + F_BAR_OFF, bD = bC + 16 * F_CST, bE = bD + 16 * F_DST;
  const int tid = threadIdx.x, warp = tid >> 5, lane = tid & 31;
  const int bx = blockIdx.x, rb = blockIdx.y, m0 = rb * 128, cx = bx & 1;
  TS_BEGIN(3);
  if (tid == 0) {
    for (int i = 0; i < F_CST; i++) { mbar_init(bC + 8 * i, 1); mbar_init(bC + 8 * (F_CST + i), F_MC ? 4 : 2); }
    for (int i = 0; i < F_DST; i++) { mbar_init(bD + 8 * i, 1); mbar_init(bD + 8 * (F_DST + i), F_MC ? 4 : 2); }
    for (int i = 0; i < F_EST; i++) { mbar_init(bE + 8 * i, 1); mbar_init(bE + 8 * (F_EST + i), F_MC ? 4 : 2); }
    asm volatile("fence.mbarrier_init.release.cluster;" ::: "memory");
  }
  __syncthreads();
  if (F_MC) { cluster_arrive(); cluster_wait(); }
  if (warp >= 8) {
    asm volatile("setmaxnreg.dec.sync.aligned.u32 40;");
    if (warp == 8) {
      if (lane == 0) {
        auto load_a = [&](const CUtensorMap* tm, uint32_t stage, int kt, uint32_t bar) {
          if (F_MC) tma_2d_mc(stage + cx * 8192, tm, kt * 64, m0 + cx * 64, bar, (uint16_t)3); else tma_2d(stage, tm, kt * 64, m0, bar);
        };
        for (int s = 0; s < F_CST; s++) { mbar_expect_tx(bC + 8 * s, F_RS); if (s < 3) tma_3d(sbase + s * F_RS + 16384, &tmWo, 0, s * 64, bx * 5, bC + 8 * s); }
        pdl_wait();
        for (int s = 0; s < F_CST; s++) { load_a(&tmO, sbase + s * F_RS, s, bC + 8 * s); if (s >= 3) tma_3d(sbase + s * F_RS + 16384, &tmWo, 0, s * 64, bx * 5, bC + 8 * s); }
        for (int kt = F_CST; kt < 10; kt++) {
          const int s = kt - F_CST;
          mbar_wait(bC + 8 * (F_CST + s), 0);
          mbar_expect_tx(bC + 8 * s, F_RS);
          load_a(&tmO, sbase + s * F_RS, kt, bC + 8 * s);
          tma_3d(sbase + s * F_RS + 16384, &tmWo, 0, kt * 64, bx * 5, bC + 8 * s);
        }
        auto load_bd = [&](int kt, int s) {
          tma_3d(sbase + s * F_DS + 16384, &tmWg, 0, kt * 64, bx * 3, bD + 8 * s);
          tma_3d(sbase + s * F_DS + 16384 + 3 * 8192, &tmWu, 0, kt * 64, bx * 3, bD + 8 * s);
        };
        for (int s = 0; s < F_DST; s++) { mbar_wait(bD + 8 * (F_DST + s), 0); mbar_expect_tx(bD + 8 * s, F_DS); load_bd(s, s); }
        flag_wait(&g_flag[rb], 8);
        for (int s = 0; s < F_DST; s++) load_a(&tmH, sbase + s * F_DS, s, bD + 8 * s);
        for (int kt = F_DST; kt < 10; kt++) {
          const int s = kt % F_DST;
          mbar_wait(bD + 8 * (F_DST + s), (kt / F_DST) & 1);
          mbar_expect_tx(bD + 8 * s, F_DS);
          load_a(&tmH, sbase + s * F_DS, kt, bD + 8 * s);
          load_bd(kt, s);
        }
        const uint32_t eb = sbase + F_E_OFF;
        for (int s = 0; s < F_EST; s++) { mbar_wait(bE + 8 * (F_EST + s), 0); mbar_expect_tx(bE + 8 * s, F_RS); tma_3d(eb + s * F_RS + 16384, &tmWd, 0, s * 64, bx * 5, bE + 8 * s); }
        flag_wait(&g_flag[16 + rb], 8);
        for (int s = 0; s < F_EST; s++) load_a(&tmAct, eb + s * F_RS, s, bE + 8 * s);
        for (int kt = F_EST; kt < 24; kt++) {
          const int s = kt % F_EST;
          mbar_wait(bE + 8 * (F_EST + s), (kt / F_EST) & 1);
          mbar_expect_tx(bE + 8 * s, F_RS);
          load_a(&tmAct, eb + s * F_RS, kt, bE + 8 * s);
          tma_3d(eb + s * F_RS + 16384, &tmWd, 0, kt * 64, bx * 5, bE + 8 * s);
        }
      }
    } else {
      float2* s_st = (float2*)(sptr + F_VEC_OFF);
      float* s_cs = (float*)(sptr + F_VEC_OFF + 1024);
      pdl_wait();
      for (int c = tid - 288; c < 192; c += 96) { s_cs[c] = g_cs_g[bx * 192 + c]; s_cs[192 + c] = g_cs_u[bx * 192 + c]; }
      flag_wait(&g_flag[rb], 8);
      for (int r = tid - 288; r < 128; r += 96) {
        const float2* pp = &g_part2[(m0 + r) * 8];
        float2 p[8];
        float s = 0.f;
#pragma unroll
        for (int i = 0; i < 8; i++) { asm volatile("ld.global.v2.f32 {%0, %1}, [%2];" : "=f"(p[i].x), "=f"(p[i].y) : "l"(pp + i) : "memory"); s += p[i].x; }
        const float mean = s * (1.0f / DM);
        float q = 0.f;
#pragma unroll
        for (int i = 0; i < 8; i++) { const float d = p[i].x * (1.0f / 80.f) - mean; q += p[i].y + 80.f * d * d; }
        s_st[r] = ln_finish(mean, q * (1.0f / DM));
      }
      __threadfence_block();
      asm volatile("bar.arrive 2, 352;" ::: "memory");
    }
    if (F_MC) { __syncwarp(); cluster_arrive(); cluster_wait(); }
    return;
  }
  asm volatile("setmaxnreg.inc.sync.aligned.u32 232;");
  const int wg = warp >> 2, g = lane >> 2, t = lane & 3;
  auto release = [&](uint32_t bar) { if (F_MC) { if ((tid & 127) < 2) mbar_arrive_remote(bar, (tid & 127) ^ cx); } else if ((tid & 127) == 0) mbar_arrive(bar); };
  const int n0 = bx * 80;
  uint4 rv[5];
  pdl_wait();
  {
#pragma unroll
    for (int i = 0; i < 5; i++) { const int idx = i * 256 + tid, r = idx / 10, c = idx % 10; rv[i] = ld_g16(x + (size_t)(m0 + r) * DM + n0 + c * 8); }
    float acc[40];
#pragma unroll
    for (int i = 0; i < 40; i++) acc[i] = 0.f;
    for (int kt = 0; kt < 10; kt++) {
      const int s = kt % F_CST;
      mbar_wait(bC + 8 * s, kt / F_CST);
      if (kt == 0) TS_MID(3, 0);
      const uint32_t sa = sbase + s * F_RS + wg * 8192, sb = sbase + s * F_RS + 16384;
      wgmma_fence();
#pragma unroll
      for (int ks = 0; ks < 4; ks++) wgmma_ss_n80(acc, make_desc(sa + ks * 32, 16, 1024, 1), make_desc(sb + ks * 512, 2048, 256, 3), 1);
      wgmma_commit();
      wgmma_wait<1>();
      if (kt > 0 && kt - 1 + F_CST < 10) release(bC + 8 * (F_CST + kt - 1));
    }
    wgmma_wait<0>();
#pragma unroll
    for (int i = 0; i < 40; i++) asm volatile("" : "+f"(acc[i]) :: "memory");
    for (int s = 0; s < F_DST; s++) release(bD + 8 * (F_DST + s));
    TS_MID(3, 1);
    res_epilogue<true>(acc, rv, sptr + F_STG_OFF, g_h, m0, n0, tid, bx);
    __threadfence();
    named_bar(1, 256);
    if (tid == 0) flag_signal(&g_flag[rb]);
    TS_END(3);
  }
  {
    float acc[2][96];
#pragma unroll
    for (int i = 0; i < 96; i++) { acc[0][i] = 0.f; acc[1][i] = 0.f; }
    for (int kt = 0; kt < 10; kt++) {
      const int s = kt % F_DST;
      mbar_wait(bD + 8 * s, (kt / F_DST) & 1);
      if (kt == 0) TS_MID(4, 0);
      const uint32_t sa = sbase + s * F_DS + wg * 8192, sb = sbase + s * F_DS + 16384;
      wgmma_fence();
#pragma unroll
      for (int ks = 0; ks < 4; ks++) {
        const uint64_t da = make_desc(sa + ks * 32, 16, 1024, 1);
        wgmma_ss_n192(acc[0], da, make_desc(sb + ks * 2048, 8192, 1024, 1), 1);
        wgmma_ss_n192(acc[1], da, make_desc(sb + 3 * 8192 + ks * 2048, 8192, 1024, 1), 1);
      }
      wgmma_commit();
      wgmma_wait<1>();
      if (kt > 0 && kt - 1 + F_DST < 10) release(bD + 8 * (F_DST + (kt - 1) % F_DST));
    }
    wgmma_wait<0>();
#pragma unroll
    for (int i = 0; i < 96; i++) { asm volatile("" : "+f"(acc[0][i]) :: "memory"); asm volatile("" : "+f"(acc[1][i]) :: "memory"); }
    for (int s = 0; s < F_EST; s++) release(bE + 8 * (F_EST + s));
    TS_MID(4, 1);
    named_bar(1, 256);
    named_bar(2, 352);
    constexpr int LDS = 400;
    const float2* s_st = (const float2*)(sptr + F_VEC_OFF);
    const float* s_cs = (const float*)(sptr + F_VEC_OFF + 1024);
    const int r0 = wg * 64 + (warp & 3) * 16 + g;
    const float2 st[2] = {s_st[r0], s_st[r0 + 8]};
#pragma unroll
    for (int j = 0; j < 24; j++) {
      const float2 cg = *(const float2*)&s_cs[j * 8 + 2 * t], cu = *(const float2*)&s_cs[192 + j * 8 + 2 * t];
      const float* a = &acc[0][4 * j];
      const float* b = &acc[1][4 * j];
#pragma unroll
      for (int e = 0; e < 2; e++) {
        const float2 s_ = st[e];
        const uint32_t gp = pack_bf16(fmaf(-s_.x, cg.x, a[2 * e]) * s_.y, fmaf(-s_.x, cg.y, a[2 * e + 1]) * s_.y);
        const uint32_t up = pack_bf16(fmaf(-s_.x, cu.x, b[2 * e]) * s_.y, fmaf(-s_.x, cu.y, b[2 * e + 1]) * s_.y);
        uint32_t r;
        asm("{\n.reg .b32 z;\nmax.bf16x2 z, %1, %3;\nmul.rn.bf16x2 %0, z, %2;\n}" : "=r"(r) : "r"(gp), "r"(up), "r"(0u));
        *(uint32_t*)(sptr + (r0 + 8 * e) * LDS + j * 16 + t * 4) = r;
      }
    }
    named_bar(1, 256);
#pragma unroll
    for (int i = 0; i < 12; i++) {
      const int idx = i * 256 + tid, r = idx / 24, c = idx % 24;
      st_g16(g_act + (size_t)(m0 + r) * DFF + bx * 192 + c * 8, *(const uint4*)(sptr + r * LDS + c * 16));
    }
    __threadfence();
    named_bar(1, 256);
    if (tid == 0) flag_signal(&g_flag[16 + rb]);
    TS_END(4);
  }
  {
#pragma unroll
    for (int i = 0; i < 5; i++) { const int idx = i * 256 + tid, r = idx / 10, c = idx % 10; rv[i] = ld_g16(g_h + (size_t)(m0 + r) * DM + n0 + c * 8); }
    float acc[40];
#pragma unroll
    for (int i = 0; i < 40; i++) acc[i] = 0.f;
    const uint32_t eb = sbase + F_E_OFF;
    for (int kt = 0; kt < 24; kt++) {
      const int s = kt % F_EST;
      mbar_wait(bE + 8 * s, (kt / F_EST) & 1);
      if (kt == 0) TS_MID(5, 0);
      const uint32_t sa = eb + s * F_RS + wg * 8192, sb = eb + s * F_RS + 16384;
      wgmma_fence();
#pragma unroll
      for (int ks = 0; ks < 4; ks++) wgmma_ss_n80(acc, make_desc(sa + ks * 32, 16, 1024, 1), make_desc(sb + ks * 512, 2048, 256, 3), 1);
      wgmma_commit();
      wgmma_wait<1>();
      if (kt > 0 && kt - 1 + F_EST < 24) release(bE + 8 * (F_EST + (kt - 1) % F_EST));
    }
    wgmma_wait<0>();
#pragma unroll
    for (int i = 0; i < 40; i++) asm volatile("" : "+f"(acc[i]) :: "memory");
    if (F_MC) cluster_arrive();
    TS_MID(5, 1);
    res_epilogue<false>(acc, rv, sptr + F_STG_OFF, out, m0, n0, tid, bx);
    if (F_MC) cluster_wait();
    TS_END(5);
  }
}

#define POLY_NUM 5
__device__ __forceinline__ float ex2_poly(float x, int shl23) {
  const float MAGIC = 12582912.f;
  const float tt = x + MAGIC;
  const float f = x - (tt - MAGIC);
  float p = fmaf(0.0013276472454890609f, f, 0.009675540961325169f);
  p = fmaf(p, f, 0.05550713092088699f);
  p = fmaf(p, f, 0.24022120237350464f);
  p = fmaf(p, f, 0.6931469440460205f);
  p = fmaf(p, f, 1.0000001192092896f);
  return __int_as_float(__float_as_int(tt) * shl23 + __float_as_int(p));
}
constexpr int KV_BYTES = S_LEN * 48;
constexpr int ATT_SMEM = 2 * KV_BYTES + 256 + 32768;
constexpr int ATT_BODY = 8;

__global__ void __launch_bounds__(512, 1) attn_kernel(int shl23, const __nv_bfloat16* __restrict__ wg_, const __nv_bfloat16* __restrict__ wu_,
                                                      const __nv_bfloat16* __restrict__ wo_, const __nv_bfloat16* __restrict__ wd_) {
  extern __shared__ __align__(1024) uint8_t smem[];
  if (blockIdx.x >= 128) {
    pdl_launch();
    const int e = blockIdx.x - 128, half = threadIdx.x >> 8;
    constexpr int NCH = (DM + DFF) * (DM / 8);
    for (int c0 = e * 512 + threadIdx.x; c0 < NCH; c0 += 2048 * 17) {
      uint4 v[17];
#pragma unroll
      for (int i = 0; i < 17; i++) {
        const int c = c0 + i * 2048;
        const bool isd = c >= DM * (DM / 8);
        const int cc = isd ? c - DM * (DM / 8) : c;
        v[i] = __ldg((const uint4*)(isd ? wd_ : wo_) + cc);
      }
#pragma unroll
      for (int i = 0; i < 17; i++) {
        const int c = c0 + i * 2048;
        const bool isd = c >= DM * (DM / 8);
        const int cc = isd ? c - DM * (DM / 8) : c;
        const int k = cc / (DM / 8), nc = cc % (DM / 8);
        const int j = nc / 10, kt = k >> 6;
        st_g16((uint8_t*)(isd ? g_wd_t : g_wo_t) + (size_t)(j * (isd ? DFF / 64 : DM / 64) + kt) * 10240 + ((k & 63) >> 3) * 1280 + (nc % 10) * 128 + (k & 7) * 16, v[i]);
      }
    }
    float (*red)[65] = (float (*)[65])(smem + half * 16384);
    for (int b = e * 12 + half; b < e * 12 + 12; b += 2) {
      if (b < 24) colsum64(wg_, DFF, b * 64, g_cs_g, red, threadIdx.x & 255, 1 + half);
      else colsum64(wu_, DFF, (b - 24) * 64, g_cs_u, red, threadIdx.x & 255, 1 + half);
    }
    return;
  }
  const int h = blockIdx.x >> 2, qb = blockIdx.x & 3;
  const uint32_t sK = smem_u32(smem), sV = sK + KV_BYTES, sBar = sV + KV_BYTES;
  const int tid = threadIdx.x;
  TS_BEGIN(2);
  if (tid == 0) {
    for (int i = 0; i < 9; i++) mbar_init(sBar + 8 * i, 1);
    asm volatile("fence.mbarrier_init.release.cluster;" ::: "memory");
  }
  __syncthreads();
  pdl_launch();
  pdl_wait();
  TS_MID(2, 0);
  const uint8_t* gk = (const uint8_t*)(g_k + (size_t)h * S_LEN * 24);
  const uint8_t* gv = (const uint8_t*)(g_v + (size_t)h * S_LEN * 24);
  auto load_kv = [&](int i0, int i1) {
    for (int i = i0; i < i1; i++) {
      mbar_expect_tx(sBar + 8 * i, 2 * 12288);
      bulk_g2s(sK + i * 12288, gk + i * 12288, 12288, sBar + 8 * i);
      bulk_g2s(sV + i * 12288, gv + i * 12288, 12288, sBar + 8 * i);
    }
  };
  if (tid == 0) {
    mbar_expect_tx(sBar + 64, 32768);
    bulk_g2s(sBar + 256, (const uint8_t*)g_q + ((size_t)h * S_LEN + qb * 512) * 64, 32768, sBar + 64);
    load_kv(0, 2);
  }
  float ka = 0.f, kb = 0.f;
#pragma unroll
  for (int i = 0; i < 8; i++) {
    const float2 v = *(const float2*)&g_kn[(i * NH + h) * 2];
    ka = (v.x > ka || v.x != v.x) ? v.x : ka;
    kb = (v.y > kb || v.y != v.y) ? v.y : kb;
  }
  bool fast;
  {
    const float kn = sqrtf(ka + kb);
    mbar_wait(sBar + 64, 0);
    if (tid == 0) load_kv(2, 8);
    uint8_t* qrow = smem + 2 * KV_BYTES + 256 + (tid >> 3) * 512 + (tid & 7) * 16;
    const uint4 c0 = *(const uint4*)qrow, c1 = *(const uint4*)(qrow + 128);
    const uint2 c2 = *(const uint2*)(qrow + 256);
    auto sq = [](uint32_t u) { const float a = bf_lo(u), b = bf_hi(u); return a * a + b * b; };
    const float n2 = sq(c0.x) + sq(c0.y) + sq(c0.z) + sq(c0.w) + sq(c1.x) + sq(c1.y) + sq(c1.z) + sq(c1.w) + sq(c2.x) + sq(c2.y);
    const float m = ceilf(sqrtf(n2) * kn * 1.001f) + 1.f;
    fast = __syncthreads_or(!(m <= 62.f)) == 0;
    if (fast) *(uint32_t*)(qrow + 256 + 8) = pack_bf16(-m, 0.f);
    asm volatile("fence.proxy.async.shared::cta;" ::: "memory");
    __syncthreads();
  }
  auto write_out = [&](float (&O)[12], int it) {
    uint32_t tid2;
    asm volatile("mov.u32 %0, %%tid.x;" : "=r"(tid2));
    const int lane2 = tid2 & 31, t2 = lane2 & 3;
    const int qq = (blockIdx.x & 3) * 512 + (it * 4 + (tid2 >> 7)) * 64 + ((tid2 >> 5) & 3) * 16 + (lane2 >> 2);
    const float l0 = __shfl_sync(~0u, O[8], (lane2 & ~3) | 2), l1 = __shfl_sync(~0u, O[10], (lane2 & ~3) | 2);
    const float r0 = 1.f / l0, r1 = 1.f / l1;
    uint32_t* o0 = (uint32_t*)(g_o + (size_t)qq * DM + (blockIdx.x >> 2) * DH);
    uint32_t* o1 = o0 + 8 * DM / 2;
    o0[t2] = pack_bf16(O[0] * r0, O[1] * r0); o1[t2] = pack_bf16(O[2] * r1, O[3] * r1);
    o0[t2 + 4] = pack_bf16(O[4] * r0, O[5] * r0); o1[t2 + 4] = pack_bf16(O[6] * r1, O[7] * r1);
    if (t2 < 2) { o0[t2 + 8] = pack_bf16(O[8] * r0, O[9] * r0); o1[t2 + 8] = pack_bf16(O[10] * r1, O[11] * r1); }
  };
  TS_MID(2, 1);
  if (fast) {
#pragma unroll 1
    for (int it = 0; it < 2; it++) {
      const uint64_t dq = make_desc(sBar + 256 + (it * 4 + (tid >> 7)) * 4096, 128, 512, 0);
      float O[12];
#pragma unroll
      for (int i = 0; i < 12; i++) { O[i] = 0.f; asm volatile("" : "+f"(O[i]) :: "memory"); }
      float S[2][32];
      uint32_t P[16];
#pragma unroll 1
      for (int jb = 0; jb < 32 / ATT_BODY; jb++) {
        if (it == 0) { for (int c = 0; c < ATT_BODY / 4; c++) mbar_wait(sBar + 8 * (jb * (ATT_BODY / 4) + c), 0); }
        const uint64_t dk0 = make_desc(sK + jb * ATT_BODY * 8 * 384, 128, 384, 0);
        const uint64_t dv0 = make_desc(sV + jb * ATT_BODY * 8 * 384, 384, 128, 0);
        wgmma_fence();
        wgmma_ss_n64_k(S[0], dq, dk0, 0);
        wgmma_ss_n64_k(S[0], dq + (256 >> 4), dk0 + (256 >> 4), 1);
        wgmma_commit();
#pragma unroll
        for (int u = 0; u < ATT_BODY; u++) {
          if (u + 1 < ATT_BODY) {
            const uint64_t dk = dk0 + (((u + 1) * 8 * 384) >> 4);
            wgmma_fence();
            wgmma_ss_n64_k(S[(u + 1) & 1], dq, dk, 0);
            wgmma_ss_n64_k(S[(u + 1) & 1], dq + (256 >> 4), dk + (256 >> 4), 1);
            wgmma_commit();
          }
          if (u == 0 || u == ATT_BODY - 1) wgmma_wait<1>(); else wgmma_wait<2>();
#pragma unroll
          for (int i = 0; i < 32; i++) asm volatile("" : "+f"(S[u & 1][i]) :: "memory");
          const uint64_t dv = dv0 + ((u * 8 * 384) >> 4);
#pragma unroll
          for (int hf = 0; hf < 2; hf++) {
            if (hf == 1 && u > 0) { if (u == ATT_BODY - 1) wgmma_wait<1>(); else wgmma_wait<2>(); }
#pragma unroll
            for (int i = hf * 8; i < hf * 8 + 8; i++) {
              const bool usepoly = ((i + 1) * POLY_NUM / 16) != (i * POLY_NUM / 16);
              float a, b;
              if (usepoly) { a = ex2_poly(S[u & 1][2 * i], shl23); b = ex2_poly(S[u & 1][2 * i + 1], shl23); }
              else { a = ex2_mufu(S[u & 1][2 * i]); b = ex2_mufu(S[u & 1][2 * i + 1]); }
              P[i] = pack_bf16(a, b);
            }
            wgmma_fence();
#pragma unroll
            for (int ks = hf * 2; ks < hf * 2 + 2; ks++)
              wgmma_rs_n24_tb(O, P[4 * ks], P[4 * ks + 1], P[4 * ks + 2], P[4 * ks + 3], dv + ((ks * 768) >> 4), 1);
            wgmma_commit();
          }
        }
        wgmma_wait<0>();
      }
#pragma unroll
      for (int i = 0; i < 12; i++) asm volatile("" : "+f"(O[i]) :: "memory");
      write_out(O, it);
      if (it == 0) TS_MID(2, 2);
    }
  } else {
#pragma unroll 1
    for (int it = 0; it < 2; it++) {
      const uint64_t dq = make_desc(sBar + 256 + (it * 4 + (tid >> 7)) * 4096, 128, 512, 0);
      float O[12];
#pragma unroll
      for (int i = 0; i < 12; i++) { O[i] = 0.f; asm volatile("" : "+f"(O[i]) :: "memory"); }
      float S[32];
      float mx0 = -INFINITY, mx1 = -INFINITY;
#pragma unroll 1
      for (int j = 0; j < 32; j++) {
        if (it == 0 && (j & 3) == 0) mbar_wait(sBar + 8 * (j >> 2), 0);
        const uint64_t dk = make_desc(sK + j * 8 * 384, 128, 384, 0);
        wgmma_fence();
        wgmma_ss_n64_k(S, dq, dk, 0);
        wgmma_ss_n64_k(S, dq + (256 >> 4), dk + (256 >> 4), 1);
        wgmma_commit();
        wgmma_wait<0>();
#pragma unroll
        for (int i = 0; i < 8; i++) {
          mx0 = fmaxf(mx0, fmaxf(S[4 * i], S[4 * i + 1]));
          mx1 = fmaxf(mx1, fmaxf(S[4 * i + 2], S[4 * i + 3]));
        }
      }
      mx0 = fmaxf(mx0, __shfl_xor_sync(~0u, mx0, 1)); mx0 = fmaxf(mx0, __shfl_xor_sync(~0u, mx0, 2));
      mx1 = fmaxf(mx1, __shfl_xor_sync(~0u, mx1, 1)); mx1 = fmaxf(mx1, __shfl_xor_sync(~0u, mx1, 2));
#pragma unroll 1
      for (int j = 0; j < 32; j++) {
        const uint64_t dk = make_desc(sK + j * 8 * 384, 128, 384, 0);
        wgmma_fence();
        wgmma_ss_n64_k(S, dq, dk, 0);
        wgmma_ss_n64_k(S, dq + (256 >> 4), dk + (256 >> 4), 1);
        wgmma_commit();
        wgmma_wait<0>();
        uint32_t P[16];
#pragma unroll
        for (int i = 0; i < 8; i++) {
          P[2 * i] = pack_bf16(ex2_mufu(S[4 * i] - mx0), ex2_mufu(S[4 * i + 1] - mx0));
          P[2 * i + 1] = pack_bf16(ex2_mufu(S[4 * i + 2] - mx1), ex2_mufu(S[4 * i + 3] - mx1));
        }
        wgmma_fence();
        const uint64_t dv = make_desc(sV + j * 8 * 384, 384, 128, 0);
#pragma unroll
        for (int ks = 0; ks < 4; ks++)
          wgmma_rs_n24_tb(O, P[4 * ks], P[4 * ks + 1], P[4 * ks + 2], P[4 * ks + 3], dv + ((ks * 768) >> 4), 1);
        wgmma_commit();
        wgmma_wait<0>();
      }
#pragma unroll
      for (int i = 0; i < 12; i++) asm volatile("" : "+f"(O[i]) :: "memory");
      write_out(O, it);
    }
  }
  TS_END(2);
}

typedef CUresult (*EncodeFn)(CUtensorMap*, CUtensorMapDataType, cuuint32_t, void*, const cuuint64_t*, const cuuint64_t*, const cuuint32_t*,
                             const cuuint32_t*, CUtensorMapInterleave, CUtensorMapSwizzle, CUtensorMapL2promotion, CUtensorMapFloatOOBfill);
static EncodeFn get_encode() {
  static EncodeFn fn = nullptr;
  if (!fn) {
    void* p = nullptr; cudaDriverEntryPointQueryResult st;
    cudaGetDriverEntryPoint("cuTensorMapEncodeTiled", &p, cudaEnableDefault, &st);
    fn = (EncodeFn)p;
  }
  return fn;
}
static CUtensorMap make_map(const void* ptr, int rows, int cols, int box_rows, int box_cols = 64) {
  CUtensorMap m;
  cuuint64_t dims[2] = {(cuuint64_t)cols, (cuuint64_t)rows};
  cuuint64_t strides[1] = {(cuuint64_t)cols * 2};
  cuuint32_t box[2] = {(cuuint32_t)box_cols, (cuuint32_t)box_rows};
  cuuint32_t es[2] = {1, 1};
  get_encode()(&m, CU_TENSOR_MAP_DATA_TYPE_BFLOAT16, 2, const_cast<void*>(ptr), dims, strides, box, es, CU_TENSOR_MAP_INTERLEAVE_NONE,
               box_cols == 64 ? CU_TENSOR_MAP_SWIZZLE_128B : (box_cols == 32 ? CU_TENSOR_MAP_SWIZZLE_64B : CU_TENSOR_MAP_SWIZZLE_32B), CU_TENSOR_MAP_L2_PROMOTION_L2_128B, CU_TENSOR_MAP_FLOAT_OOB_FILL_NONE);
  return m;
}
static CUtensorMap make_map_w(const void* ptr, int rows, int cols, int bc, int nblk) {
  CUtensorMap m;
  cuuint64_t dims[3] = {(cuuint64_t)bc, (cuuint64_t)rows, (cuuint64_t)(cols / bc)};
  cuuint64_t strides[2] = {(cuuint64_t)cols * 2, (cuuint64_t)bc * 2};
  cuuint32_t box[3] = {(cuuint32_t)bc, 64, (cuuint32_t)nblk};
  cuuint32_t es[3] = {1, 1, 1};
  get_encode()(&m, CU_TENSOR_MAP_DATA_TYPE_BFLOAT16, 3, const_cast<void*>(ptr), dims, strides, box, es, CU_TENSOR_MAP_INTERLEAVE_NONE,
               bc == 64 ? CU_TENSOR_MAP_SWIZZLE_128B : (bc == 32 ? CU_TENSOR_MAP_SWIZZLE_64B : CU_TENSOR_MAP_SWIZZLE_32B),
               CU_TENSOR_MAP_L2_PROMOTION_L2_128B, CU_TENSOR_MAP_FLOAT_OOB_FILL_NONE);
  return m;
}
template <typename... KArgs, typename... Args>
static void launch(void (*kern)(KArgs...), dim3 grid, dim3 block, size_t smem, bool pdl, dim3 cluster, Args... args) {
  cudaLaunchConfig_t cfg = {};
  cfg.gridDim = grid; cfg.blockDim = block; cfg.dynamicSmemBytes = smem; cfg.stream = cudaStreamPerThread;
  cudaLaunchAttribute at[2];
  int na = 0;
  if (pdl) { at[na].id = cudaLaunchAttributeProgrammaticStreamSerialization; at[na].val.programmaticStreamSerializationAllowed = 1; na++; }
  if (cluster.x * cluster.y > 1) { at[na].id = cudaLaunchAttributeClusterDimension; at[na].val.clusterDim.x = cluster.x; at[na].val.clusterDim.y = cluster.y; at[na].val.clusterDim.z = 1; na++; }
  cfg.attrs = at; cfg.numAttrs = na;
  cudaLaunchKernelEx(&cfg, kern, KArgs(args)...);
}

extern "C" void kernel_launch(void* const* d_in, const int* in_sizes, int n_in, void* d_out, int out_size) {
  const __nv_bfloat16* x = (const __nv_bfloat16*)d_in[0];
  const __nv_bfloat16* wqkv = (const __nv_bfloat16*)d_in[1];
  const __nv_bfloat16* wo = (const __nv_bfloat16*)d_in[2];
  const __nv_bfloat16* wgate = (const __nv_bfloat16*)d_in[4];
  const __nv_bfloat16* wup = (const __nv_bfloat16*)d_in[5];
  const __nv_bfloat16* wdown = (const __nv_bfloat16*)d_in[6];
  __nv_bfloat16* out = (__nv_bfloat16*)d_out;
  void *p_o, *p_h, *p_act;
  cudaGetSymbolAddress(&p_o, g_o); cudaGetSymbolAddress(&p_h, g_h); cudaGetSymbolAddress(&p_act, g_act);

#define A_CN 1
#define A_CM 1
#define D_CN 1
#define D_CM 1
  auto kA = gemm_kernel<256, 128, 1, DM, 4, EPI_QKV, 1, A_CN, A_CM>;
  auto kC = gemm_res_kernel<DM, true>;
  auto kD = gemm_kernel<128, 192, 2, DM, 3, EPI_GLU, 1, D_CN, D_CM>;
  auto kE = gemm_res_kernel<DFF, false>;
  constexpr int smA = GemmCfg<256, 128, 1, 4>::SMEM, smC = R_SMEM, smD = GemmCfg<128, 192, 2, 3>::SMEM;
  cudaFuncSetAttribute(kA, cudaFuncAttributeMaxDynamicSharedMemorySize, smA);
  cudaFuncSetAttribute(kC, cudaFuncAttributeMaxDynamicSharedMemorySize, smC);
  cudaFuncSetAttribute(kD, cudaFuncAttributeMaxDynamicSharedMemorySize, smD);
  cudaFuncSetAttribute(kE, cudaFuncAttributeMaxDynamicSharedMemorySize, smC);
  cudaFuncSetAttribute(attn_kernel, cudaFuncAttributeMaxDynamicSharedMemorySize, ATT_SMEM);

  const CUtensorMap tm_x = make_map(x, S_LEN, DM, 256), tm_wqkv = make_map_w(wqkv, DM, 3 * DM, 64, 2);
  const CUtensorMap tm_o = make_map(p_o, S_LEN, DM, 128), tm_wo = make_map_w(wo, DM, DM, 16, 5);
  const CUtensorMap tm_h = make_map(p_h, S_LEN, DM, 128), tm_wg = make_map_w(wgate, DM, DFF, 64, 3), tm_wu = make_map_w(wup, DM, DFF, 64, 3);
  const CUtensorMap tm_act = make_map(p_act, S_LEN, DFF, 128), tm_wd = make_map_w(wdown, DFF, DM, 16, 5);

  launch(pre_kernel, dim3(12), dim3(1024), 0, false, dim3(1, 1), x, wqkv);
  launch(kA, dim3(15, 8), dim3(288), smA, true, dim3(A_CN, A_CM), tm_x, tm_wqkv, tm_wqkv, x, (__nv_bfloat16*)wqkv);
  launch(attn_kernel, dim3(132), dim3(512), ATT_SMEM, true, dim3(1, 1), 0x800000, wgate, wup, wo, wdown);
  launch(kC, dim3(8, 16), dim3(288), smC, true, dim3(1, 1), tm_o, tm_wo, x, (__nv_bfloat16*)p_h);
  launch(kD, dim3(8, 16), dim3(384), smD, true, dim3(D_CN, D_CM), tm_h, tm_wg, tm_wu, (const __nv_bfloat16*)nullptr, (__nv_bfloat16*)p_act);
  launch(kE, dim3(8, 16), dim3(288), smC, true, dim3(1, 1), tm_act, tm_wd, (const __nv_bfloat16*)p_h, out);
}
```

```cpp
#include <cuda_runtime.h>
#include <cuda_bf16.h>
#include <cuda.h>
#include <stdint.h>

constexpr int S_LEN = 2048, DM = 640, NH = 32, DH = 20, DFF = 1536;

__device__ __align__(1024) __nv_bfloat16 g_q[NH * S_LEN * 32];
__device__ __align__(1024) __nv_bfloat16 g_k[NH * S_LEN * 24];
__device__ __align__(1024) __nv_bfloat16 g_v[NH * S_LEN * 24];
__device__ __align__(1024) __nv_bfloat16 g_o[S_LEN * DM];
__device__ __align__(1024) __nv_bfloat16 g_h[S_LEN * DM];
__device__ __align__(1024) __nv_bfloat16 g_act[S_LEN * DFF];
__device__ __align__(1024) __nv_bfloat16 g_wo_t[DM * DM];
__device__ __align__(1024) __nv_bfloat16 g_wd_t[DFF * DM];
__device__ float g_kn[8 * NH * 2];
__device__ float2 g_stat1[S_LEN];
__device__ float g_cs_qkv[3 * DM];
__device__ float g_cs_g[DFF];
__device__ float g_cs_u[DFF];
__device__ unsigned int g_flag[32];
__device__ float2 g_part2[S_LEN * 10];

#define TS_BEGIN(k)
#define TS_END(k)
#define TS_MID(k, i)
__device__ __forceinline__ uint32_t smem_u32(const void* p) { return (uint32_t)__cvta_generic_to_shared(p); }
__device__ __forceinline__ void mbar_init(uint32_t bar, uint32_t cnt) { asm volatile("mbarrier.init.shared::cta.b64 [%0], %1;" :: "r"(bar), "r"(cnt)); }
__device__ __forceinline__ void mbar_expect_tx(uint32_t bar, uint32_t bytes) { asm volatile("mbarrier.arrive.expect_tx.shared::cta.b64 _, [%0], %1;" :: "r"(bar), "r"(bytes) : "memory"); }
__device__ __forceinline__ void mbar_arrive(uint32_t bar) { asm volatile("mbarrier.arrive.shared::cta.b64 _, [%0];" :: "r"(bar) : "memory"); }
__device__ __forceinline__ void mbar_wait(uint32_t bar, uint32_t parity) {
  uint32_t done;
  uint32_t spins = 0;
  do {
    asm volatile("{\n.reg .pred P1;\nmbarrier.try_wait.parity.shared::cta.b64 P1, [%1], %2;\nselp.u32 %0, 1, 0, P1;\n}" : "=r"(done) : "r"(bar), "r"(parity) : "memory");
  } while (!done && ++spins < (1u << 24));
}
__device__ __forceinline__ void bulk_g2s(uint32_t dst, const void* src, uint32_t bytes, uint32_t bar) {
  asm volatile("cp.async.bulk.shared::cluster.global.mbarrier::complete_tx::bytes [%0], [%1], %2, [%3];" :: "r"(dst), "l"(src), "r"(bytes), "r"(bar) : "memory");
}
__device__ __forceinline__ void tma_2d(uint32_t dst, const CUtensorMap* tm, int c0, int c1, uint32_t bar) {
  asm volatile("cp.async.bulk.tensor.2d.shared::cluster.global.mbarrier::complete_tx::bytes [%0], [%1, {%3, %4}], [%2];"
               :: "r"(dst), "l"(tm), "r"(bar), "r"(c0), "r"(c1) : "memory");
}
__device__ __forceinline__ void tma_3d(uint32_t dst, const CUtensorMap* tm, int c0, int c1, int c2, uint32_t bar) {
  asm volatile("cp.async.bulk.tensor.3d.shared::cluster.global.mbarrier::complete_tx::bytes [%0], [%1, {%3, %4, %5}], [%2];"
               :: "r"(dst), "l"(tm), "r"(bar), "r"(c0), "r"(c1), "r"(c2) : "memory");
}
__device__ __forceinline__ void tma_2d_mc(uint32_t dst, const CUtensorMap* tm, int c0, int c1, uint32_t bar, uint16_t mask) {
  asm volatile("cp.async.bulk.tensor.2d.shared::cluster.global.mbarrier::complete_tx::bytes.multicast::cluster [%0], [%1, {%3, %4}], [%2], %5;"
               :: "r"(dst), "l"(tm), "r"(bar), "r"(c0), "r"(c1), "h"(mask) : "memory");
}
__device__ __forceinline__ void mbar_arrive_remote(uint32_t bar, uint32_t rank) {
  asm volatile("{\n.reg .b32 ra;\nmapa.shared::cluster.u32 ra, %0, %1;\nmbarrier.arrive.release.cluster.shared::cluster.b64 _, [ra];\n}" :: "r"(bar), "r"(rank) : "memory");
}
__device__ __forceinline__ void cluster_arrive() { asm volatile("barrier.cluster.arrive.release.aligned;" ::: "memory"); }
__device__ __forceinline__ void cluster_wait() { asm volatile("barrier.cluster.wait.acquire.aligned;" ::: "memory"); }
__device__ __forceinline__ void wgmma_fence() { asm volatile("wgmma.fence.sync.aligned;" ::: "memory"); }
__device__ __forceinline__ void wgmma_commit() { asm volatile("wgmma.commit_group.sync.aligned;" ::: "memory"); }
template <int N> __device__ __forceinline__ void wgmma_wait() { asm volatile("wgmma.wait_group.sync.aligned %0;" :: "n"(N) : "memory"); }
__device__ __forceinline__ void pdl_wait() { asm volatile("griddepcontrol.wait;" ::: "memory"); }
__device__ __forceinline__ void pdl_launch() { asm volatile("griddepcontrol.launch_dependents;" ::: "memory"); }
__device__ __forceinline__ void named_bar(int id, int n) { asm volatile("bar.sync %0, %1;" :: "r"(id), "r"(n) : "memory"); }
__device__ __forceinline__ uint64_t make_desc(uint32_t addr, uint32_t lbo, uint32_t sbo, uint32_t swz) {
  return (uint64_t)((addr & 0x3FFFF) >> 4) | ((uint64_t)(lbo >> 4) << 16) | ((uint64_t)(sbo >> 4) << 32) | ((uint64_t)swz << 62);
}
__device__ __forceinline__ void st_g16(void* p, uint4 v) { asm volatile("st.global.v4.b32 [%0], {%1, %2, %3, %4};" :: "l"(p), "r"(v.x), "r"(v.y), "r"(v.z), "r"(v.w) : "memory"); }
__device__ __forceinline__ void st_g8(void* p, uint2 v) { asm volatile("st.global.v2.b32 [%0], {%1, %2};" :: "l"(p), "r"(v.x), "r"(v.y) : "memory"); }
__device__ __forceinline__ uint4 ld_g16(const void* p) { uint4 v; asm volatile("ld.global.v4.b32 {%0, %1, %2, %3}, [%4];" : "=r"(v.x), "=r"(v.y), "=r"(v.z), "=r"(v.w) : "l"(p) : "memory"); return v; }
__device__ __forceinline__ uint32_t pack_bf16(float lo, float hi) { uint32_t r; asm("cvt.rn.bf16x2.f32 %0, %1, %2;" : "=r"(r) : "f"(hi), "f"(lo)); return r; }
__device__ __forceinline__ float bf_lo(uint32_t u) { return __uint_as_float(u << 16); }
__device__ __forceinline__ float bf_hi(uint32_t u) { return __uint_as_float(u & 0xffff0000u); }
__device__ __forceinline__ float bf_round(float x) { return __bfloat162float(__float2bfloat16_rn(x)); }
__device__ __forceinline__ float ex2_mufu(float x) { float y; asm("ex2.approx.ftz.f32 %0, %1;" : "=f"(y) : "f"(x)); return y; }

__device__ __forceinline__ void wgmma_ss_n80(float (&d)[40], uint64_t da, uint64_t db, int scale_d) {
  asm volatile("{\n.reg .pred p;\nsetp.ne.b32 p, %42, 0;\n"
    "wgmma.mma_async.sync.aligned.m64n80k16.f32.bf16.bf16 {%0,%1,%2,%3,%4,%5,%6,%7,%8,%9,%10,%11,%12,%13,%14,%15,%16,%17,%18,%19,%20,%21,%22,%23,%24,%25,%26,%27,%28,%29,%30,%31,%32,%33,%34,%35,%36,%37,%38,%39}, %40, %41, p, 1, 1, 0, 1;\n}\n"
    : "+f"(d[0]),"+f"(d[1]),"+f"(d[2]),"+f"(d[3]),"+f"(d[4]),"+f"(d[5]),"+f"(d[6]),"+f"(d[7]),"+f"(d[8]),"+f"(d[9]),"+f"(d[10]),"+f"(d[11]),"+f"(d[12]),"+f"(d[13]),"+f"(d[14]),"+f"(d[15]),"+f"(d[16]),"+f"(d[17]),"+f"(d[18]),"+f"(d[19]),"+f"(d[20]),"+f"(d[21]),"+f"(d[22]),"+f"(d[23]),"+f"(d[24]),"+f"(d[25]),"+f"(d[26]),"+f"(d[27]),"+f"(d[28]),"+f"(d[29]),"+f"(d[30]),"+f"(d[31]),"+f"(d[32]),"+f"(d[33]),"+f"(d[34]),"+f"(d[35]),"+f"(d[36]),"+f"(d[37]),"+f"(d[38]),"+f"(d[39])
    : "l"(da), "l"(db), "r"(scale_d));
}
__device__ __forceinline__ void wgmma_ss_n128(float (&d)[64], uint64_t da, uint64_t db, int scale_d) {
  asm volatile("{\n.reg .pred p;\nsetp.ne.b32 p, %66, 0;\n"
    "wgmma.mma_async.sync.aligned.m64n128k16.f32.bf16.bf16 {%0,%1,%2,%3,%4,%5,%6,%7,%8,%9,%10,%11,%12,%13,%14,%15,%16,%17,%18,%19,%20,%21,%22,%23,%24,%25,%26,%27,%28,%29,%30,%31,%32,%33,%34,%35,%36,%37,%38,%39,%40,%41,%42,%43,%44,%45,%46,%47,%48,%49,%50,%51,%52,%53,%54,%55,%56,%57,%58,%59,%60,%61,%62,%63}, %64, %65, p, 1, 1, 0, 1;\n}\n"
    : "+f"(d[0]),"+f"(d[1]),"+f"(d[2]),"+f"(d[3]),"+f"(d[4]),"+f"(d[5]),"+f"(d[6]),"+f"(d[7]),"+f"(d[8]),"+f"(d[9]),"+f"(d[10]),"+f"(d[11]),"+f"(d[12]),"+f"(d[13]),"+f"(d[14]),"+f"(d[15]),"+f"(d[16]),"+f"(d[17]),"+f"(d[18]),"+f"(d[19]),"+f"(d[20]),"+f"(d[21]),"+f"(d[22]),"+f"(d[23]),"+f"(d[24]),"+f"(d[25]),"+f"(d[26]),"+f"(d[27]),"+f"(d[28]),"+f"(d[29]),"+f"(d[30]),"+f"(d[31]),"+f"(d[32]),"+f"(d[33]),"+f"(d[34]),"+f"(d[35]),"+f"(d[36]),"+f"(d[37]),"+f"(d[38]),"+f"(d[39]),"+f"(d[40]),"+f"(d[41]),"+f"(d[42]),"+f"(d[43]),"+f"(d[44]),"+f"(d[45]),"+f"(d[46]),"+f"(d[47]),"+f"(d[48]),"+f"(d[49]),"+f"(d[50]),"+f"(d[51]),"+f"(d[52]),"+f"(d[53]),"+f"(d[54]),"+f"(d[55]),"+f"(d[56]),"+f"(d[57]),"+f"(d[58]),"+f"(d[59]),"+f"(d[60]),"+f"(d[61]),"+f"(d[62]),"+f"(d[63])
    : "l"(da), "l"(db), "r"(scale_d));
}
__device__ __forceinline__ void wgmma_ss_n192(float (&d)[96], uint64_t da, uint64_t db, int scale_d) {
  asm volatile("{\n.reg .pred p;\nsetp.ne.b32 p, %98, 0;\n"
    "wgmma.mma_async.sync.aligned.m64n192k16.f32.bf16.bf16 {%0,%1,%2,%3,%4,%5,%6,%7,%8,%9,%10,%11,%12,%13,%14,%15,%16,%17,%18,%19,%20,%21,%22,%23,%24,%25,%26,%27,%28,%29,%30,%31,%32,%33,%34,%35,%36,%37,%38,%39,%40,%41,%42,%43,%44,%45,%46,%47,%48,%49,%50,%51,%52,%53,%54,%55,%56,%57,%58,%59,%60,%61,%62,%63,%64,%65,%66,%67,%68,%69,%70,%71,%72,%73,%74,%75,%76,%77,%78,%79,%80,%81,%82,%83,%84,%85,%86,%87,%88,%89,%90,%91,%92,%93,%94,%95}, %96, %97, p, 1, 1, 0, 1;\n}\n"
    : "+f"(d[0]),"+f"(d[1]),"+f"(d[2]),"+f"(d[3]),"+f"(d[4]),"+f"(d[5]),"+f"(d[6]),"+f"(d[7]),"+f"(d[8]),"+f"(d[9]),"+f"(d[10]),"+f"(d[11]),"+f"(d[12]),"+f"(d[13]),"+f"(d[14]),"+f"(d[15]),"+f"(d[16]),"+f"(d[17]),"+f"(d[18]),"+f"(d[19]),"+f"(d[20]),"+f"(d[21]),"+f"(d[22]),"+f"(d[23]),"+f"(d[24]),"+f"(d[25]),"+f"(d[26]),"+f"(d[27]),"+f"(d[28]),"+f"(d[29]),"+f"(d[30]),"+f"(d[31]),"+f"(d[32]),"+f"(d[33]),"+f"(d[34]),"+f"(d[35]),"+f"(d[36]),"+f"(d[37]),"+f"(d[38]),"+f"(d[39]),"+f"(d[40]),"+f"(d[41]),"+f"(d[42]),"+f"(d[43]),"+f"(d[44]),"+f"(d[45]),"+f"(d[46]),"+f"(d[47]),"+f"(d[48]),"+f"(d[49]),"+f"(d[50]),"+f"(d[51]),"+f"(d[52]),"+f"(d[53]),"+f"(d[54]),"+f"(d[55]),"+f"(d[56]),"+f"(d[57]),"+f"(d[58]),"+f"(d[59]),"+f"(d[60]),"+f"(d[61]),"+f"(d[62]),"+f"(d[63]),"+f"(d[64]),"+f"(d[65]),"+f"(d[66]),"+f"(d[67]),"+f"(d[68]),"+f"(d[69]),"+f"(d[70]),"+f"(d[71]),"+f"(d[72]),"+f"(d[73]),"+f"(d[74]),"+f"(d[75]),"+f"(d[76]),"+f"(d[77]),"+f"(d[78]),"+f"(d[79]),"+f"(d[80]),"+f"(d[81]),"+f"(d[82]),"+f"(d[83]),"+f"(d[84]),"+f"(d[85]),"+f"(d[86]),"+f"(d[87]),"+f"(d[88]),"+f"(d[89]),"+f"(d[90]),"+f"(d[91]),"+f"(d[92]),"+f"(d[93]),"+f"(d[94]),"+f"(d[95])
    : "l"(da), "l"(db), "r"(scale_d));
}
__device__ __forceinline__ void wgmma_ss_n64_k(float (&d)[32], uint64_t da, uint64_t db, int scale_d) {
  asm volatile("{\n.reg .pred p;\nsetp.ne.b32 p, %34, 0;\n"
    "wgmma.mma_async.sync.aligned.m64n64k16.f32.bf16.bf16 {%0,%1,%2,%3,%4,%5,%6,%7,%8,%9,%10,%11,%12,%13,%14,%15,%16,%17,%18,%19,%20,%21,%22,%23,%24,%25,%26,%27,%28,%29,%30,%31}, %32, %33, p, 1, 1, 0, 0;\n}\n"
    : "+f"(d[0]),"+f"(d[1]),"+f"(d[2]),"+f"(d[3]),"+f"(d[4]),"+f"(d[5]),"+f"(d[6]),"+f"(d[7]),"+f"(d[8]),"+f"(d[9]),"+f"(d[10]),"+f"(d[11]),"+f"(d[12]),"+f"(d[13]),"+f"(d[14]),"+f"(d[15]),"+f"(d[16]),"+f"(d[17]),"+f"(d[18]),"+f"(d[19]),"+f"(d[20]),"+f"(d[21]),"+f"(d[22]),"+f"(d[23]),"+f"(d[24]),"+f"(d[25]),"+f"(d[26]),"+f"(d[27]),"+f"(d[28]),"+f"(d[29]),"+f"(d[30]),"+f"(d[31])
    : "l"(da), "l"(db), "r"(scale_d));
}
__device__ __forceinline__ void wgmma_rs_n24_tb(float (&d)[12], uint32_t a0, uint32_t a1, uint32_t a2, uint32_t a3, uint64_t db, int scale_d) {
  asm volatile("{\n.reg .pred p;\nsetp.ne.b32 p, %17, 0;\n"
    "wgmma.mma_async.sync.aligned.m64n24k16.f32.bf16.bf16 {%0,%1,%2,%3,%4,%5,%6,%7,%8,%9,%10,%11}, {%12,%13,%14,%15}, %16, p, 1, 1, 1;\n}\n"
    : "+f"(d[0]),"+f"(d[1]),"+f"(d[2]),"+f"(d[3]),"+f"(d[4]),"+f"(d[5]),"+f"(d[6]),"+f"(d[7]),"+f"(d[8]),"+f"(d[9]),"+f"(d[10]),"+f"(d[11])
    : "r"(a0), "r"(a1), "r"(a2), "r"(a3), "l"(db), "r"(scale_d));
}

constexpr int PRE_ROW_BLOCKS = 64;
constexpr int PRE_COL_BLOCKS = 3 * DM / 64;
__device__ __forceinline__ float2 ln_finish(float mean, float var) {
  float mb = bf_round(mean);
  float s = bf_round(sqrtf(bf_round(bf_round(var) + 1e-5f)));
  return make_float2(mb, 1.0f / s);
}
__device__ __forceinline__ void colsum64(const __nv_bfloat16* __restrict__ w, int ld, int c0, float* __restrict__ dst, float (*red)[65], int tid, int bar_id) {
  const int cg = tid & 7, r0 = tid >> 3;
  float acc[8];
#pragma unroll
  for (int i = 0; i < 8; i++) acc[i] = 0.f;
#pragma unroll 10
  for (int r = r0; r < DM; r += 32) {
    uint4 v = __ldg((const uint4*)(w + (size_t)r * ld + c0 + cg * 8));
    acc[0] += bf_lo(v.x); acc[1] += bf_hi(v.x); acc[2] += bf_lo(v.y); acc[3] += bf_hi(v.y);
    acc[4] += bf_lo(v.z); acc[5] += bf_hi(v.z); acc[6] += bf_lo(v.w); acc[7] += bf_hi(v.w);
  }
#pragma unroll
  for (int i = 0; i < 8; i++) red[r0][cg * 8 + i] = acc[i];
  named_bar(bar_id, 256);
  if (tid < 64) {
    float s = 0.f;
#pragma unroll
    for (int r = 0; r < 32; r++) s += red[r][tid];
    dst[c0 + tid] = s;
  }
  named_bar(bar_id, 256);
}
__global__ void __launch_bounds__(1024) pre_kernel(const __nv_bfloat16* __restrict__ x, const __nv_bfloat16* __restrict__ wqkv) {
  TS_BEGIN(0);
  pdl_launch();
  __shared__ float red[51][161];
  const int tid = threadIdx.x, lane = tid & 31, warp = tid >> 5;
  {
    const int ch = tid % 20, rl = tid / 20;
    if (rl < 51) {
      const __nv_bfloat16* w = wqkv + blockIdx.x * 160 + ch * 8;
      uint4 v[13];
#pragma unroll
      for (int i = 0; i < 13; i++) { const int r = rl + i * 51; v[i] = r < DM ? __ldg((const uint4*)(w + (size_t)r * (3 * DM))) : make_uint4(0, 0, 0, 0); }
      float acc[8];
#pragma unroll
      for (int i = 0; i < 8; i++) acc[i] = 0.f;
#pragma unroll
      for (int i = 0; i < 13; i++) {
        acc[0] += bf_lo(v[i].x); acc[1] += bf_hi(v[i].x); acc[2] += bf_lo(v[i].y); acc[3] += bf_hi(v[i].y);
        acc[4] += bf_lo(v[i].z); acc[5] += bf_hi(v[i].z); acc[6] += bf_lo(v[i].w); acc[7] += bf_hi(v[i].w);
      }
#pragma unroll
      for (int i = 0; i < 8; i++) red[rl][ch * 8 + i] = acc[i];
    }
  }
  const int rbeg = blockIdx.x * 171, rend = min(rbeg + 171, S_LEN);
  for (int row0 = rbeg + warp * 2; row0 < rend; row0 += 64) {
    uint4 v[2][3];
#pragma unroll
    for (int k = 0; k < 2; k++) {
      const int row = min(row0 + k, rend - 1);
      const uint4* p = (const uint4*)(x + (size_t)row * DM);
      v[k][0] = __ldg(p + lane); v[k][1] = __ldg(p + 32 + lane);
      v[k][2] = lane < 16 ? __ldg(p + 64 + lane) : make_uint4(0, 0, 0, 0);
    }
#pragma unroll
    for (int k = 0; k < 2; k++) {
      float f[24];
      const uint32_t u[12] = {v[k][0].x, v[k][0].y, v[k][0].z, v[k][0].w, v[k][1].x, v[k][1].y, v[k][1].z, v[k][1].w, v[k][2].x, v[k][2].y, v[k][2].z, v[k][2].w};
#pragma unroll
      for (int j = 0; j < 12; j++) { f[2 * j] = bf_lo(u[j]); f[2 * j + 1] = bf_hi(u[j]); }
      float s = 0.f;
#pragma unroll
      for (int j = 0; j < 24; j++) s += f[j];
#pragma unroll
      for (int o = 16; o; o >>= 1) s += __shfl_xor_sync(~0u, s, o);
      const float mean = s * (1.0f / DM);
      float q = 0.f;
#pragma unroll
      for (int j = 0; j < 16; j++) { const float d = f[j] - mean; q += d * d; }
      if (lane < 16) {
#pragma unroll
        for (int j = 16; j < 24; j++) { const float d = f[j] - mean; q += d * d; }
      }
#pragma unroll
      for (int o = 16; o; o >>= 1) q += __shfl_xor_sync(~0u, q, o);
      if (lane == 0 && row0 + k < rend) g_stat1[row0 + k] = ln_finish(mean, q * (1.0f / DM));
    }
  }
  __syncthreads();
  if (tid < 160) {
    float s = 0.f;
#pragma unroll 17
    for (int r = 0; r < 51; r++) s += red[r][tid];
    g_cs_qkv[blockIdx.x * 160 + tid] = s;
  }
  TS_END(0);
}

enum { EPI_QKV = 0, EPI_WO = 1, EPI_GLU = 2, EPI_DOWN = 3 };
template <int N> struct WG;
template <> struct WG<128> { static __device__ __forceinline__ void mma(float (&d)[64], uint64_t a, uint64_t b, int s) { wgmma_ss_n128(d, a, b, s); } };
template <> struct WG<192> { static __device__ __forceinline__ void mma(float (&d)[96], uint64_t a, uint64_t b, int s) { wgmma_ss_n192(d, a, b, s); } };

template <int BM, int BN, int NB, int STAGES> struct GemmCfg {
  static constexpr int A_BYTES = BM * 128;
  static constexpr int B_BYTES = NB * (BN / 64) * 8192;
  static constexpr int STAGE_BYTES = A_BYTES + B_BYTES;
  static constexpr int SMEM = STAGES * STAGE_BYTES + 1024   + 256   + 4096  ;
};

constexpr float QSCALE = 0.22360679774997896f * 1.4426950408889634f;

template <int BM, int BN, int NB, int KDIM, int STAGES, int EPI, int MINB, int CN, int CM>
__global__ void __launch_bounds__(EPI == EPI_GLU ? 384 : 288, MINB) gemm_kernel(const __grid_constant__ CUtensorMap tmA, const __grid_constant__ CUtensorMap tmB0,
                                                         const __grid_constant__ CUtensorMap tmB1,
                                                         const __nv_bfloat16* resid, __nv_bfloat16* out) {
  using Cfg = GemmCfg<BM, BN, NB, STAGES>;
  constexpr int MB = BM / 128;
  constexpr int KT = KDIM / 64;
  extern __shared__ uint8_t smem_raw[];
  const uint32_t sbase = (smem_u32(smem_raw) + 1023u) & ~1023u;
  uint8_t* sptr = smem_raw + (sbase - smem_u32(smem_raw));
  const uint32_t sbar = sbase + STAGES * Cfg::STAGE_BYTES;
  const int tid = threadIdx.x, warp = tid >> 5, lane = tid & 31;
  const int n0 = blockIdx.x * BN, m0 = blockIdx.y * BM;
  TS_BEGIN(EPI == EPI_QKV ? 1 : EPI + 2);
  TS_MID(EPI == EPI_QKV ? 1 : EPI + 2, 3);
  constexpr int NCL = CN + CM - 1;
  const int cx = blockIdx.x % CN, cy = blockIdx.y % CM;
  if (tid == 0) {
    for (int i = 0; i < STAGES; i++) { mbar_init(sbar + 8 * i, 1); mbar_init(sbar + 8 * (STAGES + i), 2 * NCL); }
    asm volatile("fence.mbarrier_init.release.cluster;" ::: "memory");
  }
  __syncthreads();
  if constexpr (CN * CM > 1) { cluster_arrive(); cluster_wait(); }
  pdl_launch();
  if (warp >= 8) {
    if constexpr (EPI == EPI_GLU) asm volatile("setmaxnreg.dec.sync.aligned.u32 40;");
    if (warp == 8 && lane == 0) {
      auto load_a = [&](int kt, int s) { tma_2d(sbase + s * Cfg::STAGE_BYTES, &tmA, kt * 64, m0, sbar + 8 * s); };
      auto load_b = [&](int kt, int s) {
        const uint32_t sb = sbase + s * Cfg::STAGE_BYTES + Cfg::A_BYTES;
        tma_3d(sb, &tmB0, 0, kt * 64, blockIdx.x * (BN / 64), sbar + 8 * s);
        if constexpr (NB == 2) tma_3d(sb + (BN / 64) * 8192, &tmB1, 0, kt * 64, blockIdx.x * (BN / 64), sbar + 8 * s);
      };
      if constexpr (EPI == EPI_QKV) {
        const int cta = blockIdx.y * gridDim.x + blockIdx.x;
        const uint32_t xb = S_LEN * DM * 2, xs = 21888;
        if (cta * xs < xb) asm volatile("cp.async.bulk.prefetch.L2.global [%0], %1;" :: "l"((const uint8_t*)resid + (size_t)cta * xs), "r"(min(xs, xb - cta * xs)));
        asm volatile("cp.async.bulk.prefetch.L2.global [%0], %1;" :: "l"((const uint8_t*)out + (size_t)cta * 20480), "r"(20480));
      }
      for (int s = 0; s < STAGES; s++) { mbar_expect_tx(sbar + 8 * s, Cfg::STAGE_BYTES); if (EPI != EPI_QKV || s == 0) load_b(s, s); }
      if (EPI != EPI_QKV) pdl_wait();
      for (int s = 0; s < STAGES; s++) { load_a(s, s); if (EPI == EPI_QKV && s > 0) load_b(s, s); }
      for (int kt = STAGES; kt < KT; kt++) {
        const int s = kt % STAGES;
        mbar_wait(sbar + 8 * (STAGES + s), ((kt / STAGES) - 1) & 1);
        mbar_expect_tx(sbar + 8 * s, Cfg::STAGE_BYTES);
        load_a(kt, s);
        load_b(kt, s);
      }
    }
    if constexpr (EPI == EPI_GLU) {
      if (warp > 8) {
        float2* s_st = (float2*)(sptr + STAGES * Cfg::STAGE_BYTES + 256);
        float* s_cs = (float*)(sptr + STAGES * Cfg::STAGE_BYTES + 256 + 1024);
        pdl_wait();
        for (int r = tid - 288; r < BM; r += 96) {
          const float2* pp = &g_part2[(m0 + r) * 8];
          float s = 0.f;
#pragma unroll
          for (int i = 0; i < 8; i++) s += pp[i].x;
          const float mean = s * (1.0f / DM);
          float q = 0.f;
#pragma unroll
          for (int i = 0; i < 8; i++) { const float2 p = pp[i]; const float d = p.x * (1.0f / 80.f) - mean; q += p.y + 80.f * d * d; }
          s_st[r] = ln_finish(mean, q * (1.0f / DM));
        }
        for (int c = tid - 288; c < BN; c += 96) { s_cs[c] = g_cs_g[n0 + c]; s_cs[BN + c] = g_cs_u[n0 + c]; }
        __threadfence_block();
        asm volatile("bar.arrive 2, 352;" ::: "memory");
      }
    }
    if constexpr (CN * CM > 1) { __syncwarp(); cluster_arrive(); cluster_wait(); }
    return;
  }
  if constexpr (EPI == EPI_GLU) asm volatile("setmaxnreg.inc.sync.aligned.u32 232;");
  const int wg = warp >> 2, g = lane >> 2, t = lane & 3;
  float acc[MB][NB][BN / 2];
#pragma unroll
  for (int mb = 0; mb < MB; mb++)
#pragma unroll
    for (int nb = 0; nb < NB; nb++)
#pragma unroll
      for (int i = 0; i < BN / 2; i++) acc[mb][nb][i] = 0.f;
  for (int kt = 0; kt < KT; kt++) {
    const int s = kt % STAGES;
    mbar_wait(sbar + 8 * s, (kt / STAGES) & 1);
    if (kt == 0) TS_MID(EPI == EPI_QKV ? 1 : EPI + 2, 0);
    const uint32_t sa = sbase + s * Cfg::STAGE_BYTES + wg * (MB * 64 * 128);
    const uint32_t sb = sbase + s * Cfg::STAGE_BYTES + Cfg::A_BYTES;
    wgmma_fence();
#pragma unroll
    for (int ks = 0; ks < 4; ks++) {
#pragma unroll
      for (int mb = 0; mb < MB; mb++) {
        const uint64_t da = make_desc(sa + mb * 8192 + ks * 32, 16, 1024, 1);
#pragma unroll
        for (int nb = 0; nb < NB; nb++) {
          const uint64_t db = make_desc(sb + nb * (BN / 64) * 8192 + ks * 2048, 8192, 1024, 1);
          WG<BN>::mma(acc[mb][nb], da, db, 1);
        }
      }
    }
    wgmma_commit();
    wgmma_wait<1>();
    if (kt > 0 && kt - 1 + STAGES < KT && (tid & 127) < NCL) {
      const uint32_t eb = sbar + 8 * (STAGES + (kt - 1) % STAGES);
      if constexpr (CN * CM > 1) {
        const int i = tid & 127;
        const uint32_t rank = i < CN ? cy * CN + i : ((i - CN + (i - CN >= cy ? 1 : 0)) * CN + cx);
        mbar_arrive_remote(eb, rank);
      } else mbar_arrive(eb);
    }
  }
  wgmma_wait<0>();
#pragma unroll
  for (int mb = 0; mb < MB; mb++)
#pragma unroll
    for (int nb = 0; nb < NB; nb++)
#pragma unroll
      for (int i = 0; i < BN / 2; i++) asm volatile("" : "+f"(acc[mb][nb][i]) :: "memory");
  if constexpr (CN * CM > 1) cluster_arrive();
  TS_MID(EPI == EPI_QKV ? 1 : EPI + 2, 1);
  pdl_wait();
  TS_MID(EPI == EPI_QKV ? 1 : EPI + 2, 2);
  named_bar(1, 256);
  constexpr int LDS = BN * 2 + 16;
  const int ctid = tid;

  if constexpr (EPI == EPI_QKV) {
    const int sec = n0 / DM;
    constexpr int lds = 264;
    __shared__ unsigned int s_kn[8];
    if (ctid < 8) s_kn[ctid] = 0u;
    if (blockIdx.x == 0 && blockIdx.y == 0 && ctid < 32) g_flag[ctid] = 0u;
    float2 cs[BN / 8];
#pragma unroll
    for (int j = 0; j < BN / 8; j++) cs[j] = *(const float2*)&g_cs_qkv[n0 + j * 8 + 2 * t];
#pragma unroll
    for (int mb = 0; mb < MB; mb++) {
      const int r0 = wg * (MB * 64) + mb * 64 + (warp & 3) * 16 + g;
      const float2 st0 = g_stat1[m0 + r0], st1 = g_stat1[m0 + r0 + 8];
      const float sc0 = sec == 0 ? st0.y * QSCALE : st0.y, sc1 = sec == 0 ? st1.y * QSCALE : st1.y;
#pragma unroll
      for (int j = 0; j < BN / 8; j++) {
        const float* a = &acc[mb][0][4 * j];
        *(uint32_t*)(sptr + r0 * lds + j * 16 + t * 4) = pack_bf16(fmaf(-st0.x, cs[j].x, a[0]) * sc0, fmaf(-st0.x, cs[j].y, a[1]) * sc0);
        *(uint32_t*)(sptr + (r0 + 8) * lds + j * 16 + t * 4) = pack_bf16(fmaf(-st1.x, cs[j].x, a[2]) * sc1, fmaf(-st1.x, cs[j].y, a[3]) * sc1);
      }
    }
    named_bar(1, 256);
    {
      const int cbase = n0 - sec * DM;
      const int hfirst = cbase / DH;
      const int j = m0 + ctid;
      uint8_t* dst = (uint8_t*)(sec == 0 ? g_q : (sec == 1 ? g_k : g_v)) + (size_t)(j >> 3) * (sec == 0 ? 512 : 384) + (j & 7) * 16;
      const uint8_t* row = sptr + ctid * 264;
#pragma unroll
      for (int i = 0; i < 8; i++) {
        const int hh = hfirst + i;
        const int cr = hh * DH - cbase;
        if (cr < BN) {
          uint2 v[5];
          bool in[5];
          float s = 0.f;
#pragma unroll
          for (int qd = 0; qd < 5; qd++) {
            const int c = cr + 4 * qd;
            in[qd] = c >= 0 && c < BN;
            v[qd] = in[qd] ? *(const uint2*)(row + c * 2) : make_uint2(0u, 0u);
            s += bf_lo(v[qd].x) * bf_lo(v[qd].x) + bf_hi(v[qd].x) * bf_hi(v[qd].x) + bf_lo(v[qd].y) * bf_lo(v[qd].y) + bf_hi(v[qd].y) * bf_hi(v[qd].y);
          }
          uint8_t* p = dst + (size_t)hh * (sec == 0 ? S_LEN * 64 : S_LEN * 48);
          if (in[0] && in[1]) st_g16(p, make_uint4(v[0].x, v[0].y, v[1].x, v[1].y));
          else if (in[0]) st_g8(p, v[0]);
          else if (in[1]) st_g8(p + 8, v[1]);
          if (in[2] && in[3]) st_g16(p + 128, make_uint4(v[2].x, v[2].y, v[3].x, v[3].y));
          else if (in[2]) st_g8(p + 128, v[2]);
          else if (in[3]) st_g8(p + 136, v[3]);
          if (in[4]) {
            st_g16(p + 256, make_uint4(v[4].x, v[4].y, sec == 0 ? 0u : 0x00003f80u, 0u));
            if (sec == 0) st_g16(p + 384, make_uint4(0u, 0u, 0u, 0u));
          }
          if (sec == 1) {
            const unsigned int mxb = __reduce_max_sync(~0u, __float_as_uint(s) & 0x7fffffffu);
            if (lane == 0) atomicMax(&s_kn[i], mxb);
          }
        }
      }
      if (sec == 1) {
        named_bar(1, 256);
        const int hh = hfirst + ctid;
        if (ctid < 8 && hh * DH < cbase + BN) {
          const bool starts_here = hh * DH >= cbase, ends_here = hh * DH + DH <= cbase + BN;
          const float v = __uint_as_float(s_kn[ctid]);
          float* o = &g_kn[(blockIdx.y * NH + hh) * 2];
          if (starts_here) { o[0] = v; if (ends_here) o[1] = 0.f; }
          else o[1] = v;
        }
      }
    }
  } else if constexpr (EPI == EPI_WO || EPI == EPI_DOWN) {
    const int r0 = wg * 64 + (warp & 3) * 16 + g;
#pragma unroll
    for (int j = 0; j < BN / 8; j++) {
      const float* a = &acc[0][0][4 * j];
      *(uint32_t*)(sptr + r0 * LDS + j * 16 + t * 4) = pack_bf16(a[0], a[1]);
      *(uint32_t*)(sptr + (r0 + 8) * LDS + j * 16 + t * 4) = pack_bf16(a[2], a[3]);
    }
    named_bar(1, 256);
#pragma unroll
    for (int i = 0; i < BM * (BN / 8) / 256; i++) {
      const int idx = i * 256 + ctid, r = idx / (BN / 8), c = idx % (BN / 8);
      const uint4 a = *(const uint4*)(sptr + r * LDS + c * 16);
      const size_t go = (size_t)(m0 + r) * DM + n0 + c * 8;
      const uint4 b = ld_g16(resid + go);
      uint4 o;
      o.x = pack_bf16(bf_lo(a.x) + bf_lo(b.x), bf_hi(a.x) + bf_hi(b.x));
      o.y = pack_bf16(bf_lo(a.y) + bf_lo(b.y), bf_hi(a.y) + bf_hi(b.y));
      o.z = pack_bf16(bf_lo(a.z) + bf_lo(b.z), bf_hi(a.z) + bf_hi(b.z));
      o.w = pack_bf16(bf_lo(a.w) + bf_lo(b.w), bf_hi(a.w) + bf_hi(b.w));
      st_g16(out + go, o);
      if constexpr (EPI == EPI_WO) {
        static_assert(BN == 64, "stats assume 8 lanes per row");
        const float f[8] = {bf_lo(o.x), bf_hi(o.x), bf_lo(o.y), bf_hi(o.y), bf_lo(o.z), bf_hi(o.z), bf_lo(o.w), bf_hi(o.w)};
        float s = 0.f;
#pragma unroll
        for (int k = 0; k < 8; k++) s += f[k];
        s += __shfl_xor_sync(~0u, s, 1); s += __shfl_xor_sync(~0u, s, 2); s += __shfl_xor_sync(~0u, s, 4);
        const float mu = s * (1.0f / 64.f);
        float q = 0.f;
#pragma unroll
        for (int k = 0; k < 8; k++) { const float d = f[k] - mu; q += d * d; }
        q += __shfl_xor_sync(~0u, q, 1); q += __shfl_xor_sync(~0u, q, 2); q += __shfl_xor_sync(~0u, q, 4);
        if (c == 0) g_part2[(m0 + r) * 10 + blockIdx.x] = make_float2(s, q);
      }
    }
  } else {
    const int r0 = wg * 64 + (warp & 3) * 16 + g;
    const float2* s_st = (const float2*)(sptr + STAGES * Cfg::STAGE_BYTES + 256);
    const float* s_cs = (const float*)(sptr + STAGES * Cfg::STAGE_BYTES + 256 + 1024);
    named_bar(2, 352);
    float2 st[2] = {s_st[r0], s_st[r0 + 8]};
#pragma unroll
    for (int j = 0; j < BN / 8; j++) {
      const float2 cg = *(const float2*)&s_cs[j * 8 + 2 * t], cu = *(const float2*)&s_cs[BN + j * 8 + 2 * t];
      const float* a = &acc[0][0][4 * j];
      const float* b = &acc[0][1][4 * j];
#pragma unroll
      for (int e = 0; e < 2; e++) {
        const float2 s_ = st[e];
        const uint32_t gp = pack_bf16(fmaf(-s_.x, cg.x, a[2 * e]) * s_.y, fmaf(-s_.x, cg.y, a[2 * e + 1]) * s_.y);
        const uint32_t up = pack_bf16(fmaf(-s_.x, cu.x, b[2 * e]) * s_.y, fmaf(-s_.x, cu.y, b[2 * e + 1]) * s_.y);
        uint32_t r;
        asm("{\n.reg .b32 z;\nmax.bf16x2 z, %1, %3;\nmul.rn.bf16x2 %0, z, %2;\n}" : "=r"(r) : "r"(gp), "r"(up), "r"(0u));
        *(uint32_t*)(sptr + (r0 + 8 * e) * LDS + j * 16 + t * 4) = r;
      }
    }
    named_bar(1, 256);
#pragma unroll
    for (int i = 0; i < BM * (BN / 8) / 256; i++) {
      const int idx = i * 256 + ctid, r = idx / (BN / 8), c = idx % (BN / 8);
      st_g16(out + (size_t)(m0 + r) * DFF + n0 + c * 8, *(const uint4*)(sptr + r * LDS + c * 16));
    }
  }
  if constexpr (CN * CM > 1) cluster_wait();
  TS_END(EPI == EPI_QKV ? 1 : EPI + 2);
}

constexpr int R_STAGES = 8;
constexpr int R_STAGE_BYTES = 16384 + 5 * 2048;
constexpr int R_BAR_OFF = R_STAGES * R_STAGE_BYTES;
constexpr int R_SMEM = R_BAR_OFF + 256 + 1024;
template <int KDIM, bool STATS>
__global__ void __launch_bounds__(288, 1) gemm_res_kernel(const __grid_constant__ CUtensorMap tmA, const __grid_constant__ CUtensorMap tmB,
                                                          const __nv_bfloat16* resid, __nv_bfloat16* out) {
  constexpr int KT = KDIM / 64;
  extern __shared__ uint8_t smem_raw[];
  const uint32_t sbase = (smem_u32(smem_raw) + 1023u) & ~1023u;
  uint8_t* sptr = smem_raw + (sbase - smem_u32(smem_raw));
  const uint32_t sbar = sbase + R_BAR_OFF;
  const int tid = threadIdx.x, warp = tid >> 5, lane = tid & 31;
  const int n0 = blockIdx.x * 80, m0 = blockIdx.y * 128;
  TS_BEGIN(STATS ? 3 : 5);
  if (tid == 0) {
    for (int i = 0; i < R_STAGES; i++) { mbar_init(sbar + 8 * i, 1); mbar_init(sbar + 8 * (R_STAGES + i), 2); }
    asm volatile("fence.mbarrier_init.release.cluster;" ::: "memory");
  }
  __syncthreads();
  pdl_launch();
  if (warp == 8) {
    if (lane == 0) {
      const uint8_t* wt = (const uint8_t*)(STATS ? g_wo_t : g_wd_t) + (size_t)blockIdx.x * KT * 10240;
      auto load_b = [&](int kt, int s) { bulk_g2s(sbase + s * R_STAGE_BYTES + 16384, wt + kt * 10240, 10240, sbar + 8 * s); };
      pdl_wait();
      for (int s = 0; s < R_STAGES; s++) { mbar_expect_tx(sbar + 8 * s, R_STAGE_BYTES); tma_2d(sbase + s * R_STAGE_BYTES, &tmA, s * 64, m0, sbar + 8 * s); load_b(s, s); }
      for (int kt = R_STAGES; kt < KT; kt++) {
        const int s = kt % R_STAGES;
        mbar_wait(sbar + 8 * (R_STAGES + s), ((kt / R_STAGES) - 1) & 1);
        mbar_expect_tx(sbar + 8 * s, R_STAGE_BYTES);
        tma_2d(sbase + s * R_STAGE_BYTES, &tmA, kt * 64, m0, sbar + 8 * s);
        load_b(kt, s);
      }
    }
    return;
  }
  const int wg = warp >> 2, g = lane >> 2, t = lane & 3;
  pdl_wait();
  uint4 rv[5];
#pragma unroll
  for (int i = 0; i < 5; i++) {
    const int idx = i * 256 + tid, r = idx / 10, c = idx % 10;
    rv[i] = ld_g16(resid + (size_t)(m0 + r) * DM + n0 + c * 8);
  }
  float acc[40];
#pragma unroll
  for (int i = 0; i < 40; i++) acc[i] = 0.f;
  for (int kt = 0; kt < KT; kt++) {
    const int s = kt % R_STAGES;
    mbar_wait(sbar + 8 * s, (kt / R_STAGES) & 1);
    if (kt == 0) TS_MID(STATS ? 3 : 5, 0);
    const uint32_t sa = sbase + s * R_STAGE_BYTES + wg * 8192;
    const uint32_t sb = sbase + s * R_STAGE_BYTES + 16384;
    wgmma_fence();
#pragma unroll
    for (int ks = 0; ks < 4; ks++)
      wgmma_ss_n80(acc, make_desc(sa + ks * 32, 16, 1024, 1), make_desc(sb + ks * 2560, 1280, 128, 0), 1);
    wgmma_commit();
    wgmma_wait<1>();
    if (kt > 0 && kt - 1 + R_STAGES < KT && (tid & 127) == 0) mbar_arrive(sbar + 8 * (R_STAGES + (kt - 1) % R_STAGES));
  }
  wgmma_wait<0>();
#pragma unroll
  for (int i = 0; i < 40; i++) asm volatile("" : "+f"(acc[i]) :: "memory");
  TS_MID(STATS ? 3 : 5, 1);
  named_bar(1, 256);
  constexpr int LDS = 176;
  const int r0 = wg * 64 + (warp & 3) * 16 + g;
#pragma unroll
  for (int i = 0; i < 10; i++) {
    *(uint32_t*)(sptr + r0 * LDS + i * 16 + t * 4) = pack_bf16(acc[4 * i], acc[4 * i + 1]);
    *(uint32_t*)(sptr + (r0 + 8) * LDS + i * 16 + t * 4) = pack_bf16(acc[4 * i + 2], acc[4 * i + 3]);
  }
  named_bar(1, 256);
  TS_MID(STATS ? 3 : 5, 2);
#pragma unroll
  for (int i = 0; i < 5; i++) {
    const int idx = i * 256 + tid, r = idx / 10, c = idx % 10;
    const uint4 a = *(const uint4*)(sptr + r * LDS + c * 16);
    const uint4 b = rv[i];
    uint4 o;
    o.x = pack_bf16(bf_lo(a.x) + bf_lo(b.x), bf_hi(a.x) + bf_hi(b.x));
    o.y = pack_bf16(bf_lo(a.y) + bf_lo(b.y), bf_hi(a.y) + bf_hi(b.y));
    o.z = pack_bf16(bf_lo(a.z) + bf_lo(b.z), bf_hi(a.z) + bf_hi(b.z));
    o.w = pack_bf16(bf_lo(a.w) + bf_lo(b.w), bf_hi(a.w) + bf_hi(b.w));
    st_g16(out + (size_t)(m0 + r) * DM + n0 + c * 8, o);
    if constexpr (STATS) *(uint4*)(sptr + r * LDS + c * 16) = o;
  }
  TS_MID(STATS ? 3 : 5, 3);
  if constexpr (STATS) {
    named_bar(1, 256);
    const int r = tid >> 1, hf = tid & 1;
    float f[40];
#pragma unroll
    for (int i = 0; i < 5; i++) {
      const uint4 v = *(const uint4*)(sptr + r * LDS + hf * 80 + i * 16);
      f[8 * i] = bf_lo(v.x); f[8 * i + 1] = bf_hi(v.x); f[8 * i + 2] = bf_lo(v.y); f[8 * i + 3] = bf_hi(v.y);
      f[8 * i + 4] = bf_lo(v.z); f[8 * i + 5] = bf_hi(v.z); f[8 * i + 6] = bf_lo(v.w); f[8 * i + 7] = bf_hi(v.w);
    }
    float s = 0.f;
#pragma unroll
    for (int i = 0; i < 40; i++) s += f[i];
    s += __shfl_xor_sync(~0u, s, 1);
    const float mu = s * (1.0f / 80.f);
    float q = 0.f;
#pragma unroll
    for (int i = 0; i < 40; i++) { const float d = f[i] - mu; q += d * d; }
    q += __shfl_xor_sync(~0u, q, 1);
    if (hf == 0) g_part2[(m0 + r) * 8 + blockIdx.x] = make_float2(s, q);
  }
  TS_END(STATS ? 3 : 5);
}

#define F_MC 0
constexpr int F_CST = 7, F_DST = 3, F_EST = 5;
constexpr int F_RS = 16384 + 5 * 2048;
constexpr int F_DS = 16384 + 6 * 8192;
constexpr int F_E_OFF = 53248;
constexpr int F_STG_OFF = F_DST * F_DS;
constexpr int F_BAR_OFF = F_STG_OFF + 128 * 176;
constexpr int F_VEC_OFF = F_BAR_OFF + 256;
constexpr int F_SMEM = F_VEC_OFF + 1024 + 1536 + 1024;

__device__ __forceinline__ void flag_wait(const unsigned int* f, unsigned int target) {
  unsigned int v, spins = 0;
  do { asm volatile("ld.acquire.gpu.global.u32 %0, [%1];" : "=r"(v) : "l"(f) : "memory"); } while (v < target && ++spins < (1u << 22));
  asm volatile("fence.proxy.async;" ::: "memory");
}
__device__ __forceinline__ void flag_signal(unsigned int* f) {
  asm volatile("fence.proxy.async;" ::: "memory");
  asm volatile("red.release.gpu.global.add.u32 [%0], 1;" :: "l"(f) : "memory");
}

template <bool STATS>
__device__ __forceinline__ void res_epilogue(float (&acc)[40], const uint4 (&rv)[5], uint8_t* stg, __nv_bfloat16* out, int m0, int n0, int tid, int bx) {
  constexpr int LDS = 176;
  const int warp = tid >> 5, lane = tid & 31;
  const int r0 = (warp >> 2) * 64 + (warp & 3) * 16 + (lane >> 2), t = lane & 3;
#pragma unroll
  for (int i = 0; i < 10; i++) {
    *(uint32_t*)(stg + r0 * LDS + i * 16 + t * 4) = pack_bf16(acc[4 * i], acc[4 * i + 1]);
    *(uint32_t*)(stg + (r0 + 8) * LDS + i * 16 + t * 4) = pack_bf16(acc[4 * i + 2], acc[4 * i + 3]);
  }
  named_bar(1, 256);
#pragma unroll
  for (int i = 0; i < 5; i++) {
    const int idx = i * 256 + tid, r = idx / 10, c = idx % 10;
    const uint4 a = *(const uint4*)(stg + r * LDS + c * 16);
    const uint4 b = rv[i];
    uint4 o;
    o.x = pack_bf16(bf_lo(a.x) + bf_lo(b.x), bf_hi(a.x) + bf_hi(b.x));
    o.y = pack_bf16(bf_lo(a.y) + bf_lo(b.y), bf_hi(a.y) + bf_hi(b.y));
    o.z = pack_bf16(bf_lo(a.z) + bf_lo(b.z), bf_hi(a.z) + bf_hi(b.z));
    o.w = pack_bf16(bf_lo(a.w) + bf_lo(b.w), bf_hi(a.w) + bf_hi(b.w));
    st_g16(out + (size_t)(m0 + r) * DM + n0 + c * 8, o);
    if constexpr (STATS) *(uint4*)(stg + r * LDS + c * 16) = o;
  }
  if constexpr (STATS) {
    named_bar(1, 256);
    const int r = tid >> 1, hf = tid & 1;
    float f[40];
#pragma unroll
    for (int i = 0; i < 5; i++) {
      const uint4 v = *(const uint4*)(stg + r * LDS + hf * 80 + i * 16);
      f[8 * i] = bf_lo(v.x); f[8 * i + 1] = bf_hi(v.x); f[8 * i + 2] = bf_lo(v.y); f[8 * i + 3] = bf_hi(v.y);
      f[8 * i + 4] = bf_lo(v.z); f[8 * i + 5] = bf_hi(v.z); f[8 * i + 6] = bf_lo(v.w); f[8 * i + 7] = bf_hi(v.w);
    }
    float s = 0.f;
#pragma unroll
    for (int i = 0; i < 40; i++) s += f[i];
    s += __shfl_xor_sync(~0u, s, 1);
    const float mu = s * (1.0f / 80.f);
    float q = 0.f;
#pragma unroll
    for (int i = 0; i < 40; i++) { const float d = f[i] - mu; q += d * d; }
    q += __shfl_xor_sync(~0u, q, 1);
    if (hf == 0) g_part2[(m0 + r) * 8 + bx] = make_float2(s, q);
  }
}

__global__ void __launch_bounds__(384, 1) post_kernel(const __grid_constant__ CUtensorMap tmO, const __grid_constant__ CUtensorMap tmWo,
                                                      const __grid_constant__ CUtensorMap tmH, const __grid_constant__ CUtensorMap tmWg,
                                                      const __grid_constant__ CUtensorMap tmWu, const __grid_constant__ CUtensorMap tmAct,
                                                      const __grid_constant__ CUtensorMap tmWd, const __nv_bfloat16* x, __nv_bfloat16* out) {
  extern __shared__ uint8_t smem_raw[];
  const uint32_t sbase = (smem_u32(smem_raw) + 1023u) & ~1023u;
  uint8_t* sptr = smem_raw + (sbase - smem_u32(smem_raw));
  const uint32_t bC = sbase + F_BAR_OFF, bD = bC + 16 * F_CST, bE = bD + 16 * F_DST;
  const int tid = threadIdx.x, warp = tid >> 5, lane = tid & 31;
  const int bx = blockIdx.x, rb = blockIdx.y, m0 = rb * 128, cx = bx & 1;
  TS_BEGIN(3);
  if (tid == 0) {
    for (int i = 0; i < F_CST; i++) { mbar_init(bC + 8 * i, 1); mbar_init(bC + 8 * (F_CST + i), F_MC ? 4 : 2); }
    for (int i = 0; i < F_DST; i++) { mbar_init(bD + 8 * i, 1); mbar_init(bD + 8 * (F_DST + i), F_MC ? 4 : 2); }
    for (int i = 0; i < F_EST; i++) { mbar_init(bE + 8 * i, 1); mbar_init(bE + 8 * (F_EST + i), F_MC ? 4 : 2); }
    asm volatile("fence.mbarrier_init.release.cluster;" ::: "memory");
  }
  __syncthreads();
  if (F_MC) { cluster_arrive(); cluster_wait(); }
  if (warp >= 8) {
    asm volatile("setmaxnreg.dec.sync.aligned.u32 40;");
    if (warp == 8) {
      if (lane == 0) {
        auto load_a = [&](const CUtensorMap* tm, uint32_t stage, int kt, uint32_t bar) {
          if (F_MC) tma_2d_mc(stage + cx * 8192, tm, kt * 64, m0 + cx * 64, bar, (uint16_t)3); else tma_2d(stage, tm, kt * 64, m0, bar);
        };
        for (int s = 0; s < F_CST; s++) { mbar_expect_tx(bC + 8 * s, F_RS); if (s < 3) tma_3d(sbase + s * F_RS + 16384, &tmWo, 0, s * 64, bx * 5, bC + 8 * s); }
        pdl_wait();
        for (int s = 0; s < F_CST; s++) { load_a(&tmO, sbase + s * F_RS, s, bC + 8 * s); if (s >= 3) tma_3d(sbase + s * F_RS + 16384, &tmWo, 0, s * 64, bx * 5, bC + 8 * s); }
        for (int kt = F_CST; kt < 10; kt++) {
          const int s = kt - F_CST;
          mbar_wait(bC + 8 * (F_CST + s), 0);
          mbar_expect_tx(bC + 8 * s, F_RS);
          load_a(&tmO, sbase + s * F_RS, kt, bC + 8 * s);
          tma_3d(sbase + s * F_RS + 16384, &tmWo, 0, kt * 64, bx * 5, bC + 8 * s);
        }
        auto load_bd = [&](int kt, int s) {
          tma_3d(sbase + s * F_DS + 16384, &tmWg, 0, kt * 64, bx * 3, bD + 8 * s);
          tma_3d(sbase + s * F_DS + 16384 + 3 * 8192, &tmWu, 0, kt * 64, bx * 3, bD + 8 * s);
        };
        for (int s = 0; s < F_DST; s++) { mbar_wait(bD + 8 * (F_DST + s), 0); mbar_expect_tx(bD + 8 * s, F_DS); load_bd(s, s); }
        flag_wait(&g_flag[rb], 8);
        for (int s = 0; s < F_DST; s++) load_a(&tmH, sbase + s * F_DS, s, bD + 8 * s);
        for (int kt = F_DST; kt < 10; kt++) {
          const int s = kt % F_DST;
          mbar_wait(bD + 8 * (F_DST + s), (kt / F_DST) & 1);
          mbar_expect_tx(bD + 8 * s, F_DS);
          load_a(&tmH, sbase + s * F_DS, kt, bD + 8 * s);
          load_bd(kt, s);
        }
        const uint32_t eb = sbase + F_E_OFF;
        for (int s = 0; s < F_EST; s++) { mbar_wait(bE + 8 * (F_EST + s), 0); mbar_expect_tx(bE + 8 * s, F_RS); tma_3d(eb + s * F_RS + 16384, &tmWd, 0, s * 64, bx * 5, bE + 8 * s); }
        flag_wait(&g_flag[16 + rb], 8);
        for (int s = 0; s < F_EST; s++) load_a(&tmAct, eb + s * F_RS, s, bE + 8 * s);
        for (int kt = F_EST; kt < 24; kt++) {
          const int s = kt % F_EST;
          mbar_wait(bE + 8 * (F_EST + s), (kt / F_EST) & 1);
          mbar_expect_tx(bE + 8 * s, F_RS);
          load_a(&tmAct, eb + s * F_RS, kt, bE + 8 * s);
          tma_3d(eb + s * F_RS + 16384, &tmWd, 0, kt * 64, bx * 5, bE + 8 * s);
        }
      }
    } else {
      float2* s_st = (float2*)(sptr + F_VEC_OFF);
      float* s_cs = (float*)(sptr + F_VEC_OFF + 1024);
      pdl_wait();
      for (int c = tid - 288; c < 192; c += 96) { s_cs[c] = g_cs_g[bx * 192 + c]; s_cs[192 + c] = g_cs_u[bx * 192 + c]; }
      flag_wait(&g_flag[rb], 8);
      for (int r = tid - 288; r < 128; r += 96) {
        const float2* pp = &g_part2[(m0 + r) * 8];
        float2 p[8];
        float s = 0.f;
#pragma unroll
        for (int i = 0; i < 8; i++) { asm volatile("ld.global.v2.f32 {%0, %1}, [%2];" : "=f"(p[i].x), "=f"(p[i].y) : "l"(pp + i) : "memory"); s += p[i].x; }
        const float mean = s * (1.0f / DM);
        float q = 0.f;
#pragma unroll
        for (int i = 0; i < 8; i++) { const float d = p[i].x * (1.0f / 80.f) - mean; q += p[i].y + 80.f * d * d; }
        s_st[r] = ln_finish(mean, q * (1.0f / DM));
      }
      __threadfence_block();
      asm volatile("bar.arrive 2, 352;" ::: "memory");
    }
    if (F_MC) { __syncwarp(); cluster_arrive(); cluster_wait(); }
    return;
  }
  asm volatile("setmaxnreg.inc.sync.aligned.u32 232;");
  const int wg = warp >> 2, g = lane >> 2, t = lane & 3;
  auto release = [&](uint32_t bar) { if (F_MC) { if ((tid & 127) < 2) mbar_arrive_remote(bar, (tid & 127) ^ cx); } else if ((tid & 127) == 0) mbar_arrive(bar); };
  const int n0 = bx * 80;
  uint4 rv[5];
  pdl_wait();
  {
#pragma unroll
    for (int i = 0; i < 5; i++) { const int idx = i * 256 + tid, r = idx / 10, c = idx % 10; rv[i] = ld_g16(x + (size_t)(m0 + r) * DM + n0 + c * 8); }
    float acc[40];
#pragma unroll
    for (int i = 0; i < 40; i++) acc[i] = 0.f;
    for (int kt = 0; kt < 10; kt++) {
      const int s = kt % F_CST;
      mbar_wait(bC + 8 * s, kt / F_CST);
      if (kt == 0) TS_MID(3, 0);
      const uint32_t sa = sbase + s * F_RS + wg * 8192, sb = sbase + s * F_RS + 16384;
      wgmma_fence();
#pragma unroll
      for (int ks = 0; ks < 4; ks++) wgmma_ss_n80(acc, make_desc(sa + ks * 32, 16, 1024, 1), make_desc(sb + ks * 512, 2048, 256, 3), 1);
      wgmma_commit();
      wgmma_wait<1>();
      if (kt > 0 && kt - 1 + F_CST < 10) release(bC + 8 * (F_CST + kt - 1));
    }
    wgmma_wait<0>();
#pragma unroll
    for (int i = 0; i < 40; i++) asm volatile("" : "+f"(acc[i]) :: "memory");
    for (int s = 0; s < F_DST; s++) release(bD + 8 * (F_DST + s));
    TS_MID(3, 1);
    res_epilogue<true>(acc, rv, sptr + F_STG_OFF, g_h, m0, n0, tid, bx);
    __threadfence();
    named_bar(1, 256);
    if (tid == 0) flag_signal(&g_flag[rb]);
    TS_END(3);
  }
  {
    float acc[2][96];
#pragma unroll
    for (int i = 0; i < 96; i++) { acc[0][i] = 0.f; acc[1][i] = 0.f; }
    for (int kt = 0; kt < 10; kt++) {
      const int s = kt % F_DST;
      mbar_wait(bD + 8 * s, (kt / F_DST) & 1);
      if (kt == 0) TS_MID(4, 0);
      const uint32_t sa = sbase + s * F_DS + wg * 8192, sb = sbase + s * F_DS + 16384;
      wgmma_fence();
#pragma unroll
      for (int ks = 0; ks < 4; ks++) {
        const uint64_t da = make_desc(sa + ks * 32, 16, 1024, 1);
        wgmma_ss_n192(acc[0], da, make_desc(sb + ks * 2048, 8192, 1024, 1), 1);
        wgmma_ss_n192(acc[1], da, make_desc(sb + 3 * 8192 + ks * 2048, 8192, 1024, 1), 1);
      }
      wgmma_commit();
      wgmma_wait<1>();
      if (kt > 0 && kt - 1 + F_DST < 10) release(bD + 8 * (F_DST + (kt - 1) % F_DST));
    }
    wgmma_wait<0>();
#pragma unroll
    for (int i = 0; i < 96; i++) { asm volatile("" : "+f"(acc[0][i]) :: "memory"); asm volatile("" : "+f"(acc[1][i]) :: "memory"); }
    for (int s = 0; s < F_EST; s++) release(bE + 8 * (F_EST + s));
    TS_MID(4, 1);
    named_bar(1, 256);
    named_bar(2, 352);
    constexpr int LDS = 400;
    const float2* s_st = (const float2*)(sptr + F_VEC_OFF);
    const float* s_cs = (const float*)(sptr + F_VEC_OFF + 1024);
    const int r0 = wg * 64 + (warp & 3) * 16 + g;
    const float2 st[2] = {s_st[r0], s_st[r0 + 8]};
#pragma unroll
    for (int j = 0; j < 24; j++) {
      const float2 cg = *(const float2*)&s_cs[j * 8 + 2 * t], cu = *(const float2*)&s_cs[192 + j * 8 + 2 * t];
      const float* a = &acc[0][4 * j];
      const float* b = &acc[1][4 * j];
#pragma unroll
      for (int e = 0; e < 2; e++) {
        const float2 s_ = st[e];
        const uint32_t gp = pack_bf16(fmaf(-s_.x, cg.x, a[2 * e]) * s_.y, fmaf(-s_.x, cg.y, a[2 * e + 1]) * s_.y);
        const uint32_t up = pack_bf16(fmaf(-s_.x, cu.x, b[2 * e]) * s_.y, fmaf(-s_.x, cu.y, b[2 * e + 1]) * s_.y);
        uint32_t r;
        asm("{\n.reg .b32 z;\nmax.bf16x2 z, %1, %3;\nmul.rn.bf16x2 %0, z, %2;\n}" : "=r"(r) : "r"(gp), "r"(up), "r"(0u));
        *(uint32_t*)(sptr + (r0 + 8 * e) * LDS + j * 16 + t * 4) = r;
      }
    }
    named_bar(1, 256);
#pragma unroll
    for (int i = 0; i < 12; i++) {
      const int idx = i * 256 + tid, r = idx / 24, c = idx % 24;
      st_g16(g_act + (size_t)(m0 + r) * DFF + bx * 192 + c * 8, *(const uint4*)(sptr + r * LDS + c * 16));
    }
    __threadfence();
    named_bar(1, 256);
    if (tid == 0) flag_signal(&g_flag[16 + rb]);
    TS_END(4);
  }
  {
#pragma unroll
    for (int i = 0; i < 5; i++) { const int idx = i * 256 + tid, r = idx / 10, c = idx % 10; rv[i] = ld_g16(g_h + (size_t)(m0 + r) * DM + n0 + c * 8); }
    float acc[40];
#pragma unroll
    for (int i = 0; i < 40; i++) acc[i] = 0.f;
    const uint32_t eb = sbase + F_E_OFF;
    for (int kt = 0; kt < 24; kt++) {
      const int s = kt % F_EST;
      mbar_wait(bE + 8 * s, (kt / F_EST) & 1);
      if (kt == 0) TS_MID(5, 0);
      const uint32_t sa = eb + s * F_RS + wg * 8192, sb = eb + s * F_RS + 16384;
      wgmma_fence();
#pragma unroll
      for (int ks = 0; ks < 4; ks++) wgmma_ss_n80(acc, make_desc(sa + ks * 32, 16, 1024, 1), make_desc(sb + ks * 512, 2048, 256, 3), 1);
      wgmma_commit();
      wgmma_wait<1>();
      if (kt > 0 && kt - 1 + F_EST < 24) release(bE + 8 * (F_EST + (kt - 1) % F_EST));
    }
    wgmma_wait<0>();
#pragma unroll
    for (int i = 0; i < 40; i++) asm volatile("" : "+f"(acc[i]) :: "memory");
    if (F_MC) cluster_arrive();
    TS_MID(5, 1);
    res_epilogue<false>(acc, rv, sptr + F_STG_OFF, out, m0, n0, tid, bx);
    if (F_MC) cluster_wait();
    TS_END(5);
  }
}

#define POLY_NUM 5
__device__ __forceinline__ float ex2_poly(float x, int shl23) {
  const float MAGIC = 12582912.f;
  const float tt = x + MAGIC;
  const float f = x - (tt - MAGIC);
  float p = fmaf(0.0013276472454890609f, f, 0.009675540961325169f);
  p = fmaf(p, f, 0.05550713092088699f);
  p = fmaf(p, f, 0.24022120237350464f);
  p = fmaf(p, f, 0.6931469440460205f);
  p = fmaf(p, f, 1.0000001192092896f);
  return __int_as_float(__float_as_int(tt) * shl23 + __float_as_int(p));
}
constexpr int KV_BYTES = S_LEN * 48;
constexpr int ATT_SMEM = 2 * KV_BYTES + 256 + 32768;
constexpr int ATT_BODY = 8;

__global__ void __launch_bounds__(512, 1) attn_kernel(int shl23, const __nv_bfloat16* __restrict__ wg_, const __nv_bfloat16* __restrict__ wu_,
                                                      const __nv_bfloat16* __restrict__ wo_, const __nv_bfloat16* __restrict__ wd_) {
  extern __shared__ __align__(1024) uint8_t smem[];
  if (blockIdx.x >= 128) {
    pdl_launch();
    const int e = blockIdx.x - 128, half = threadIdx.x >> 8;
    for (int rd = 0; rd < 4; rd++) {
      const int tile0 = e * 68 + rd * 17;
      uint4 v[22];
#pragma unroll
      for (int i = 0; i < 22; i++) {
        const int c = i * 512 + threadIdx.x;
        if (c < 17 * 640) {
          const int tl = tile0 + c / 640, cc = c % 640, k = cc / 10, nc = cc % 10;
          const bool isd = tl >= 80;
          const int tt = isd ? tl - 80 : tl, j = isd ? tt / 24 : tt / 10, kt = isd ? tt % 24 : tt % 10;
          v[i] = __ldg((const uint4*)((isd ? wd_ : wo_) + (size_t)(kt * 64 + k) * DM + j * 80 + nc * 8));
        }
      }
#pragma unroll
      for (int i = 0; i < 22; i++) {
        const int c = i * 512 + threadIdx.x;
        if (c < 17 * 640) {
          const int cc = c % 640, k = cc / 10, nc = cc % 10;
          *(uint4*)(smem + (c / 640) * 10240 + (k >> 3) * 1280 + nc * 128 + (k & 7) * 16) = v[i];
        }
      }
      __syncthreads();
#pragma unroll
      for (int i = 0; i < 22; i++) {
        const int c = i * 512 + threadIdx.x;
        if (c < 17 * 640) {
          const int tl = tile0 + c / 640;
          uint8_t* dst = tl >= 80 ? (uint8_t*)g_wd_t + (size_t)(tl - 80) * 10240 : (uint8_t*)g_wo_t + (size_t)tl * 10240;
          st_g16(dst + (c % 640) * 16, *(const uint4*)(smem + c * 16));
        }
      }
      __syncthreads();
    }
    float (*red)[65] = (float (*)[65])(smem + half * 16384);
    for (int b = e * 12 + half; b < e * 12 + 12; b += 2) {
      if (b < 24) colsum64(wg_, DFF, b * 64, g_cs_g, red, threadIdx.x & 255, 1 + half);
      else colsum64(wu_, DFF, (b - 24) * 64, g_cs_u, red, threadIdx.x & 255, 1 + half);
    }
    return;
  }
  const int h = blockIdx.x >> 2, qb = blockIdx.x & 3;
  const uint32_t sK = smem_u32(smem), sV = sK + KV_BYTES, sBar = sV + KV_BYTES;
  const int tid = threadIdx.x;
  TS_BEGIN(2);
  if (tid == 0) {
    for (int i = 0; i < 9; i++) mbar_init(sBar + 8 * i, 1);
    asm volatile("fence.mbarrier_init.release.cluster;" ::: "memory");
  }
  __syncthreads();
  pdl_launch();
  pdl_wait();
  TS_MID(2, 0);
  const uint8_t* gk = (const uint8_t*)(g_k + (size_t)h * S_LEN * 24);
  const uint8_t* gv = (const uint8_t*)(g_v + (size_t)h * S_LEN * 24);
  auto load_kv = [&](int i0, int i1) {
    for (int i = i0; i < i1; i++) {
      mbar_expect_tx(sBar + 8 * i, 2 * 12288);
      bulk_g2s(sK + i * 12288, gk + i * 12288, 12288, sBar + 8 * i);
      bulk_g2s(sV + i * 12288, gv + i * 12288, 12288, sBar + 8 * i);
    }
  };
  if (tid == 0) {
    mbar_expect_tx(sBar + 64, 32768);
    bulk_g2s(sBar + 256, (const uint8_t*)g_q + ((size_t)h * S_LEN + qb * 512) * 64, 32768, sBar + 64);
    load_kv(0, 2);
  }
  float ka = 0.f, kb = 0.f;
#pragma unroll
  for (int i = 0; i < 8; i++) {
    const float2 v = *(const float2*)&g_kn[(i * NH + h) * 2];
    ka = (v.x > ka || v.x != v.x) ? v.x : ka;
    kb = (v.y > kb || v.y != v.y) ? v.y : kb;
  }
  bool fast;
  {
    const float kn = sqrtf(ka + kb);
    mbar_wait(sBar + 64, 0);
    if (tid == 0) load_kv(2, 8);
    uint8_t* qrow = smem + 2 * KV_BYTES + 256 + (tid >> 3) * 512 + (tid & 7) * 16;
    const uint4 c0 = *(const uint4*)qrow, c1 = *(const uint4*)(qrow + 128);
    const uint2 c2 = *(const uint2*)(qrow + 256);
    auto sq = [](uint32_t u) { const float a = bf_lo(u), b = bf_hi(u); return a * a + b * b; };
    const float n2 = sq(c0.x) + sq(c0.y) + sq(c0.z) + sq(c0.w) + sq(c1.x) + sq(c1.y) + sq(c1.z) + sq(c1.w) + sq(c2.x) + sq(c2.y);
    const float m = ceilf(sqrtf(n2) * kn * 1.001f) + 1.f;
    fast = __syncthreads_or(!(m <= 62.f)) == 0;
    if (fast) *(uint32_t*)(qrow + 256 + 8) = pack_bf16(-m, 0.f);
    asm volatile("fence.proxy.async.shared::cta;" ::: "memory");
    __syncthreads();
  }
  auto write_out = [&](float (&O)[12], int it) {
    uint32_t tid2;
    asm volatile("mov.u32 %0, %%tid.x;" : "=r"(tid2));
    const int lane2 = tid2 & 31, t2 = lane2 & 3;
    const int qq = (blockIdx.x & 3) * 512 + (it * 4 + (tid2 >> 7)) * 64 + ((tid2 >> 5) & 3) * 16 + (lane2 >> 2);
    const float l0 = __shfl_sync(~0u, O[8], (lane2 & ~3) | 2), l1 = __shfl_sync(~0u, O[10], (lane2 & ~3) | 2);
    const float r0 = 1.f / l0, r1 = 1.f / l1;
    uint32_t* o0 = (uint32_t*)(g_o + (size_t)qq * DM + (blockIdx.x >> 2) * DH);
    uint32_t* o1 = o0 + 8 * DM / 2;
    o0[t2] = pack_bf16(O[0] * r0, O[1] * r0); o1[t2] = pack_bf16(O[2] * r1, O[3] * r1);
    o0[t2 + 4] = pack_bf16(O[4] * r0, O[5] * r0); o1[t2 + 4] = pack_bf16(O[6] * r1, O[7] * r1);
    if (t2 < 2) { o0[t2 + 8] = pack_bf16(O[8] * r0, O[9] * r0); o1[t2 + 8] = pack_bf16(O[10] * r1, O[11] * r1); }
  };
  TS_MID(2, 1);
  if (fast) {
#pragma unroll 1
    for (int it = 0; it < 2; it++) {
      const uint64_t dq = make_desc(sBar + 256 + (it * 4 + (tid >> 7)) * 4096, 128, 512, 0);
      float O[12];
#pragma unroll
      for (int i = 0; i < 12; i++) { O[i] = 0.f; asm volatile("" : "+f"(O[i]) :: "memory"); }
      float S[2][32];
      uint32_t P[16];
#pragma unroll 1
      for (int jb = 0; jb < 32 / ATT_BODY; jb++) {
        if (it == 0) { for (int c = 0; c < ATT_BODY / 4; c++) mbar_wait(sBar + 8 * (jb * (ATT_BODY / 4) + c), 0); }
        const uint64_t dk0 = make_desc(sK + jb * ATT_BODY * 8 * 384, 128, 384, 0);
        const uint64_t dv0 = make_desc(sV + jb * ATT_BODY * 8 * 384, 384, 128, 0);
        wgmma_fence();
        wgmma_ss_n64_k(S[0], dq, dk0, 0);
        wgmma_ss_n64_k(S[0], dq + (256 >> 4), dk0 + (256 >> 4), 1);
        wgmma_commit();
#pragma unroll
        for (int u = 0; u < ATT_BODY; u++) {
          if (u + 1 < ATT_BODY) {
            const uint64_t dk = dk0 + (((u + 1) * 8 * 384) >> 4);
            wgmma_fence();
            wgmma_ss_n64_k(S[(u + 1) & 1], dq, dk, 0);
            wgmma_ss_n64_k(S[(u + 1) & 1], dq + (256 >> 4), dk + (256 >> 4), 1);
            wgmma_commit();
          }
          if (u == 0 || u == ATT_BODY - 1) wgmma_wait<1>(); else wgmma_wait<2>();
#pragma unroll
          for (int i = 0; i < 32; i++) asm volatile("" : "+f"(S[u & 1][i]) :: "memory");
          const uint64_t dv = dv0 + ((u * 8 * 384) >> 4);
#pragma unroll
          for (int hf = 0; hf < 2; hf++) {
            if (hf == 1 && u > 0) { if (u == ATT_BODY - 1) wgmma_wait<1>(); else wgmma_wait<2>(); }
#pragma unroll
            for (int i = hf * 8; i < hf * 8 + 8; i++) {
              const bool usepoly = ((i + 1) * POLY_NUM / 16) != (i * POLY_NUM / 16);
              float a, b;
              if (usepoly) { a = ex2_poly(S[u & 1][2 * i], shl23); b = ex2_poly(S[u & 1][2 * i + 1], shl23); }
              else { a = ex2_mufu(S[u & 1][2 * i]); b = ex2_mufu(S[u & 1][2 * i + 1]); }
              P[i] = pack_bf16(a, b);
            }
            wgmma_fence();
#pragma unroll
            for (int ks = hf * 2; ks < hf * 2 + 2; ks++)
              wgmma_rs_n24_tb(O, P[4 * ks], P[4 * ks + 1], P[4 * ks + 2], P[4 * ks + 3], dv + ((ks * 768) >> 4), 1);
            wgmma_commit();
          }
        }
        wgmma_wait<0>();
      }
#pragma unroll
      for (int i = 0; i < 12; i++) asm volatile("" : "+f"(O[i]) :: "memory");
      write_out(O, it);
      if (it == 0) TS_MID(2, 2);
    }
  } else {
#pragma unroll 1
    for (int it = 0; it < 2; it++) {
      const uint64_t dq = make_desc(sBar + 256 + (it * 4 + (tid >> 7)) * 4096, 128, 512, 0);
      float O[12];
#pragma unroll
      for (int i = 0; i < 12; i++) { O[i] = 0.f; asm volatile("" : "+f"(O[i]) :: "memory"); }
      float S[32];
      float mx0 = -INFINITY, mx1 = -INFINITY;
#pragma unroll 1
      for (int j = 0; j < 32; j++) {
        if (it == 0 && (j & 3) == 0) mbar_wait(sBar + 8 * (j >> 2), 0);
        const uint64_t dk = make_desc(sK + j * 8 * 384, 128, 384, 0);
        wgmma_fence();
        wgmma_ss_n64_k(S, dq, dk, 0);
        wgmma_ss_n64_k(S, dq + (256 >> 4), dk + (256 >> 4), 1);
        wgmma_commit();
        wgmma_wait<0>();
#pragma unroll
        for (int i = 0; i < 8; i++) {
          mx0 = fmaxf(mx0, fmaxf(S[4 * i], S[4 * i + 1]));
          mx1 = fmaxf(mx1, fmaxf(S[4 * i + 2], S[4 * i + 3]));
        }
      }
      mx0 = fmaxf(mx0, __shfl_xor_sync(~0u, mx0, 1)); mx0 = fmaxf(mx0, __shfl_xor_sync(~0u, mx0, 2));
      mx1 = fmaxf(mx1, __shfl_xor_sync(~0u, mx1, 1)); mx1 = fmaxf(mx1, __shfl_xor_sync(~0u, mx1, 2));
#pragma unroll 1
      for (int j = 0; j < 32; j++) {
        const uint64_t dk = make_desc(sK + j * 8 * 384, 128, 384, 0);
        wgmma_fence();
        wgmma_ss_n64_k(S, dq, dk, 0);
        wgmma_ss_n64_k(S, dq + (256 >> 4), dk + (256 >> 4), 1);
        wgmma_commit();
        wgmma_wait<0>();
        uint32_t P[16];
#pragma unroll
        for (int i = 0; i < 8; i++) {
          P[2 * i] = pack_bf16(ex2_mufu(S[4 * i] - mx0), ex2_mufu(S[4 * i + 1] - mx0));
          P[2 * i + 1] = pack_bf16(ex2_mufu(S[4 * i + 2] - mx1), ex2_mufu(S[4 * i + 3] - mx1));
        }
        wgmma_fence();
        const uint64_t dv = make_desc(sV + j * 8 * 384, 384, 128, 0);
#pragma unroll
        for (int ks = 0; ks < 4; ks++)
          wgmma_rs_n24_tb(O, P[4 * ks], P[4 * ks + 1], P[4 * ks + 2], P[4 * ks + 3], dv + ((ks * 768) >> 4), 1);
        wgmma_commit();
        wgmma_wait<0>();
      }
#pragma unroll
      for (int i = 0; i < 12; i++) asm volatile("" : "+f"(O[i]) :: "memory");
      write_out(O, it);
    }
  }
  TS_END(2);
}

typedef CUresult (*EncodeFn)(CUtensorMap*, CUtensorMapDataType, cuuint32_t, void*, const cuuint64_t*, const cuuint64_t*, const cuuint32_t*,
                             const cuuint32_t*, CUtensorMapInterleave, CUtensorMapSwizzle, CUtensorMapL2promotion, CUtensorMapFloatOOBfill);
static EncodeFn get_encode() {
  static EncodeFn fn = nullptr;
  if (!fn) {
    void* p = nullptr; cudaDriverEntryPointQueryResult st;
    cudaGetDriverEntryPoint("cuTensorMapEncodeTiled", &p, cudaEnableDefault, &st);
    fn = (EncodeFn)p;
  }
  return fn;
}
static CUtensorMap make_map(const void* ptr, int rows, int cols, int box_rows, int box_cols = 64) {
  CUtensorMap m;
  cuuint64_t dims[2] = {(cuuint64_t)cols, (cuuint64_t)rows};
  cuuint64_t strides[1] = {(cuuint64_t)cols * 2};
  cuuint32_t box[2] = {(cuuint32_t)box_cols, (cuuint32_t)box_rows};
  cuuint32_t es[2] = {1, 1};
  get_encode()(&m, CU_TENSOR_MAP_DATA_TYPE_BFLOAT16, 2, const_cast<void*>(ptr), dims, strides, box, es, CU_TENSOR_MAP_INTERLEAVE_NONE,
               box_cols == 64 ? CU_TENSOR_MAP_SWIZZLE_128B : (box_cols == 32 ? CU_TENSOR_MAP_SWIZZLE_64B : CU_TENSOR_MAP_SWIZZLE_32B), CU_TENSOR_MAP_L2_PROMOTION_L2_128B, CU_TENSOR_MAP_FLOAT_OOB_FILL_NONE);
  return m;
}
static CUtensorMap make_map_w(const void* ptr, int rows, int cols, int bc, int nblk) {
  CUtensorMap m;
  cuuint64_t dims[3] = {(cuuint64_t)bc, (cuuint64_t)rows, (cuuint64_t)(cols / bc)};
  cuuint64_t strides[2] = {(cuuint64_t)cols * 2, (cuuint64_t)bc * 2};
  cuuint32_t box[3] = {(cuuint32_t)bc, 64, (cuuint32_t)nblk};
  cuuint32_t es[3] = {1, 1, 1};
  get_encode()(&m, CU_TENSOR_MAP_DATA_TYPE_BFLOAT16, 3, const_cast<void*>(ptr), dims, strides, box, es, CU_TENSOR_MAP_INTERLEAVE_NONE,
               bc == 64 ? CU_TENSOR_MAP_SWIZZLE_128B : (bc == 32 ? CU_TENSOR_MAP_SWIZZLE_64B : CU_TENSOR_MAP_SWIZZLE_32B),
               CU_TENSOR_MAP_L2_PROMOTION_L2_128B, CU_TENSOR_MAP_FLOAT_OOB_FILL_NONE);
  return m;
}
template <typename... KArgs, typename... Args>
static void launch(void (*kern)(KArgs...), dim3 grid, dim3 block, size_t smem, bool pdl, dim3 cluster, Args... args) {
  cudaLaunchConfig_t cfg = {};
  cfg.gridDim = grid; cfg.blockDim = block; cfg.dynamicSmemBytes = smem; cfg.stream = cudaStreamPerThread;
  cudaLaunchAttribute at[2];
  int na = 0;
  if (pdl) { at[na].id = cudaLaunchAttributeProgrammaticStreamSerialization; at[na].val.programmaticStreamSerializationAllowed = 1; na++; }
  if (cluster.x * cluster.y > 1) { at[na].id = cudaLaunchAttributeClusterDimension; at[na].val.clusterDim.x = cluster.x; at[na].val.clusterDim.y = cluster.y; at[na].val.clusterDim.z = 1; na++; }
  cfg.attrs = at; cfg.numAttrs = na;
  cudaLaunchKernelEx(&cfg, kern, KArgs(args)...);
}

extern "C" void kernel_launch(void* const* d_in, const int* in_sizes, int n_in, void* d_out, int out_size) {
  const __nv_bfloat16* x = (const __nv_bfloat16*)d_in[0];
  const __nv_bfloat16* wqkv = (const __nv_bfloat16*)d_in[1];
  const __nv_bfloat16* wo = (const __nv_bfloat16*)d_in[2];
  const __nv_bfloat16* wgate = (const __nv_bfloat16*)d_in[4];
  const __nv_bfloat16* wup = (const __nv_bfloat16*)d_in[5];
  const __nv_bfloat16* wdown = (const __nv_bfloat16*)d_in[6];
  __nv_bfloat16* out = (__nv_bfloat16*)d_out;
  void *p_o, *p_h, *p_act;
  cudaGetSymbolAddress(&p_o, g_o); cudaGetSymbolAddress(&p_h, g_h); cudaGetSymbolAddress(&p_act, g_act);

#define A_CN 1
#define A_CM 1
#define D_CN 1
#define D_CM 1
  auto kA = gemm_kernel<256, 128, 1, DM, 4, EPI_QKV, 1, A_CN, A_CM>;
  auto kC = gemm_res_kernel<DM, true>;
  auto kD = gemm_kernel<128, 192, 2, DM, 3, EPI_GLU, 1, D_CN, D_CM>;
  auto kE = gemm_res_kernel<DFF, false>;
  constexpr int smA = GemmCfg<256, 128, 1, 4>::SMEM, smC = R_SMEM, smD = GemmCfg<128, 192, 2, 3>::SMEM;
  cudaFuncSetAttribute(kA, cudaFuncAttributeMaxDynamicSharedMemorySize, smA);
  cudaFuncSetAttribute(kC, cudaFuncAttributeMaxDynamicSharedMemorySize, smC);
  cudaFuncSetAttribute(kD, cudaFuncAttributeMaxDynamicSharedMemorySize, smD);
  cudaFuncSetAttribute(kE, cudaFuncAttributeMaxDynamicSharedMemorySize, smC);
  cudaFuncSetAttribute(attn_kernel, cudaFuncAttributeMaxDynamicSharedMemorySize, ATT_SMEM);

  const CUtensorMap tm_x = make_map(x, S_LEN, DM, 256), tm_wqkv = make_map_w(wqkv, DM, 3 * DM, 64, 2);
  const CUtensorMap tm_o = make_map(p_o, S_LEN, DM, 128), tm_wo = make_map_w(wo, DM, DM, 16, 5);
  const CUtensorMap tm_h = make_map(p_h, S_LEN, DM, 128), tm_wg = make_map_w(wgate, DM, DFF, 64, 3), tm_wu = make_map_w(wup, DM, DFF, 64, 3);
  const CUtensorMap tm_act = make_map(p_act, S_LEN, DFF, 128), tm_wd = make_map_w(wdown, DFF, DM, 16, 5);

  launch(pre_kernel, dim3(12), dim3(1024), 0, false, dim3(1, 1), x, wqkv);
  launch(kA, dim3(15, 8), dim3(288), smA, true, dim3(A_CN, A_CM), tm_x, tm_wqkv, tm_wqkv, x, (__nv_bfloat16*)wqkv);
  launch(attn_kernel, dim3(132), dim3(512), ATT_SMEM, true, dim3(1, 1), 0x800000, wgate, wup, wo, wdown);
  launch(kC, dim3(8, 16), dim3(288), smC, true, dim3(1, 1), tm_o, tm_wo, x, (__nv_bfloat16*)p_h);
  launch(kD, dim3(8, 16), dim3(384), smD, true, dim3(D_CN, D_CM), tm_h, tm_wg, tm_wu, (const __nv_bfloat16*)nullptr, (__nv_bfloat16*)p_act);
  launch(kE, dim3(8, 16), dim3(288), smC, true, dim3(1, 1), tm_act, tm_wd, (const __nv_bfloat16*)p_h, out);
}
```

```cpp
#include <cuda_runtime.h>
#include <cuda_bf16.h>
#include <cuda.h>
#include <stdint.h>

constexpr int S_LEN = 2048, DM = 640, NH = 32, DH = 20, DFF = 1536;

__device__ __align__(1024) __nv_bfloat16 g_q[NH * S_LEN * 32];
__device__ __align__(1024) __nv_bfloat16 g_k[NH * S_LEN * 24];
__device__ __align__(1024) __nv_bfloat16 g_v[NH * S_LEN * 24];
__device__ __align__(1024) __nv_bfloat16 g_o[S_LEN * DM];
__device__ __align__(1024) __nv_bfloat16 g_h[S_LEN * DM];
__device__ __align__(1024) __nv_bfloat16 g_act[S_LEN * DFF];
__device__ __align__(1024) __nv_bfloat16 g_wo_t[DM * DM];
__device__ __align__(1024) __nv_bfloat16 g_wd_t[DFF * DM];
__device__ float g_kn[8 * NH * 2];
__device__ float2 g_stat1[S_LEN];
__device__ float g_cs_qkv[3 * DM];
__device__ float g_cs_g[DFF];
__device__ float g_cs_u[DFF];
__device__ unsigned int g_flag[32];
__device__ float2 g_part2[S_LEN * 10];

#define TS_BEGIN(k)
#define TS_END(k)
#define TS_MID(k, i)
__device__ __forceinline__ uint32_t smem_u32(const void* p) { return (uint32_t)__cvta_generic_to_shared(p); }
__device__ __forceinline__ void mbar_init(uint32_t bar, uint32_t cnt) { asm volatile("mbarrier.init.shared::cta.b64 [%0], %1;" :: "r"(bar), "r"(cnt)); }
__device__ __forceinline__ void mbar_expect_tx(uint32_t bar, uint32_t bytes) { asm volatile("mbarrier.arrive.expect_tx.shared::cta.b64 _, [%0], %1;" :: "r"(bar), "r"(bytes) : "memory"); }
__device__ __forceinline__ void mbar_arrive(uint32_t bar) { asm volatile("mbarrier.arrive.shared::cta.b64 _, [%0];" :: "r"(bar) : "memory"); }
__device__ __forceinline__ void mbar_wait(uint32_t bar, uint32_t parity) {
  uint32_t done;
  uint32_t spins = 0;
  do {
    asm volatile("{\n.reg .pred P1;\nmbarrier.try_wait.parity.shared::cta.b64 P1, [%1], %2;\nselp.u32 %0, 1, 0, P1;\n}" : "=r"(done) : "r"(bar), "r"(parity) : "memory");
  } while (!done && ++spins < (1u << 24));
}
__device__ __forceinline__ void bulk_g2s(uint32_t dst, const void* src, uint32_t bytes, uint32_t bar) {
  asm volatile("cp.async.bulk.shared::cluster.global.mbarrier::complete_tx::bytes [%0], [%1], %2, [%3];" :: "r"(dst), "l"(src), "r"(bytes), "r"(bar) : "memory");
}
__device__ __forceinline__ void tma_2d(uint32_t dst, const CUtensorMap* tm, int c0, int c1, uint32_t bar) {
  asm volatile("cp.async.bulk.tensor.2d.shared::cluster.global.mbarrier::complete_tx::bytes [%0], [%1, {%3, %4}], [%2];"
               :: "r"(dst), "l"(tm), "r"(bar), "r"(c0), "r"(c1) : "memory");
}
__device__ __forceinline__ void tma_3d(uint32_t dst, const CUtensorMap* tm, int c0, int c1, int c2, uint32_t bar) {
  asm volatile("cp.async.bulk.tensor.3d.shared::cluster.global.mbarrier::complete_tx::bytes [%0], [%1, {%3, %4, %5}], [%2];"
               :: "r"(dst), "l"(tm), "r"(bar), "r"(c0), "r"(c1), "r"(c2) : "memory");
}
__device__ __forceinline__ void tma_2d_mc(uint32_t dst, const CUtensorMap* tm, int c0, int c1, uint32_t bar, uint16_t mask) {
  asm volatile("cp.async.bulk.tensor.2d.shared::cluster.global.mbarrier::complete_tx::bytes.multicast::cluster [%0], [%1, {%3, %4}], [%2], %5;"
               :: "r"(dst), "l"(tm), "r"(bar), "r"(c0), "r"(c1), "h"(mask) : "memory");
}
__device__ __forceinline__ void mbar_arrive_remote(uint32_t bar, uint32_t rank) {
  asm volatile("{\n.reg .b32 ra;\nmapa.shared::cluster.u32 ra, %0, %1;\nmbarrier.arrive.release.cluster.shared::cluster.b64 _, [ra];\n}" :: "r"(bar), "r"(rank) : "memory");
}
__device__ __forceinline__ void cluster_arrive() { asm volatile("barrier.cluster.arrive.release.aligned;" ::: "memory"); }
__device__ __forceinline__ void cluster_wait() { asm volatile("barrier.cluster.wait.acquire.aligned;" ::: "memory"); }
__device__ __forceinline__ void wgmma_fence() { asm volatile("wgmma.fence.sync.aligned;" ::: "memory"); }
__device__ __forceinline__ void wgmma_commit() { asm volatile("wgmma.commit_group.sync.aligned;" ::: "memory"); }
template <int N> __device__ __forceinline__ void wgmma_wait() { asm volatile("wgmma.wait_group.sync.aligned %0;" :: "n"(N) : "memory"); }
__device__ __forceinline__ void pdl_wait() { asm volatile("griddepcontrol.wait;" ::: "memory"); }
__device__ __forceinline__ void pdl_launch() { asm volatile("griddepcontrol.launch_dependents;" ::: "memory"); }
__device__ __forceinline__ void named_bar(int id, int n) { asm volatile("bar.sync %0, %1;" :: "r"(id), "r"(n) : "memory"); }
__device__ __forceinline__ uint64_t make_desc(uint32_t addr, uint32_t lbo, uint32_t sbo, uint32_t swz) {
  return (uint64_t)((addr & 0x3FFFF) >> 4) | ((uint64_t)(lbo >> 4) << 16) | ((uint64_t)(sbo >> 4) << 32) | ((uint64_t)swz << 62);
}
__device__ __forceinline__ void st_g16(void* p, uint4 v) { asm volatile("st.global.v4.b32 [%0], {%1, %2, %3, %4};" :: "l"(p), "r"(v.x), "r"(v.y), "r"(v.z), "r"(v.w) : "memory"); }
__device__ __forceinline__ void st_g8(void* p, uint2 v) { asm volatile("st.global.v2.b32 [%0], {%1, %2};" :: "l"(p), "r"(v.x), "r"(v.y) : "memory"); }
__device__ __forceinline__ uint4 ld_g16(const void* p) { uint4 v; asm volatile("ld.global.v4.b32 {%0, %1, %2, %3}, [%4];" : "=r"(v.x), "=r"(v.y), "=r"(v.z), "=r"(v.w) : "l"(p) : "memory"); return v; }
__device__ __forceinline__ uint32_t pack_bf16(float lo, float hi) { uint32_t r; asm("cvt.rn.bf16x2.f32 %0, %1, %2;" : "=r"(r) : "f"(hi), "f"(lo)); return r; }
__device__ __forceinline__ float bf_lo(uint32_t u) { return __uint_as_float(u << 16); }
__device__ __forceinline__ float bf_hi(uint32_t u) { return __uint_as_float(u & 0xffff0000u); }
__device__ __forceinline__ float bf_round(float x) { return __bfloat162float(__float2bfloat16_rn(x)); }
__device__ __forceinline__ float ex2_mufu(float x) { float y; asm("ex2.approx.ftz.f32 %0, %1;" : "=f"(y) : "f"(x)); return y; }

__device__ __forceinline__ void wgmma_ss_n80(float (&d)[40], uint64_t da, uint64_t db, int scale_d) {
  asm volatile("{\n.reg .pred p;\nsetp.ne.b32 p, %42, 0;\n"
    "wgmma.mma_async.sync.aligned.m64n80k16.f32.bf16.bf16 {%0,%1,%2,%3,%4,%5,%6,%7,%8,%9,%10,%11,%12,%13,%14,%15,%16,%17,%18,%19,%20,%21,%22,%23,%24,%25,%26,%27,%28,%29,%30,%31,%32,%33,%34,%35,%36,%37,%38,%39}, %40, %41, p, 1, 1, 0, 1;\n}\n"
    : "+f"(d[0]),"+f"(d[1]),"+f"(d[2]),"+f"(d[3]),"+f"(d[4]),"+f"(d[5]),"+f"(d[6]),"+f"(d[7]),"+f"(d[8]),"+f"(d[9]),"+f"(d[10]),"+f"(d[11]),"+f"(d[12]),"+f"(d[13]),"+f"(d[14]),"+f"(d[15]),"+f"(d[16]),"+f"(d[17]),"+f"(d[18]),"+f"(d[19]),"+f"(d[20]),"+f"(d[21]),"+f"(d[22]),"+f"(d[23]),"+f"(d[24]),"+f"(d[25]),"+f"(d[26]),"+f"(d[27]),"+f"(d[28]),"+f"(d[29]),"+f"(d[30]),"+f"(d[31]),"+f"(d[32]),"+f"(d[33]),"+f"(d[34]),"+f"(d[35]),"+f"(d[36]),"+f"(d[37]),"+f"(d[38]),"+f"(d[39])
    : "l"(da), "l"(db), "r"(scale_d));
}
__device__ __forceinline__ void wgmma_ss_n128(float (&d)[64], uint64_t da, uint64_t db, int scale_d) {
  asm volatile("{\n.reg .pred p;\nsetp.ne.b32 p, %66, 0;\n"
    "wgmma.mma_async.sync.aligned.m64n128k16.f32.bf16.bf16 {%0,%1,%2,%3,%4,%5,%6,%7,%8,%9,%10,%11,%12,%13,%14,%15,%16,%17,%18,%19,%20,%21,%22,%23,%24,%25,%26,%27,%28,%29,%30,%31,%32,%33,%34,%35,%36,%37,%38,%39,%40,%41,%42,%43,%44,%45,%46,%47,%48,%49,%50,%51,%52,%53,%54,%55,%56,%57,%58,%59,%60,%61,%62,%63}, %64, %65, p, 1, 1, 0, 1;\n}\n"
    : "+f"(d[0]),"+f"(d[1]),"+f"(d[2]),"+f"(d[3]),"+f"(d[4]),"+f"(d[5]),"+f"(d[6]),"+f"(d[7]),"+f"(d[8]),"+f"(d[9]),"+f"(d[10]),"+f"(d[11]),"+f"(d[12]),"+f"(d[13]),"+f"(d[14]),"+f"(d[15]),"+f"(d[16]),"+f"(d[17]),"+f"(d[18]),"+f"(d[19]),"+f"(d[20]),"+f"(d[21]),"+f"(d[22]),"+f"(d[23]),"+f"(d[24]),"+f"(d[25]),"+f"(d[26]),"+f"(d[27]),"+f"(d[28]),"+f"(d[29]),"+f"(d[30]),"+f"(d[31]),"+f"(d[32]),"+f"(d[33]),"+f"(d[34]),"+f"(d[35]),"+f"(d[36]),"+f"(d[37]),"+f"(d[38]),"+f"(d[39]),"+f"(d[40]),"+f"(d[41]),"+f"(d[42]),"+f"(d[43]),"+f"(d[44]),"+f"(d[45]),"+f"(d[46]),"+f"(d[47]),"+f"(d[48]),"+f"(d[49]),"+f"(d[50]),"+f"(d[51]),"+f"(d[52]),"+f"(d[53]),"+f"(d[54]),"+f"(d[55]),"+f"(d[56]),"+f"(d[57]),"+f"(d[58]),"+f"(d[59]),"+f"(d[60]),"+f"(d[61]),"+f"(d[62]),"+f"(d[63])
    : "l"(da), "l"(db), "r"(scale_d));
}
__device__ __forceinline__ void wgmma_ss_n192(float (&d)[96], uint64_t da, uint64_t db, int scale_d) {
  asm volatile("{\n.reg .pred p;\nsetp.ne.b32 p, %98, 0;\n"
    "wgmma.mma_async.sync.aligned.m64n192k16.f32.bf16.bf16 {%0,%1,%2,%3,%4,%5,%6,%7,%8,%9,%10,%11,%12,%13,%14,%15,%16,%17,%18,%19,%20,%21,%22,%23,%24,%25,%26,%27,%28,%29,%30,%31,%32,%33,%34,%35,%36,%37,%38,%39,%40,%41,%42,%43,%44,%45,%46,%47,%48,%49,%50,%51,%52,%53,%54,%55,%56,%57,%58,%59,%60,%61,%62,%63,%64,%65,%66,%67,%68,%69,%70,%71,%72,%73,%74,%75,%76,%77,%78,%79,%80,%81,%82,%83,%84,%85,%86,%87,%88,%89,%90,%91,%92,%93,%94,%95}, %96, %97, p, 1, 1, 0, 1;\n}\n"
    : "+f"(d[0]),"+f"(d[1]),"+f"(d[2]),"+f"(d[3]),"+f"(d[4]),"+f"(d[5]),"+f"(d[6]),"+f"(d[7]),"+f"(d[8]),"+f"(d[9]),"+f"(d[10]),"+f"(d[11]),"+f"(d[12]),"+f"(d[13]),"+f"(d[14]),"+f"(d[15]),"+f"(d[16]),"+f"(d[17]),"+f"(d[18]),"+f"(d[19]),"+f"(d[20]),"+f"(d[21]),"+f"(d[22]),"+f"(d[23]),"+f"(d[24]),"+f"(d[25]),"+f"(d[26]),"+f"(d[27]),"+f"(d[28]),"+f"(d[29]),"+f"(d[30]),"+f"(d[31]),"+f"(d[32]),"+f"(d[33]),"+f"(d[34]),"+f"(d[35]),"+f"(d[36]),"+f"(d[37]),"+f"(d[38]),"+f"(d[39]),"+f"(d[40]),"+f"(d[41]),"+f"(d[42]),"+f"(d[43]),"+f"(d[44]),"+f"(d[45]),"+f"(d[46]),"+f"(d[47]),"+f"(d[48]),"+f"(d[49]),"+f"(d[50]),"+f"(d[51]),"+f"(d[52]),"+f"(d[53]),"+f"(d[54]),"+f"(d[55]),"+f"(d[56]),"+f"(d[57]),"+f"(d[58]),"+f"(d[59]),"+f"(d[60]),"+f"(d[61]),"+f"(d[62]),"+f"(d[63]),"+f"(d[64]),"+f"(d[65]),"+f"(d[66]),"+f"(d[67]),"+f"(d[68]),"+f"(d[69]),"+f"(d[70]),"+f"(d[71]),"+f"(d[72]),"+f"(d[73]),"+f"(d[74]),"+f"(d[75]),"+f"(d[76]),"+f"(d[77]),"+f"(d[78]),"+f"(d[79]),"+f"(d[80]),"+f"(d[81]),"+f"(d[82]),"+f"(d[83]),"+f"(d[84]),"+f"(d[85]),"+f"(d[86]),"+f"(d[87]),"+f"(d[88]),"+f"(d[89]),"+f"(d[90]),"+f"(d[91]),"+f"(d[92]),"+f"(d[93]),"+f"(d[94]),"+f"(d[95])
    : "l"(da), "l"(db), "r"(scale_d));
}
__device__ __forceinline__ void wgmma_ss_n64_k(float (&d)[32], uint64_t da, uint64_t db, int scale_d) {
  asm volatile("{\n.reg .pred p;\nsetp.ne.b32 p, %34, 0;\n"
    "wgmma.mma_async.sync.aligned.m64n64k16.f32.bf16.bf16 {%0,%1,%2,%3,%4,%5,%6,%7,%8,%9,%10,%11,%12,%13,%14,%15,%16,%17,%18,%19,%20,%21,%22,%23,%24,%25,%26,%27,%28,%29,%30,%31}, %32, %33, p, 1, 1, 0, 0;\n}\n"
    : "+f"(d[0]),"+f"(d[1]),"+f"(d[2]),"+f"(d[3]),"+f"(d[4]),"+f"(d[5]),"+f"(d[6]),"+f"(d[7]),"+f"(d[8]),"+f"(d[9]),"+f"(d[10]),"+f"(d[11]),"+f"(d[12]),"+f"(d[13]),"+f"(d[14]),"+f"(d[15]),"+f"(d[16]),"+f"(d[17]),"+f"(d[18]),"+f"(d[19]),"+f"(d[20]),"+f"(d[21]),"+f"(d[22]),"+f"(d[23]),"+f"(d[24]),"+f"(d[25]),"+f"(d[26]),"+f"(d[27]),"+f"(d[28]),"+f"(d[29]),"+f"(d[30]),"+f"(d[31])
    : "l"(da), "l"(db), "r"(scale_d));
}
__device__ __forceinline__ void wgmma_rs_n24_tb(float (&d)[12], uint32_t a0, uint32_t a1, uint32_t a2, uint32_t a3, uint64_t db, int scale_d) {
  asm volatile("{\n.reg .pred p;\nsetp.ne.b32 p, %17, 0;\n"
    "wgmma.mma_async.sync.aligned.m64n24k16.f32.bf16.bf16 {%0,%1,%2,%3,%4,%5,%6,%7,%8,%9,%10,%11}, {%12,%13,%14,%15}, %16, p, 1, 1, 1;\n}\n"
    : "+f"(d[0]),"+f"(d[1]),"+f"(d[2]),"+f"(d[3]),"+f"(d[4]),"+f"(d[5]),"+f"(d[6]),"+f"(d[7]),"+f"(d[8]),"+f"(d[9]),"+f"(d[10]),"+f"(d[11])
    : "r"(a0), "r"(a1), "r"(a2), "r"(a3), "l"(db), "r"(scale_d));
}

constexpr int PRE_ROW_BLOCKS = 64;
constexpr int PRE_COL_BLOCKS = 3 * DM / 64;
__device__ __forceinline__ float2 ln_finish(float mean, float var) {
  float mb = bf_round(mean);
  float s = bf_round(sqrtf(bf_round(bf_round(var) + 1e-5f)));
  return make_float2(mb, 1.0f / s);
}
__device__ __forceinline__ void colsum64(const __nv_bfloat16* __restrict__ w, int ld, int c0, float* __restrict__ dst, float (*red)[65], int tid, int bar_id) {
  const int cg = tid & 7, r0 = tid >> 3;
  float acc[8];
#pragma unroll
  for (int i = 0; i < 8; i++) acc[i] = 0.f;
#pragma unroll 10
  for (int r = r0; r < DM; r += 32) {
    uint4 v = __ldg((const uint4*)(w + (size_t)r * ld + c0 + cg * 8));
    acc[0] += bf_lo(v.x); acc[1] += bf_hi(v.x); acc[2] += bf_lo(v.y); acc[3] += bf_hi(v.y);
    acc[4] += bf_lo(v.z); acc[5] += bf_hi(v.z); acc[6] += bf_lo(v.w); acc[7] += bf_hi(v.w);
  }
#pragma unroll
  for (int i = 0; i < 8; i++) red[r0][cg * 8 + i] = acc[i];
  named_bar(bar_id, 256);
  if (tid < 64) {
    float s = 0.f;
#pragma unroll
    for (int r = 0; r < 32; r++) s += red[r][tid];
    dst[c0 + tid] = s;
  }
  named_bar(bar_id, 256);
}
__global__ void __launch_bounds__(1024) pre_kernel(const __nv_bfloat16* __restrict__ x, const __nv_bfloat16* __restrict__ wqkv) {
  TS_BEGIN(0);
  pdl_launch();
  __shared__ float red[51][161];
  const int tid = threadIdx.x, lane = tid & 31, warp = tid >> 5;
  {
    const int ch = tid % 20, rl = tid / 20;
    if (rl < 51) {
      const __nv_bfloat16* w = wqkv + blockIdx.x * 160 + ch * 8;
      uint4 v[13];
#pragma unroll
      for (int i = 0; i < 13; i++) { const int r = rl + i * 51; v[i] = r < DM ? __ldg((const uint4*)(w + (size_t)r * (3 * DM))) : make_uint4(0, 0, 0, 0); }
      float acc[8];
#pragma unroll
      for (int i = 0; i < 8; i++) acc[i] = 0.f;
#pragma unroll
      for (int i = 0; i < 13; i++) {
        acc[0] += bf_lo(v[i].x); acc[1] += bf_hi(v[i].x); acc[2] += bf_lo(v[i].y); acc[3] += bf_hi(v[i].y);
        acc[4] += bf_lo(v[i].z); acc[5] += bf_hi(v[i].z); acc[6] += bf_lo(v[i].w); acc[7] += bf_hi(v[i].w);
      }
#pragma unroll
      for (int i = 0; i < 8; i++) red[rl][ch * 8 + i] = acc[i];
    }
  }
  const int rbeg = blockIdx.x * 171, rend = min(rbeg + 171, S_LEN);
  for (int row0 = rbeg + warp * 2; row0 < rend; row0 += 64) {
    uint4 v[2][3];
#pragma unroll
    for (int k = 0; k < 2; k++) {
      const int row = min(row0 + k, rend - 1);
      const uint4* p = (const uint4*)(x + (size_t)row * DM);
      v[k][0] = __ldg(p + lane); v[k][1] = __ldg(p + 32 + lane);
      v[k][2] = lane < 16 ? __ldg(p + 64 + lane) : make_uint4(0, 0, 0, 0);
    }
#pragma unroll
    for (int k = 0; k < 2; k++) {
      float f[24];
      const uint32_t u[12] = {v[k][0].x, v[k][0].y, v[k][0].z, v[k][0].w, v[k][1].x, v[k][1].y, v[k][1].z, v[k][1].w, v[k][2].x, v[k][2].y, v[k][2].z, v[k][2].w};
#pragma unroll
      for (int j = 0; j < 12; j++) { f[2 * j] = bf_lo(u[j]); f[2 * j + 1] = bf_hi(u[j]); }
      float s = 0.f;
#pragma unroll
      for (int j = 0; j < 24; j++) s += f[j];
#pragma unroll
      for (int o = 16; o; o >>= 1) s += __shfl_xor_sync(~0u, s, o);
      const float mean = s * (1.0f / DM);
      float q = 0.f;
#pragma unroll
      for (int j = 0; j < 16; j++) { const float d = f[j] - mean; q += d * d; }
      if (lane < 16) {
#pragma unroll
        for (int j = 16; j < 24; j++) { const float d = f[j] - mean; q += d * d; }
      }
#pragma unroll
      for (int o = 16; o; o >>= 1) q += __shfl_xor_sync(~0u, q, o);
      if (lane == 0 && row0 + k < rend) g_stat1[row0 + k] = ln_finish(mean, q * (1.0f / DM));
    }
  }
  __syncthreads();
  if (tid < 160) {
    float s = 0.f;
#pragma unroll 17
    for (int r = 0; r < 51; r++) s += red[r][tid];
    g_cs_qkv[blockIdx.x * 160 + tid] = s;
  }
  TS_END(0);
}

enum { EPI_QKV = 0, EPI_WO = 1, EPI_GLU = 2, EPI_DOWN = 3 };
template <int N> struct WG;
template <> struct WG<128> { static __device__ __forceinline__ void mma(float (&d)[64], uint64_t a, uint64_t b, int s) { wgmma_ss_n128(d, a, b, s); } };
template <> struct WG<192> { static __device__ __forceinline__ void mma(float (&d)[96], uint64_t a, uint64_t b, int s) { wgmma_ss_n192(d, a, b, s); } };

template <int BM, int BN, int NB, int STAGES> struct GemmCfg {
  static constexpr int A_BYTES = BM * 128;
  static constexpr int B_BYTES = NB * (BN / 64) * 8192;
  static constexpr int STAGE_BYTES = A_BYTES + B_BYTES;
  static constexpr int SMEM = STAGES * STAGE_BYTES + 1024   + 256   + 4096  ;
};

constexpr float QSCALE = 0.22360679774997896f * 1.4426950408889634f;

template <int BM, int BN, int NB, int KDIM, int STAGES, int EPI, int MINB, int CN, int CM>
__global__ void __launch_bounds__(EPI == EPI_GLU ? 384 : 288, MINB) gemm_kernel(const __grid_constant__ CUtensorMap tmA, const __grid_constant__ CUtensorMap tmB0,
                                                         const __grid_constant__ CUtensorMap tmB1,
                                                         const __nv_bfloat16* resid, __nv_bfloat16* out) {
  using Cfg = GemmCfg<BM, BN, NB, STAGES>;
  constexpr int MB = BM / 128;
  constexpr int KT = KDIM / 64;
  extern __shared__ uint8_t smem_raw[];
  const uint32_t sbase = (smem_u32(smem_raw) + 1023u) & ~1023u;
  uint8_t* sptr = smem_raw + (sbase - smem_u32(smem_raw));
  const uint32_t sbar = sbase + STAGES * Cfg::STAGE_BYTES;
  const int tid = threadIdx.x, warp = tid >> 5, lane = tid & 31;
  const int n0 = blockIdx.x * BN, m0 = blockIdx.y * BM;
  TS_BEGIN(EPI == EPI_QKV ? 1 : EPI + 2);
  TS_MID(EPI == EPI_QKV ? 1 : EPI + 2, 3);
  constexpr int NCL = CN + CM - 1;
  const int cx = blockIdx.x % CN, cy = blockIdx.y % CM;
  if (tid == 0) {
    for (int i = 0; i < STAGES; i++) { mbar_init(sbar + 8 * i, 1); mbar_init(sbar + 8 * (STAGES + i), 2 * NCL); }
    asm volatile("fence.mbarrier_init.release.cluster;" ::: "memory");
  }
  __syncthreads();
  if constexpr (CN * CM > 1) { cluster_arrive(); cluster_wait(); }
  pdl_launch();
  if (warp >= 8) {
    if constexpr (EPI == EPI_GLU) asm volatile("setmaxnreg.dec.sync.aligned.u32 40;");
    if (warp == 8 && lane == 0) {
      auto load_a = [&](int kt, int s) { tma_2d(sbase + s * Cfg::STAGE_BYTES, &tmA, kt * 64, m0, sbar + 8 * s); };
      auto load_b = [&](int kt, int s) {
        const uint32_t sb = sbase + s * Cfg::STAGE_BYTES + Cfg::A_BYTES;
        tma_3d(sb, &tmB0, 0, kt * 64, blockIdx.x * (BN / 64), sbar + 8 * s);
        if constexpr (NB == 2) tma_3d(sb + (BN / 64) * 8192, &tmB1, 0, kt * 64, blockIdx.x * (BN / 64), sbar + 8 * s);
      };
      if constexpr (EPI == EPI_QKV) {
        const int cta = blockIdx.y * gridDim.x + blockIdx.x;
        const uint32_t xb = S_LEN * DM * 2, xs = 21888;
        if (cta * xs < xb) asm volatile("cp.async.bulk.prefetch.L2.global [%0], %1;" :: "l"((const uint8_t*)resid + (size_t)cta * xs), "r"(min(xs, xb - cta * xs)));
        asm volatile("cp.async.bulk.prefetch.L2.global [%0], %1;" :: "l"((const uint8_t*)out + (size_t)cta * 20480), "r"(20480));
      }
      for (int s = 0; s < STAGES; s++) { mbar_expect_tx(sbar + 8 * s, Cfg::STAGE_BYTES); if (EPI != EPI_QKV || s == 0) load_b(s, s); }
      if (EPI != EPI_QKV) pdl_wait();
      for (int s = 0; s < STAGES; s++) { load_a(s, s); if (EPI == EPI_QKV && s > 0) load_b(s, s); }
      for (int kt = STAGES; kt < KT; kt++) {
        const int s = kt % STAGES;
        mbar_wait(sbar + 8 * (STAGES + s), ((kt / STAGES) - 1) & 1);
        mbar_expect_tx(sbar + 8 * s, Cfg::STAGE_BYTES);
        load_a(kt, s);
        load_b(kt, s);
      }
    }
    if constexpr (EPI == EPI_GLU) {
      if (warp > 8) {
        float2* s_st = (float2*)(sptr + STAGES * Cfg::STAGE_BYTES + 256);
        float* s_cs = (float*)(sptr + STAGES * Cfg::STAGE_BYTES + 256 + 1024);
        pdl_wait();
        for (int r = tid - 288; r < BM; r += 96) {
          const float2* pp = &g_part2[(m0 + r) * 8];
          float s = 0.f;
#pragma unroll
          for (int i = 0; i < 8; i++) s += pp[i].x;
          const float mean = s * (1.0f / DM);
          float q = 0.f;
#pragma unroll
          for (int i = 0; i < 8; i++) { const float2 p = pp[i]; const float d = p.x * (1.0f / 80.f) - mean; q += p.y + 80.f * d * d; }
          s_st[r] = ln_finish(mean, q * (1.0f / DM));
        }
        for (int c = tid - 288; c < BN; c += 96) { s_cs[c] = g_cs_g[n0 + c]; s_cs[BN + c] = g_cs_u[n0 + c]; }
        __threadfence_block();
        asm volatile("bar.arrive 2, 352;" ::: "memory");
      }
    }
    if constexpr (CN * CM > 1) { __syncwarp(); cluster_arrive(); cluster_wait(); }
    return;
  }
  if constexpr (EPI == EPI_GLU) asm volatile("setmaxnreg.inc.sync.aligned.u32 232;");
  const int wg = warp >> 2, g = lane >> 2, t = lane & 3;
  float acc[MB][NB][BN / 2];
#pragma unroll
  for (int mb = 0; mb < MB; mb++)
#pragma unroll
    for (int nb = 0; nb < NB; nb++)
#pragma unroll
      for (int i = 0; i < BN / 2; i++) acc[mb][nb][i] = 0.f;
  for (int kt = 0; kt < KT; kt++) {
    const int s = kt % STAGES;
    mbar_wait(sbar + 8 * s, (kt / STAGES) & 1);
    if (kt == 0) TS_MID(EPI == EPI_QKV ? 1 : EPI + 2, 0);
    const uint32_t sa = sbase + s * Cfg::STAGE_BYTES + wg * (MB * 64 * 128);
    const uint32_t sb = sbase + s * Cfg::STAGE_BYTES + Cfg::A_BYTES;
    wgmma_fence();
#pragma unroll
    for (int ks = 0; ks < 4; ks++) {
#pragma unroll
      for (int mb = 0; mb < MB; mb++) {
        const uint64_t da = make_desc(sa + mb * 8192 + ks * 32, 16, 1024, 1);
#pragma unroll
        for (int nb = 0; nb < NB; nb++) {
          const uint64_t db = make_desc(sb + nb * (BN / 64) * 8192 + ks * 2048, 8192, 1024, 1);
          WG<BN>::mma(acc[mb][nb], da, db, 1);
        }
      }
    }
    wgmma_commit();
    wgmma_wait<1>();
    if (kt > 0 && kt - 1 + STAGES < KT && (tid & 127) < NCL) {
      const uint32_t eb = sbar + 8 * (STAGES + (kt - 1) % STAGES);
      if constexpr (CN * CM > 1) {
        const int i = tid & 127;
        const uint32_t rank = i < CN ? cy * CN + i : ((i - CN + (i - CN >= cy ? 1 : 0)) * CN + cx);
        mbar_arrive_remote(eb, rank);
      } else mbar_arrive(eb);
    }
  }
  wgmma_wait<0>();
#pragma unroll
  for (int mb = 0; mb < MB; mb++)
#pragma unroll
    for (int nb = 0; nb < NB; nb++)
#pragma unroll
      for (int i = 0; i < BN / 2; i++) asm volatile("" : "+f"(acc[mb][nb][i]) :: "memory");
  if constexpr (CN * CM > 1) cluster_arrive();
  TS_MID(EPI == EPI_QKV ? 1 : EPI + 2, 1);
  pdl_wait();
  TS_MID(EPI == EPI_QKV ? 1 : EPI + 2, 2);
  named_bar(1, 256);
  constexpr int LDS = BN * 2 + 16;
  const int ctid = tid;

  if constexpr (EPI == EPI_QKV) {
    const int sec = n0 / DM;
    constexpr int lds = 264;
    __shared__ unsigned int s_kn[8];
    if (ctid < 8) s_kn[ctid] = 0u;
    if (blockIdx.x == 0 && blockIdx.y == 0 && ctid < 32) g_flag[ctid] = 0u;
    float2 cs[BN / 8];
#pragma unroll
    for (int j = 0; j < BN / 8; j++) cs[j] = *(const float2*)&g_cs_qkv[n0 + j * 8 + 2 * t];
#pragma unroll
    for (int mb = 0; mb < MB; mb++) {
      const int r0 = wg * (MB * 64) + mb * 64 + (warp & 3) * 16 + g;
      const float2 st0 = g_stat1[m0 + r0], st1 = g_stat1[m0 + r0 + 8];
      const float sc0 = sec == 0 ? st0.y * QSCALE : st0.y, sc1 = sec == 0 ? st1.y * QSCALE : st1.y;
#pragma unroll
      for (int j = 0; j < BN / 8; j++) {
        const float* a = &acc[mb][0][4 * j];
        *(uint32_t*)(sptr + r0 * lds + j * 16 + t * 4) = pack_bf16(fmaf(-st0.x, cs[j].x, a[0]) * sc0, fmaf(-st0.x, cs[j].y, a[1]) * sc0);
        *(uint32_t*)(sptr + (r0 + 8) * lds + j * 16 + t * 4) = pack_bf16(fmaf(-st1.x, cs[j].x, a[2]) * sc1, fmaf(-st1.x, cs[j].y, a[3]) * sc1);
      }
    }
    named_bar(1, 256);
    {
      const int cbase = n0 - sec * DM;
      const int hfirst = cbase / DH;
      const int j = m0 + ctid;
      uint8_t* dst = (uint8_t*)(sec == 0 ? g_q : (sec == 1 ? g_k : g_v)) + (size_t)(j >> 3) * (sec == 0 ? 512 : 384) + (j & 7) * 16;
      const uint8_t* row = sptr + ctid * 264;
#pragma unroll
      for (int i = 0; i < 8; i++) {
        const int hh = hfirst + i;
        const int cr = hh * DH - cbase;
        if (cr < BN) {
          uint2 v[5];
          bool in[5];
          float s = 0.f;
#pragma unroll
          for (int qd = 0; qd < 5; qd++) {
            const int c = cr + 4 * qd;
            in[qd] = c >= 0 && c < BN;
            v[qd] = in[qd] ? *(const uint2*)(row + c * 2) : make_uint2(0u, 0u);
            s += bf_lo(v[qd].x) * bf_lo(v[qd].x) + bf_hi(v[qd].x) * bf_hi(v[qd].x) + bf_lo(v[qd].y) * bf_lo(v[qd].y) + bf_hi(v[qd].y) * bf_hi(v[qd].y);
          }
          uint8_t* p = dst + (size_t)hh * (sec == 0 ? S_LEN * 64 : S_LEN * 48);
          if (in[0] && in[1]) st_g16(p, make_uint4(v[0].x, v[0].y, v[1].x, v[1].y));
          else if (in[0]) st_g8(p, v[0]);
          else if (in[1]) st_g8(p + 8, v[1]);
          if (in[2] && in[3]) st_g16(p + 128, make_uint4(v[2].x, v[2].y, v[3].x, v[3].y));
          else if (in[2]) st_g8(p + 128, v[2]);
          else if (in[3]) st_g8(p + 136, v[3]);
          if (in[4]) {
            st_g16(p + 256, make_uint4(v[4].x, v[4].y, sec == 0 ? 0u : 0x00003f80u, 0u));
            if (sec == 0) st_g16(p + 384, make_uint4(0u, 0u, 0u, 0u));
          }
          if (sec == 1) {
            const unsigned int mxb = __reduce_max_sync(~0u, __float_as_uint(s) & 0x7fffffffu);
            if (lane == 0) atomicMax(&s_kn[i], mxb);
          }
        }
      }
      if (sec == 1) {
        named_bar(1, 256);
        const int hh = hfirst + ctid;
        if (ctid < 8 && hh * DH < cbase + BN) {
          const bool starts_here = hh * DH >= cbase, ends_here = hh * DH + DH <= cbase + BN;
          const float v = __uint_as_float(s_kn[ctid]);
          float* o = &g_kn[(blockIdx.y * NH + hh) * 2];
          if (starts_here) { o[0] = v; if (ends_here) o[1] = 0.f; }
          else o[1] = v;
        }
      }
    }
  } else if constexpr (EPI == EPI_WO || EPI == EPI_DOWN) {
    const int r0 = wg * 64 + (warp & 3) * 16 + g;
#pragma unroll
    for (int j = 0; j < BN / 8; j++) {
      const float* a = &acc[0][0][4 * j];
      *(uint32_t*)(sptr + r0 * LDS + j * 16 + t * 4) = pack_bf16(a[0], a[1]);
      *(uint32_t*)(sptr + (r0 + 8) * LDS + j * 16 + t * 4) = pack_bf16(a[2], a[3]);
    }
    named_bar(1, 256);
#pragma unroll
    for (int i = 0; i < BM * (BN / 8) / 256; i++) {
      const int idx = i * 256 + ctid, r = idx / (BN / 8), c = idx % (BN / 8);
      const uint4 a = *(const uint4*)(sptr + r * LDS + c * 16);
      const size_t go = (size_t)(m0 + r) * DM + n0 + c * 8;
      const uint4 b = ld_g16(resid + go);
      uint4 o;
      o.x = pack_bf16(bf_lo(a.x) + bf_lo(b.x), bf_hi(a.x) + bf_hi(b.x));
      o.y = pack_bf16(bf_lo(a.y) + bf_lo(b.y), bf_hi(a.y) + bf_hi(b.y));
      o.z = pack_bf16(bf_lo(a.z) + bf_lo(b.z), bf_hi(a.z) + bf_hi(b.z));
      o.w = pack_bf16(bf_lo(a.w) + bf_lo(b.w), bf_hi(a.w) + bf_hi(b.w));
      st_g16(out + go, o);
      if constexpr (EPI == EPI_WO) {
        static_assert(BN == 64, "stats assume 8 lanes per row");
        const float f[8] = {bf_lo(o.x), bf_hi(o.x), bf_lo(o.y), bf_hi(o.y), bf_lo(o.z), bf_hi(o.z), bf_lo(o.w), bf_hi(o.w)};
        float s = 0.f;
#pragma unroll
        for (int k = 0; k < 8; k++) s += f[k];
        s += __shfl_xor_sync(~0u, s, 1); s += __shfl_xor_sync(~0u, s, 2); s += __shfl_xor_sync(~0u, s, 4);
        const float mu = s * (1.0f / 64.f);
        float q = 0.f;
#pragma unroll
        for (int k = 0; k < 8; k++) { const float d = f[k] - mu; q += d * d; }
        q += __shfl_xor_sync(~0u, q, 1); q += __shfl_xor_sync(~0u, q, 2); q += __shfl_xor_sync(~0u, q, 4);
        if (c == 0) g_part2[(m0 + r) * 10 + blockIdx.x] = make_float2(s, q);
      }
    }
  } else {
    const int r0 = wg * 64 + (warp & 3) * 16 + g;
    const float2* s_st = (const float2*)(sptr + STAGES * Cfg::STAGE_BYTES + 256);
    const float* s_cs = (const float*)(sptr + STAGES * Cfg::STAGE_BYTES + 256 + 1024);
    named_bar(2, 352);
    float2 st[2] = {s_st[r0], s_st[r0 + 8]};
#pragma unroll
    for (int j = 0; j < BN / 8; j++) {
      const float2 cg = *(const float2*)&s_cs[j * 8 + 2 * t], cu = *(const float2*)&s_cs[BN + j * 8 + 2 * t];
      const float* a = &acc[0][0][4 * j];
      const float* b = &acc[0][1][4 * j];
#pragma unroll
      for (int e = 0; e < 2; e++) {
        const float2 s_ = st[e];
        const uint32_t gp = pack_bf16(fmaf(-s_.x, cg.x, a[2 * e]) * s_.y, fmaf(-s_.x, cg.y, a[2 * e + 1]) * s_.y);
        const uint32_t up = pack_bf16(fmaf(-s_.x, cu.x, b[2 * e]) * s_.y, fmaf(-s_.x, cu.y, b[2 * e + 1]) * s_.y);
        uint32_t r;
        asm("{\n.reg .b32 z;\nmax.bf16x2 z, %1, %3;\nmul.rn.bf16x2 %0, z, %2;\n}" : "=r"(r) : "r"(gp), "r"(up), "r"(0u));
        *(uint32_t*)(sptr + (r0 + 8 * e) * LDS + j * 16 + t * 4) = r;
      }
    }
    named_bar(1, 256);
#pragma unroll
    for (int i = 0; i < BM * (BN / 8) / 256; i++) {
      const int idx = i * 256 + ctid, r = idx / (BN / 8), c = idx % (BN / 8);
      st_g16(out + (size_t)(m0 + r) * DFF + n0 + c * 8, *(const uint4*)(sptr + r * LDS + c * 16));
    }
  }
  if constexpr (CN * CM > 1) cluster_wait();
  TS_END(EPI == EPI_QKV ? 1 : EPI + 2);
}

constexpr int R_STAGES = 8;
constexpr int R_STAGE_BYTES = 16384 + 5 * 2048;
constexpr int R_BAR_OFF = R_STAGES * R_STAGE_BYTES;
constexpr int R_SMEM = R_BAR_OFF + 256 + 1024;
template <int KDIM, bool STATS>
__global__ void __launch_bounds__(288, 1) gemm_res_kernel(const __grid_constant__ CUtensorMap tmA, const __grid_constant__ CUtensorMap tmB,
                                                          const __nv_bfloat16* resid, __nv_bfloat16* out) {
  constexpr int KT = KDIM / 64;
  extern __shared__ uint8_t smem_raw[];
  const uint32_t sbase = (smem_u32(smem_raw) + 1023u) & ~1023u;
  uint8_t* sptr = smem_raw + (sbase - smem_u32(smem_raw));
  const uint32_t sbar = sbase + R_BAR_OFF;
  const int tid = threadIdx.x, warp = tid >> 5, lane = tid & 31;
  const int n0 = blockIdx.x * 80, m0 = blockIdx.y * 128;
  TS_BEGIN(STATS ? 3 : 5);
  if (tid == 0) {
    for (int i = 0; i < R_STAGES; i++) { mbar_init(sbar + 8 * i, 1); mbar_init(sbar + 8 * (R_STAGES + i), 2); }
    asm volatile("fence.mbarrier_init.release.cluster;" ::: "memory");
  }
  __syncthreads();
  pdl_launch();
  if (warp == 8) {
    if (lane == 0) {
      const uint8_t* wt = (const uint8_t*)(STATS ? g_wo_t : g_wd_t) + (size_t)blockIdx.x * KT * 10240;
      auto load_b = [&](int kt, int s) { bulk_g2s(sbase + s * R_STAGE_BYTES + 16384, wt + kt * 10240, 10240, sbar + 8 * s); };
      pdl_wait();
      for (int s = 0; s < R_STAGES; s++) { mbar_expect_tx(sbar + 8 * s, R_STAGE_BYTES); tma_2d(sbase + s * R_STAGE_BYTES, &tmA, s * 64, m0, sbar + 8 * s); load_b(s, s); }
      for (int kt = R_STAGES; kt < KT; kt++) {
        const int s = kt % R_STAGES;
        mbar_wait(sbar + 8 * (R_STAGES + s), ((kt / R_STAGES) - 1) & 1);
        mbar_expect_tx(sbar + 8 * s, R_STAGE_BYTES);
        tma_2d(sbase + s * R_STAGE_BYTES, &tmA, kt * 64, m0, sbar + 8 * s);
        load_b(kt, s);
      }
    }
    return;
  }
  const int wg = warp >> 2, g = lane >> 2, t = lane & 3;
  pdl_wait();
  uint4 rv[5];
#pragma unroll
  for (int i = 0; i < 5; i++) {
    const int idx = i * 256 + tid, r = idx / 10, c = idx % 10;
    rv[i] = ld_g16(resid + (size_t)(m0 + r) * DM + n0 + c * 8);
  }
  float acc[40];
#pragma unroll
  for (int i = 0; i < 40; i++) acc[i] = 0.f;
  for (int kt = 0; kt < KT; kt++) {
    const int s = kt % R_STAGES;
    mbar_wait(sbar + 8 * s, (kt / R_STAGES) & 1);
    if (kt == 0) TS_MID(STATS ? 3 : 5, 0);
    const uint32_t sa = sbase + s * R_STAGE_BYTES + wg * 8192;
    const uint32_t sb = sbase + s * R_STAGE_BYTES + 16384;
    wgmma_fence();
#pragma unroll
    for (int ks = 0; ks < 4; ks++)
      wgmma_ss_n80(acc, make_desc(sa + ks * 32, 16, 1024, 1), make_desc(sb + ks * 512, 2048, 256, 3), 1);
    wgmma_commit();
    wgmma_wait<1>();
    if (kt > 0 && kt - 1 + R_STAGES < KT && (tid & 127) == 0) mbar_arrive(sbar + 8 * (R_STAGES + (kt - 1) % R_STAGES));
  }
  wgmma_wait<0>();
#pragma unroll
  for (int i = 0; i < 40; i++) asm volatile("" : "+f"(acc[i]) :: "memory");
  TS_MID(STATS ? 3 : 5, 1);
  named_bar(1, 256);
  constexpr int LDS = 176;
  const int r0 = wg * 64 + (warp & 3) * 16 + g;
#pragma unroll
  for (int i = 0; i < 10; i++) {
    *(uint32_t*)(sptr + r0 * LDS + i * 16 + t * 4) = pack_bf16(acc[4 * i], acc[4 * i + 1]);
    *(uint32_t*)(sptr + (r0 + 8) * LDS + i * 16 + t * 4) = pack_bf16(acc[4 * i + 2], acc[4 * i + 3]);
  }
  named_bar(1, 256);
  TS_MID(STATS ? 3 : 5, 2);
#pragma unroll
  for (int i = 0; i < 5; i++) {
    const int idx = i * 256 + tid, r = idx / 10, c = idx % 10;
    const uint4 a = *(const uint4*)(sptr + r * LDS + c * 16);
    const uint4 b = rv[i];
    uint4 o;
    o.x = pack_bf16(bf_lo(a.x) + bf_lo(b.x), bf_hi(a.x) + bf_hi(b.x));
    o.y = pack_bf16(bf_lo(a.y) + bf_lo(b.y), bf_hi(a.y) + bf_hi(b.y));
    o.z = pack_bf16(bf_lo(a.z) + bf_lo(b.z), bf_hi(a.z) + bf_hi(b.z));
    o.w = pack_bf16(bf_lo(a.w) + bf_lo(b.w), bf_hi(a.w) + bf_hi(b.w));
    st_g16(out + (size_t)(m0 + r) * DM + n0 + c * 8, o);
    if constexpr (STATS) *(uint4*)(sptr + r * LDS + c * 16) = o;
  }
  TS_MID(STATS ? 3 : 5, 3);
  if constexpr (STATS) {
    named_bar(1, 256);
    const int r = tid >> 1, hf = tid & 1;
    float f[40];
#pragma unroll
    for (int i = 0; i < 5; i++) {
      const uint4 v = *(const uint4*)(sptr + r * LDS + hf * 80 + i * 16);
      f[8 * i] = bf_lo(v.x); f[8 * i + 1] = bf_hi(v.x); f[8 * i + 2] = bf_lo(v.y); f[8 * i + 3] = bf_hi(v.y);
      f[8 * i + 4] = bf_lo(v.z); f[8 * i + 5] = bf_hi(v.z); f[8 * i + 6] = bf_lo(v.w); f[8 * i + 7] = bf_hi(v.w);
    }
    float s = 0.f;
#pragma unroll
    for (int i = 0; i < 40; i++) s += f[i];
    s += __shfl_xor_sync(~0u, s, 1);
    const float mu = s * (1.0f / 80.f);
    float q = 0.f;
#pragma unroll
    for (int i = 0; i < 40; i++) { const float d = f[i] - mu; q += d * d; }
    q += __shfl_xor_sync(~0u, q, 1);
    if (hf == 0) g_part2[(m0 + r) * 8 + blockIdx.x] = make_float2(s, q);
  }
  TS_END(STATS ? 3 : 5);
}

#define F_MC 0
constexpr int F_CST = 7, F_DST = 3, F_EST = 5;
constexpr int F_RS = 16384 + 5 * 2048;
constexpr int F_DS = 16384 + 6 * 8192;
constexpr int F_E_OFF = 53248;
constexpr int F_STG_OFF = F_DST * F_DS;
constexpr int F_BAR_OFF = F_STG_OFF + 128 * 176;
constexpr int F_VEC_OFF = F_BAR_OFF + 256;
constexpr int F_SMEM = F_VEC_OFF + 1024 + 1536 + 1024;

__device__ __forceinline__ void flag_wait(const unsigned int* f, unsigned int target) {
  unsigned int v, spins = 0;
  do { asm volatile("ld.acquire.gpu.global.u32 %0, [%1];" : "=r"(v) : "l"(f) : "memory"); } while (v < target && ++spins < (1u << 22));
  asm volatile("fence.proxy.async;" ::: "memory");
}
__device__ __forceinline__ void flag_signal(unsigned int* f) {
  asm volatile("fence.proxy.async;" ::: "memory");
  asm volatile("red.release.gpu.global.add.u32 [%0], 1;" :: "l"(f) : "memory");
}

template <bool STATS>
__device__ __forceinline__ void res_epilogue(float (&acc)[40], const uint4 (&rv)[5], uint8_t* stg, __nv_bfloat16* out, int m0, int n0, int tid, int bx) {
  constexpr int LDS = 176;
  const int warp = tid >> 5, lane = tid & 31;
  const int r0 = (warp >> 2) * 64 + (warp & 3) * 16 + (lane >> 2), t = lane & 3;
#pragma unroll
  for (int i = 0; i < 10; i++) {
    *(uint32_t*)(stg + r0 * LDS + i * 16 + t * 4) = pack_bf16(acc[4 * i], acc[4 * i + 1]);
    *(uint32_t*)(stg + (r0 + 8) * LDS + i * 16 + t * 4) = pack_bf16(acc[4 * i + 2], acc[4 * i + 3]);
  }
  named_bar(1, 256);
#pragma unroll
  for (int i = 0; i < 5; i++) {
    const int idx = i * 256 + tid, r = idx / 10, c = idx % 10;
    const uint4 a = *(const uint4*)(stg + r * LDS + c * 16);
    const uint4 b = rv[i];
    uint4 o;
    o.x = pack_bf16(bf_lo(a.x) + bf_lo(b.x), bf_hi(a.x) + bf_hi(b.x));
    o.y = pack_bf16(bf_lo(a.y) + bf_lo(b.y), bf_hi(a.y) + bf_hi(b.y));
    o.z = pack_bf16(bf_lo(a.z) + bf_lo(b.z), bf_hi(a.z) + bf_hi(b.z));
    o.w = pack_bf16(bf_lo(a.w) + bf_lo(b.w), bf_hi(a.w) + bf_hi(b.w));
    st_g16(out + (size_t)(m0 + r) * DM + n0 + c * 8, o);
    if constexpr (STATS) *(uint4*)(stg + r * LDS + c * 16) = o;
  }
  if constexpr (STATS) {
    named_bar(1, 256);
    const int r = tid >> 1, hf = tid & 1;
    float f[40];
#pragma unroll
    for (int i = 0; i < 5; i++) {
      const uint4 v = *(const uint4*)(stg + r * LDS + hf * 80 + i * 16);
      f[8 * i] = bf_lo(v.x); f[8 * i + 1] = bf_hi(v.x); f[8 * i + 2] = bf_lo(v.y); f[8 * i + 3] = bf_hi(v.y);
      f[8 * i + 4] = bf_lo(v.z); f[8 * i + 5] = bf_hi(v.z); f[8 * i + 6] = bf_lo(v.w); f[8 * i + 7] = bf_hi(v.w);
    }
    float s = 0.f;
#pragma unroll
    for (int i = 0; i < 40; i++) s += f[i];
    s += __shfl_xor_sync(~0u, s, 1);
    const float mu = s * (1.0f / 80.f);
    float q = 0.f;
#pragma unroll
    for (int i = 0; i < 40; i++) { const float d = f[i] - mu; q += d * d; }
    q += __shfl_xor_sync(~0u, q, 1);
    if (hf == 0) g_part2[(m0 + r) * 8 + bx] = make_float2(s, q);
  }
}

__global__ void __launch_bounds__(384, 1) post_kernel(const __grid_constant__ CUtensorMap tmO, const __grid_constant__ CUtensorMap tmWo,
                                                      const __grid_constant__ CUtensorMap tmH, const __grid_constant__ CUtensorMap tmWg,
                                                      const __grid_constant__ CUtensorMap tmWu, const __grid_constant__ CUtensorMap tmAct,
                                                      const __grid_constant__ CUtensorMap tmWd, const __nv_bfloat16* x, __nv_bfloat16* out) {
  extern __shared__ uint8_t smem_raw[];
  const uint32_t sbase = (smem_u32(smem_raw) + 1023u) & ~1023u;
  uint8_t* sptr = smem_raw + (sbase - smem_u32(smem_raw));
  const uint32_t bC = sbase + F_BAR_OFF, bD = bC + 16 * F_CST, bE = bD + 16 * F_DST;
  const int tid = threadIdx.x, warp = tid >> 5, lane = tid & 31;
  const int bx = blockIdx.x, rb = blockIdx.y, m0 = rb * 128, cx = bx & 1;
  TS_BEGIN(3);
  if (tid == 0) {
    for (int i = 0; i < F_CST; i++) { mbar_init(bC + 8 * i, 1); mbar_init(bC + 8 * (F_CST + i), F_MC ? 4 : 2); }
    for (int i = 0; i < F_DST; i++) { mbar_init(bD + 8 * i, 1); mbar_init(bD + 8 * (F_DST + i), F_MC ? 4 : 2); }
    for (int i = 0; i < F_EST; i++) { mbar_init(bE + 8 * i, 1); mbar_init(bE + 8 * (F_EST + i), F_MC ? 4 : 2); }
    asm volatile("fence.mbarrier_init.release.cluster;" ::: "memory");
  }
  __syncthreads();
  if (F_MC) { cluster_arrive(); cluster_wait(); }
  if (warp >= 8) {
    asm volatile("setmaxnreg.dec.sync.aligned.u32 40;");
    if (warp == 8) {
      if (lane == 0) {
        auto load_a = [&](const CUtensorMap* tm, uint32_t stage, int kt, uint32_t bar) {
          if (F_MC) tma_2d_mc(stage + cx * 8192, tm, kt * 64, m0 + cx * 64, bar, (uint16_t)3); else tma_2d(stage, tm, kt * 64, m0, bar);
        };
        for (int s = 0; s < F_CST; s++) { mbar_expect_tx(bC + 8 * s, F_RS); if (s < 3) tma_3d(sbase + s * F_RS + 16384, &tmWo, 0, s * 64, bx * 5, bC + 8 * s); }
        pdl_wait();
        for (int s = 0; s < F_CST; s++) { load_a(&tmO, sbase + s * F_RS, s, bC + 8 * s); if (s >= 3) tma_3d(sbase + s * F_RS + 16384, &tmWo, 0, s * 64, bx * 5, bC + 8 * s); }
        for (int kt = F_CST; kt < 10; kt++) {
          const int s = kt - F_CST;
          mbar_wait(bC + 8 * (F_CST + s), 0);
          mbar_expect_tx(bC + 8 * s, F_RS);
          load_a(&tmO, sbase + s * F_RS, kt, bC + 8 * s);
          tma_3d(sbase + s * F_RS + 16384, &tmWo, 0, kt * 64, bx * 5, bC + 8 * s);
        }
        auto load_bd = [&](int kt, int s) {
          tma_3d(sbase + s * F_DS + 16384, &tmWg, 0, kt * 64, bx * 3, bD + 8 * s);
          tma_3d(sbase + s * F_DS + 16384 + 3 * 8192, &tmWu, 0, kt * 64, bx * 3, bD + 8 * s);
        };
        for (int s = 0; s < F_DST; s++) { mbar_wait(bD + 8 * (F_DST + s), 0); mbar_expect_tx(bD + 8 * s, F_DS); load_bd(s, s); }
        flag_wait(&g_flag[rb], 8);
        for (int s = 0; s < F_DST; s++) load_a(&tmH, sbase + s * F_DS, s, bD + 8 * s);
        for (int kt = F_DST; kt < 10; kt++) {
          const int s = kt % F_DST;
          mbar_wait(bD + 8 * (F_DST + s), (kt / F_DST) & 1);
          mbar_expect_tx(bD + 8 * s, F_DS);
          load_a(&tmH, sbase + s * F_DS, kt, bD + 8 * s);
          load_bd(kt, s);
        }
        const uint32_t eb = sbase + F_E_OFF;
        for (int s = 0; s < F_EST; s++) { mbar_wait(bE + 8 * (F_EST + s), 0); mbar_expect_tx(bE + 8 * s, F_RS); tma_3d(eb + s * F_RS + 16384, &tmWd, 0, s * 64, bx * 5, bE + 8 * s); }
        flag_wait(&g_flag[16 + rb], 8);
        for (int s = 0; s < F_EST; s++) load_a(&tmAct, eb + s * F_RS, s, bE + 8 * s);
        for (int kt = F_EST; kt < 24; kt++) {
          const int s = kt % F_EST;
          mbar_wait(bE + 8 * (F_EST + s), (kt / F_EST) & 1);
          mbar_expect_tx(bE + 8 * s, F_RS);
          load_a(&tmAct, eb + s * F_RS, kt, bE + 8 * s);
          tma_3d(eb + s * F_RS + 16384, &tmWd, 0, kt * 64, bx * 5, bE + 8 * s);
        }
      }
    } else {
      float2* s_st = (float2*)(sptr + F_VEC_OFF);
      float* s_cs = (float*)(sptr + F_VEC_OFF + 1024);
      pdl_wait();
      for (int c = tid - 288; c < 192; c += 96) { s_cs[c] = g_cs_g[bx * 192 + c]; s_cs[192 + c] = g_cs_u[bx * 192 + c]; }
      flag_wait(&g_flag[rb], 8);
      for (int r = tid - 288; r < 128; r += 96) {
        const float2* pp = &g_part2[(m0 + r) * 8];
        float2 p[8];
        float s = 0.f;
#pragma unroll
        for (int i = 0; i < 8; i++) { asm volatile("ld.global.v2.f32 {%0, %1}, [%2];" : "=f"(p[i].x), "=f"(p[i].y) : "l"(pp + i) : "memory"); s += p[i].x; }
        const float mean = s * (1.0f / DM);
        float q = 0.f;
#pragma unroll
        for (int i = 0; i < 8; i++) { const float d = p[i].x * (1.0f / 80.f) - mean; q += p[i].y + 80.f * d * d; }
        s_st[r] = ln_finish(mean, q * (1.0f / DM));
      }
      __threadfence_block();
      asm volatile("bar.arrive 2, 352;" ::: "memory");
    }
    if (F_MC) { __syncwarp(); cluster_arrive(); cluster_wait(); }
    return;
  }
  asm volatile("setmaxnreg.inc.sync.aligned.u32 232;");
  const int wg = warp >> 2, g = lane >> 2, t = lane & 3;
  auto release = [&](uint32_t bar) { if (F_MC) { if ((tid & 127) < 2) mbar_arrive_remote(bar, (tid & 127) ^ cx); } else if ((tid & 127) == 0) mbar_arrive(bar); };
  const int n0 = bx * 80;
  uint4 rv[5];
  pdl_wait();
  {
#pragma unroll
    for (int i = 0; i < 5; i++) { const int idx = i * 256 + tid, r = idx / 10, c = idx % 10; rv[i] = ld_g16(x + (size_t)(m0 + r) * DM + n0 + c * 8); }
    float acc[40];
#pragma unroll
    for (int i = 0; i < 40; i++) acc[i] = 0.f;
    for (int kt = 0; kt < 10; kt++) {
      const int s = kt % F_CST;
      mbar_wait(bC + 8 * s, kt / F_CST);
      if (kt == 0) TS_MID(3, 0);
      const uint32_t sa = sbase + s * F_RS + wg * 8192, sb = sbase + s * F_RS + 16384;
      wgmma_fence();
#pragma unroll
      for (int ks = 0; ks < 4; ks++) wgmma_ss_n80(acc, make_desc(sa + ks * 32, 16, 1024, 1), make_desc(sb + ks * 512, 2048, 256, 3), 1);
      wgmma_commit();
      wgmma_wait<1>();
      if (kt > 0 && kt - 1 + F_CST < 10) release(bC + 8 * (F_CST + kt - 1));
    }
    wgmma_wait<0>();
#pragma unroll
    for (int i = 0; i < 40; i++) asm volatile("" : "+f"(acc[i]) :: "memory");
    for (int s = 0; s < F_DST; s++) release(bD + 8 * (F_DST + s));
    TS_MID(3, 1);
    res_epilogue<true>(acc, rv, sptr + F_STG_OFF, g_h, m0, n0, tid, bx);
    __threadfence();
    named_bar(1, 256);
    if (tid == 0) flag_signal(&g_flag[rb]);
    TS_END(3);
  }
  {
    float acc[2][96];
#pragma unroll
    for (int i = 0; i < 96; i++) { acc[0][i] = 0.f; acc[1][i] = 0.f; }
    for (int kt = 0; kt < 10; kt++) {
      const int s = kt % F_DST;
      mbar_wait(bD + 8 * s, (kt / F_DST) & 1);
      if (kt == 0) TS_MID(4, 0);
      const uint32_t sa = sbase + s * F_DS + wg * 8192, sb = sbase + s * F_DS + 16384;
      wgmma_fence();
#pragma unroll
      for (int ks = 0; ks < 4; ks++) {
        const uint64_t da = make_desc(sa + ks * 32, 16, 1024, 1);
        wgmma_ss_n192(acc[0], da, make_desc(sb + ks * 2048, 8192, 1024, 1), 1);
        wgmma_ss_n192(acc[1], da, make_desc(sb + 3 * 8192 + ks * 2048, 8192, 1024, 1), 1);
      }
      wgmma_commit();
      wgmma_wait<1>();
      if (kt > 0 && kt - 1 + F_DST < 10) release(bD + 8 * (F_DST + (kt - 1) % F_DST));
    }
    wgmma_wait<0>();
#pragma unroll
    for (int i = 0; i < 96; i++) { asm volatile("" : "+f"(acc[0][i]) :: "memory"); asm volatile("" : "+f"(acc[1][i]) :: "memory"); }
    for (int s = 0; s < F_EST; s++) release(bE + 8 * (F_EST + s));
    TS_MID(4, 1);
    named_bar(1, 256);
    named_bar(2, 352);
    constexpr int LDS = 400;
    const float2* s_st = (const float2*)(sptr + F_VEC_OFF);
    const float* s_cs = (const float*)(sptr + F_VEC_OFF + 1024);
    const int r0 = wg * 64 + (warp & 3) * 16 + g;
    const float2 st[2] = {s_st[r0], s_st[r0 + 8]};
#pragma unroll
    for (int j = 0; j < 24; j++) {
      const float2 cg = *(const float2*)&s_cs[j * 8 + 2 * t], cu = *(const float2*)&s_cs[192 + j * 8 + 2 * t];
      const float* a = &acc[0][4 * j];
      const float* b = &acc[1][4 * j];
#pragma unroll
      for (int e = 0; e < 2; e++) {
        const float2 s_ = st[e];
        const uint32_t gp = pack_bf16(fmaf(-s_.x, cg.x, a[2 * e]) * s_.y, fmaf(-s_.x, cg.y, a[2 * e + 1]) * s_.y);
        const uint32_t up = pack_bf16(fmaf(-s_.x, cu.x, b[2 * e]) * s_.y, fmaf(-s_.x, cu.y, b[2 * e + 1]) * s_.y);
        uint32_t r;
        asm("{\n.reg .b32 z;\nmax.bf16x2 z, %1, %3;\nmul.rn.bf16x2 %0, z, %2;\n}" : "=r"(r) : "r"(gp), "r"(up), "r"(0u));
        *(uint32_t*)(sptr + (r0 + 8 * e) * LDS + j * 16 + t * 4) = r;
      }
    }
    named_bar(1, 256);
#pragma unroll
    for (int i = 0; i < 12; i++) {
      const int idx = i * 256 + tid, r = idx / 24, c = idx % 24;
      st_g16(g_act + (size_t)(m0 + r) * DFF + bx * 192 + c * 8, *(const uint4*)(sptr + r * LDS + c * 16));
    }
    __threadfence();
    named_bar(1, 256);
    if (tid == 0) flag_signal(&g_flag[16 + rb]);
    TS_END(4);
  }
  {
#pragma unroll
    for (int i = 0; i < 5; i++) { const int idx = i * 256 + tid, r = idx / 10, c = idx % 10; rv[i] = ld_g16(g_h + (size_t)(m0 + r) * DM + n0 + c * 8); }
    float acc[40];
#pragma unroll
    for (int i = 0; i < 40; i++) acc[i] = 0.f;
    const uint32_t eb = sbase + F_E_OFF;
    for (int kt = 0; kt < 24; kt++) {
      const int s = kt % F_EST;
      mbar_wait(bE + 8 * s, (kt / F_EST) & 1);
      if (kt == 0) TS_MID(5, 0);
      const uint32_t sa = eb + s * F_RS + wg * 8192, sb = eb + s * F_RS + 16384;
      wgmma_fence();
#pragma unroll
      for (int ks = 0; ks < 4; ks++) wgmma_ss_n80(acc, make_desc(sa + ks * 32, 16, 1024, 1), make_desc(sb + ks * 512, 2048, 256, 3), 1);
      wgmma_commit();
      wgmma_wait<1>();
      if (kt > 0 && kt - 1 + F_EST < 24) release(bE + 8 * (F_EST + (kt - 1) % F_EST));
    }
    wgmma_wait<0>();
#pragma unroll
    for (int i = 0; i < 40; i++) asm volatile("" : "+f"(acc[i]) :: "memory");
    if (F_MC) cluster_arrive();
    TS_MID(5, 1);
    res_epilogue<false>(acc, rv, sptr + F_STG_OFF, out, m0, n0, tid, bx);
    if (F_MC) cluster_wait();
    TS_END(5);
  }
}

#define POLY_NUM 5
__device__ __forceinline__ float ex2_poly(float x, int shl23) {
  const float MAGIC = 12582912.f;
  const float tt = x + MAGIC;
  const float f = x - (tt - MAGIC);
  float p = fmaf(0.0013276472454890609f, f, 0.009675540961325169f);
  p = fmaf(p, f, 0.05550713092088699f);
  p = fmaf(p, f, 0.24022120237350464f);
  p = fmaf(p, f, 0.6931469440460205f);
  p = fmaf(p, f, 1.0000001192092896f);
  return __int_as_float(__float_as_int(tt) * shl23 + __float_as_int(p));
}
constexpr int KV_BYTES = S_LEN * 48;
constexpr int ATT_SMEM = 2 * KV_BYTES + 256 + 32768;
constexpr int ATT_BODY = 8;

__global__ void __launch_bounds__(512, 1) attn_kernel(int shl23, const __nv_bfloat16* __restrict__ wg_, const __nv_bfloat16* __restrict__ wu_,
                                                      const __grid_constant__ CUtensorMap tmWo, const __grid_constant__ CUtensorMap tmWd) {
  extern __shared__ __align__(1024) uint8_t smem[];
  if (blockIdx.x >= 128) {
    pdl_launch();
    const int e = blockIdx.x - 128, half = threadIdx.x >> 8;
    TS_MID(0, 0);
    if (threadIdx.x == 0) {
      const uint32_t sb = smem_u32(smem), bar = sb + 200 * 1024;
      mbar_init(bar, 1);
      asm volatile("fence.mbarrier_init.release.cluster;" ::: "memory");
      for (int rd = 0; rd < 4; rd++) {
        mbar_expect_tx(bar, 17 * 10240);
        for (int i = 0; i < 17; i++) {
          const int tl = e * 68 + rd * 17 + i;
          if (tl >= 80) tma_3d(sb + i * 10240, &tmWd, 0, ((tl - 80) % 24) * 64, ((tl - 80) / 24) * 5, bar);
          else tma_3d(sb + i * 10240, &tmWo, 0, (tl % 10) * 64, (tl / 10) * 5, bar);
        }
        mbar_wait(bar, rd & 1);
        for (int i = 0; i < 17; i++) {
          const int tl = e * 68 + rd * 17 + i;
          uint8_t* dst = tl >= 80 ? (uint8_t*)g_wd_t + (size_t)(tl - 80) * 10240 : (uint8_t*)g_wo_t + (size_t)tl * 10240;
          asm volatile("cp.async.bulk.global.shared::cta.bulk_group [%0], [%1], %2;" :: "l"(dst), "r"(sb + i * 10240), "r"(10240) : "memory");
        }
        asm volatile("cp.async.bulk.commit_group;" ::: "memory");
        asm volatile("cp.async.bulk.wait_group 0;" ::: "memory");
      }
    }
    __syncwarp();
    TS_MID(0, 1);
    float (*red)[65] = (float (*)[65])(smem + 176 * 1024 + half * 10240);
    for (int b = e * 12 + half; b < e * 12 + 12; b += 2) {
      if (b < 24) colsum64(wg_, DFF, b * 64, g_cs_g, red, threadIdx.x & 255, 1 + half);
      else colsum64(wu_, DFF, (b - 24) * 64, g_cs_u, red, threadIdx.x & 255, 1 + half);
    }
    TS_MID(0, 2);
    return;
  }
  const int h = blockIdx.x >> 2, qb = blockIdx.x & 3;
  const uint32_t sK = smem_u32(smem), sV = sK + KV_BYTES, sBar = sV + KV_BYTES;
  const int tid = threadIdx.x;
  TS_BEGIN(2);
  if (tid == 0) {
    for (int i = 0; i < 9; i++) mbar_init(sBar + 8 * i, 1);
    asm volatile("fence.mbarrier_init.release.cluster;" ::: "memory");
  }
  __syncthreads();
  pdl_launch();
  pdl_wait();
  TS_MID(2, 0);
  const uint8_t* gk = (const uint8_t*)(g_k + (size_t)h * S_LEN * 24);
  const uint8_t* gv = (const uint8_t*)(g_v + (size_t)h * S_LEN * 24);
  auto load_kv = [&](int i0, int i1) {
    for (int i = i0; i < i1; i++) {
      mbar_expect_tx(sBar + 8 * i, 2 * 12288);
      bulk_g2s(sK + i * 12288, gk + i * 12288, 12288, sBar + 8 * i);
      bulk_g2s(sV + i * 12288, gv + i * 12288, 12288, sBar + 8 * i);
    }
  };
  if (tid == 0) {
    mbar_expect_tx(sBar + 64, 32768);
    bulk_g2s(sBar + 256, (const uint8_t*)g_q + ((size_t)h * S_LEN + qb * 512) * 64, 32768, sBar + 64);
    load_kv(0, 2);
  }
  float ka = 0.f, kb = 0.f;
#pragma unroll
  for (int i = 0; i < 8; i++) {
    const float2 v = *(const float2*)&g_kn[(i * NH + h) * 2];
    ka = (v.x > ka || v.x != v.x) ? v.x : ka;
    kb = (v.y > kb || v.y != v.y) ? v.y : kb;
  }
  bool fast;
  {
    const float kn = sqrtf(ka + kb);
    mbar_wait(sBar + 64, 0);
    if (tid == 0) load_kv(2, 8);
    uint8_t* qrow = smem + 2 * KV_BYTES + 256 + (tid >> 3) * 512 + (tid & 7) * 16;
    const uint4 c0 = *(const uint4*)qrow, c1 = *(const uint4*)(qrow + 128);
    const uint2 c2 = *(const uint2*)(qrow + 256);
    auto sq = [](uint32_t u) { const float a = bf_lo(u), b = bf_hi(u); return a * a + b * b; };
    const float n2 = sq(c0.x) + sq(c0.y) + sq(c0.z) + sq(c0.w) + sq(c1.x) + sq(c1.y) + sq(c1.z) + sq(c1.w) + sq(c2.x) + sq(c2.y);
    const float m = ceilf(sqrtf(n2) * kn * 1.001f) + 1.f;
    fast = __syncthreads_or(!(m <= 62.f)) == 0;
    if (fast) *(uint32_t*)(qrow + 256 + 8) = pack_bf16(-m, 0.f);
    asm volatile("fence.proxy.async.shared::cta;" ::: "memory");
    __syncthreads();
  }
  auto write_out = [&](float (&O)[12], int it) {
    uint32_t tid2;
    asm volatile("mov.u32 %0, %%tid.x;" : "=r"(tid2));
    const int lane2 = tid2 & 31, t2 = lane2 & 3;
    const int qq = (blockIdx.x & 3) * 512 + (it * 4 + (tid2 >> 7)) * 64 + ((tid2 >> 5) & 3) * 16 + (lane2 >> 2);
    const float l0 = __shfl_sync(~0u, O[8], (lane2 & ~3) | 2), l1 = __shfl_sync(~0u, O[10], (lane2 & ~3) | 2);
    const float r0 = 1.f / l0, r1 = 1.f / l1;
    uint32_t* o0 = (uint32_t*)(g_o + (size_t)qq * DM + (blockIdx.x >> 2) * DH);
    uint32_t* o1 = o0 + 8 * DM / 2;
    o0[t2] = pack_bf16(O[0] * r0, O[1] * r0); o1[t2] = pack_bf16(O[2] * r1, O[3] * r1);
    o0[t2 + 4] = pack_bf16(O[4] * r0, O[5] * r0); o1[t2 + 4] = pack_bf16(O[6] * r1, O[7] * r1);
    if (t2 < 2) { o0[t2 + 8] = pack_bf16(O[8] * r0, O[9] * r0); o1[t2 + 8] = pack_bf16(O[10] * r1, O[11] * r1); }
  };
  TS_MID(2, 1);
  if (fast) {
#pragma unroll 1
    for (int it = 0; it < 2; it++) {
      const uint64_t dq = make_desc(sBar + 256 + (it * 4 + (tid >> 7)) * 4096, 128, 512, 0);
      float O[12];
#pragma unroll
      for (int i = 0; i < 12; i++) { O[i] = 0.f; asm volatile("" : "+f"(O[i]) :: "memory"); }
      float S[2][32];
      uint32_t P[16];
#pragma unroll 1
      for (int jb = 0; jb < 32 / ATT_BODY; jb++) {
        if (it == 0) { for (int c = 0; c < ATT_BODY / 4; c++) mbar_wait(sBar + 8 * (jb * (ATT_BODY / 4) + c), 0); }
        const uint64_t dk0 = make_desc(sK + jb * ATT_BODY * 8 * 384, 128, 384, 0);
        const uint64_t dv0 = make_desc(sV + jb * ATT_BODY * 8 * 384, 384, 128, 0);
        wgmma_fence();
        wgmma_ss_n64_k(S[0], dq, dk0, 0);
        wgmma_ss_n64_k(S[0], dq + (256 >> 4), dk0 + (256 >> 4), 1);
        wgmma_commit();
#pragma unroll
        for (int u = 0; u < ATT_BODY; u++) {
          if (u + 1 < ATT_BODY) {
            const uint64_t dk = dk0 + (((u + 1) * 8 * 384) >> 4);
            wgmma_fence();
            wgmma_ss_n64_k(S[(u + 1) & 1], dq, dk, 0);
            wgmma_ss_n64_k(S[(u + 1) & 1], dq + (256 >> 4), dk + (256 >> 4), 1);
            wgmma_commit();
          }
          if (u == 0 || u == ATT_BODY - 1) wgmma_wait<1>(); else wgmma_wait<2>();
#pragma unroll
          for (int i = 0; i < 32; i++) asm volatile("" : "+f"(S[u & 1][i]) :: "memory");
          const uint64_t dv = dv0 + ((u * 8 * 384) >> 4);
#pragma unroll
          for (int hf = 0; hf < 2; hf++) {
            if (hf == 1 && u > 0) { if (u == ATT_BODY - 1) wgmma_wait<1>(); else wgmma_wait<2>(); }
#pragma unroll
            for (int i = hf * 8; i < hf * 8 + 8; i++) {
              const bool usepoly = ((i + 1) * POLY_NUM / 16) != (i * POLY_NUM / 16);
              float a, b;
              if (usepoly) { a = ex2_poly(S[u & 1][2 * i], shl23); b = ex2_poly(S[u & 1][2 * i + 1], shl23); }
              else { a = ex2_mufu(S[u & 1][2 * i]); b = ex2_mufu(S[u & 1][2 * i + 1]); }
              P[i] = pack_bf16(a, b);
            }
            wgmma_fence();
#pragma unroll
            for (int ks = hf * 2; ks < hf * 2 + 2; ks++)
              wgmma_rs_n24_tb(O, P[4 * ks], P[4 * ks + 1], P[4 * ks + 2], P[4 * ks + 3], dv + ((ks * 768) >> 4), 1);
            wgmma_commit();
          }
        }
        wgmma_wait<0>();
      }
#pragma unroll
      for (int i = 0; i < 12; i++) asm volatile("" : "+f"(O[i]) :: "memory");
      write_out(O, it);
      if (it == 0) TS_MID(2, 2);
    }
  } else {
#pragma unroll 1
    for (int it = 0; it < 2; it++) {
      const uint64_t dq = make_desc(sBar + 256 + (it * 4 + (tid >> 7)) * 4096, 128, 512, 0);
      float O[12];
#pragma unroll
      for (int i = 0; i < 12; i++) { O[i] = 0.f; asm volatile("" : "+f"(O[i]) :: "memory"); }
      float S[32];
      float mx0 = -INFINITY, mx1 = -INFINITY;
#pragma unroll 1
      for (int j = 0; j < 32; j++) {
        if (it == 0 && (j & 3) == 0) mbar_wait(sBar + 8 * (j >> 2), 0);
        const uint64_t dk = make_desc(sK + j * 8 * 384, 128, 384, 0);
        wgmma_fence();
        wgmma_ss_n64_k(S, dq, dk, 0);
        wgmma_ss_n64_k(S, dq + (256 >> 4), dk + (256 >> 4), 1);
        wgmma_commit();
        wgmma_wait<0>();
#pragma unroll
        for (int i = 0; i < 8; i++) {
          mx0 = fmaxf(mx0, fmaxf(S[4 * i], S[4 * i + 1]));
          mx1 = fmaxf(mx1, fmaxf(S[4 * i + 2], S[4 * i + 3]));
        }
      }
      mx0 = fmaxf(mx0, __shfl_xor_sync(~0u, mx0, 1)); mx0 = fmaxf(mx0, __shfl_xor_sync(~0u, mx0, 2));
      mx1 = fmaxf(mx1, __shfl_xor_sync(~0u, mx1, 1)); mx1 = fmaxf(mx1, __shfl_xor_sync(~0u, mx1, 2));
#pragma unroll 1
      for (int j = 0; j < 32; j++) {
        const uint64_t dk = make_desc(sK + j * 8 * 384, 128, 384, 0);
        wgmma_fence();
        wgmma_ss_n64_k(S, dq, dk, 0);
        wgmma_ss_n64_k(S, dq + (256 >> 4), dk + (256 >> 4), 1);
        wgmma_commit();
        wgmma_wait<0>();
        uint32_t P[16];
#pragma unroll
        for (int i = 0; i < 8; i++) {
          P[2 * i] = pack_bf16(ex2_mufu(S[4 * i] - mx0), ex2_mufu(S[4 * i + 1] - mx0));
          P[2 * i + 1] = pack_bf16(ex2_mufu(S[4 * i + 2] - mx1), ex2_mufu(S[4 * i + 3] - mx1));
        }
        wgmma_fence();
        const uint64_t dv = make_desc(sV + j * 8 * 384, 384, 128, 0);
#pragma unroll
        for (int ks = 0; ks < 4; ks++)
          wgmma_rs_n24_tb(O, P[4 * ks], P[4 * ks + 1], P[4 * ks + 2], P[4 * ks + 3], dv + ((ks * 768) >> 4), 1);
        wgmma_commit();
        wgmma_wait<0>();
      }
#pragma unroll
      for (int i = 0; i < 12; i++) asm volatile("" : "+f"(O[i]) :: "memory");
      write_out(O, it);
    }
  }
  TS_END(2);
}

typedef CUresult (*EncodeFn)(CUtensorMap*, CUtensorMapDataType, cuuint32_t, void*, const cuuint64_t*, const cuuint64_t*, const cuuint32_t*,
                             const cuuint32_t*, CUtensorMapInterleave, CUtensorMapSwizzle, CUtensorMapL2promotion, CUtensorMapFloatOOBfill);
static EncodeFn get_encode() {
  static EncodeFn fn = nullptr;
  if (!fn) {
    void* p = nullptr; cudaDriverEntryPointQueryResult st;
    cudaGetDriverEntryPoint("cuTensorMapEncodeTiled", &p, cudaEnableDefault, &st);
    fn = (EncodeFn)p;
  }
  return fn;
}
static CUtensorMap make_map(const void* ptr, int rows, int cols, int box_rows, int box_cols = 64) {
  CUtensorMap m;
  cuuint64_t dims[2] = {(cuuint64_t)cols, (cuuint64_t)rows};
  cuuint64_t strides[1] = {(cuuint64_t)cols * 2};
  cuuint32_t box[2] = {(cuuint32_t)box_cols, (cuuint32_t)box_rows};
  cuuint32_t es[2] = {1, 1};
  get_encode()(&m, CU_TENSOR_MAP_DATA_TYPE_BFLOAT16, 2, const_cast<void*>(ptr), dims, strides, box, es, CU_TENSOR_MAP_INTERLEAVE_NONE,
               box_cols == 64 ? CU_TENSOR_MAP_SWIZZLE_128B : (box_cols == 32 ? CU_TENSOR_MAP_SWIZZLE_64B : CU_TENSOR_MAP_SWIZZLE_32B), CU_TENSOR_MAP_L2_PROMOTION_L2_128B, CU_TENSOR_MAP_FLOAT_OOB_FILL_NONE);
  return m;
}
static CUtensorMap make_map_w(const void* ptr, int rows, int cols, int bc, int nblk) {
  CUtensorMap m;
  cuuint64_t dims[3] = {(cuuint64_t)bc, (cuuint64_t)rows, (cuuint64_t)(cols / bc)};
  cuuint64_t strides[2] = {(cuuint64_t)cols * 2, (cuuint64_t)bc * 2};
  cuuint32_t box[3] = {(cuuint32_t)bc, 64, (cuuint32_t)nblk};
  cuuint32_t es[3] = {1, 1, 1};
  get_encode()(&m, CU_TENSOR_MAP_DATA_TYPE_BFLOAT16, 3, const_cast<void*>(ptr), dims, strides, box, es, CU_TENSOR_MAP_INTERLEAVE_NONE,
               bc == 64 ? CU_TENSOR_MAP_SWIZZLE_128B : (bc == 32 ? CU_TENSOR_MAP_SWIZZLE_64B : CU_TENSOR_MAP_SWIZZLE_32B),
               CU_TENSOR_MAP_L2_PROMOTION_L2_128B, CU_TENSOR_MAP_FLOAT_OOB_FILL_NONE);
  return m;
}
template <typename... KArgs, typename... Args>
static void launch(void (*kern)(KArgs...), dim3 grid, dim3 block, size_t smem, bool pdl, dim3 cluster, Args... args) {
  cudaLaunchConfig_t cfg = {};
  cfg.gridDim = grid; cfg.blockDim = block; cfg.dynamicSmemBytes = smem; cfg.stream = cudaStreamPerThread;
  cudaLaunchAttribute at[2];
  int na = 0;
  if (pdl) { at[na].id = cudaLaunchAttributeProgrammaticStreamSerialization; at[na].val.programmaticStreamSerializationAllowed = 1; na++; }
  if (cluster.x * cluster.y > 1) { at[na].id = cudaLaunchAttributeClusterDimension; at[na].val.clusterDim.x = cluster.x; at[na].val.clusterDim.y = cluster.y; at[na].val.clusterDim.z = 1; na++; }
  cfg.attrs = at; cfg.numAttrs = na;
  cudaLaunchKernelEx(&cfg, kern, KArgs(args)...);
}

extern "C" void kernel_launch(void* const* d_in, const int* in_sizes, int n_in, void* d_out, int out_size) {
  const __nv_bfloat16* x = (const __nv_bfloat16*)d_in[0];
  const __nv_bfloat16* wqkv = (const __nv_bfloat16*)d_in[1];
  const __nv_bfloat16* wo = (const __nv_bfloat16*)d_in[2];
  const __nv_bfloat16* wgate = (const __nv_bfloat16*)d_in[4];
  const __nv_bfloat16* wup = (const __nv_bfloat16*)d_in[5];
  const __nv_bfloat16* wdown = (const __nv_bfloat16*)d_in[6];
  __nv_bfloat16* out = (__nv_bfloat16*)d_out;
  void *p_o, *p_h, *p_act;
  cudaGetSymbolAddress(&p_o, g_o); cudaGetSymbolAddress(&p_h, g_h); cudaGetSymbolAddress(&p_act, g_act);

#define A_CN 1
#define A_CM 1
#define D_CN 1
#define D_CM 1
  auto kA = gemm_kernel<256, 128, 1, DM, 4, EPI_QKV, 1, A_CN, A_CM>;
  auto kC = gemm_res_kernel<DM, true>;
  auto kD = gemm_kernel<128, 192, 2, DM, 3, EPI_GLU, 1, D_CN, D_CM>;
  auto kE = gemm_res_kernel<DFF, false>;
  constexpr int smA = GemmCfg<256, 128, 1, 4>::SMEM, smC = R_SMEM, smD = GemmCfg<128, 192, 2, 3>::SMEM;
  cudaFuncSetAttribute(kA, cudaFuncAttributeMaxDynamicSharedMemorySize, smA);
  cudaFuncSetAttribute(kC, cudaFuncAttributeMaxDynamicSharedMemorySize, smC);
  cudaFuncSetAttribute(kD, cudaFuncAttributeMaxDynamicSharedMemorySize, smD);
  cudaFuncSetAttribute(kE, cudaFuncAttributeMaxDynamicSharedMemorySize, smC);
  cudaFuncSetAttribute(attn_kernel, cudaFuncAttributeMaxDynamicSharedMemorySize, ATT_SMEM);

  const CUtensorMap tm_x = make_map(x, S_LEN, DM, 256), tm_wqkv = make_map_w(wqkv, DM, 3 * DM, 64, 2);
  const CUtensorMap tm_o = make_map(p_o, S_LEN, DM, 128), tm_wo = make_map_w(wo, DM, DM, 16, 5);
  const CUtensorMap tm_h = make_map(p_h, S_LEN, DM, 128), tm_wg = make_map_w(wgate, DM, DFF, 64, 3), tm_wu = make_map_w(wup, DM, DFF, 64, 3);
  const CUtensorMap tm_act = make_map(p_act, S_LEN, DFF, 128), tm_wd = make_map_w(wdown, DFF, DM, 16, 5);

  launch(pre_kernel, dim3(12), dim3(1024), 0, false, dim3(1, 1), x, wqkv);
  launch(kA, dim3(15, 8), dim3(288), smA, true, dim3(A_CN, A_CM), tm_x, tm_wqkv, tm_wqkv, x, (__nv_bfloat16*)wqkv);
  launch(attn_kernel, dim3(132), dim3(512), ATT_SMEM, true, dim3(1, 1), 0x800000, wgate, wup, tm_wo, tm_wd);
  launch(kC, dim3(8, 16), dim3(288), smC, true, dim3(1, 1), tm_o, tm_wo, x, (__nv_bfloat16*)p_h);
  launch(kD, dim3(8, 16), dim3(384), smD, true, dim3(D_CN, D_CM), tm_h, tm_wg, tm_wu, (const __nv_bfloat16*)nullptr, (__nv_bfloat16*)p_act);
  launch(kE, dim3(8, 16), dim3(288), smC, true, dim3(1, 1), tm_act, tm_wd, (const __nv_bfloat16*)p_h, out);
}
```

```cpp
#include <cuda_runtime.h>
#include <cuda_bf16.h>
#include <cuda.h>
#include <stdint.h>

constexpr int S_LEN = 2048, DM = 640, NH = 32, DH = 20, DFF = 1536;

__device__ __align__(1024) __nv_bfloat16 g_q[NH * S_LEN * 32];
__device__ __align__(1024) __nv_bfloat16 g_k[NH * S_LEN * 24];
__device__ __align__(1024) __nv_bfloat16 g_v[NH * S_LEN * 24];
__device__ __align__(1024) __nv_bfloat16 g_o[S_LEN * DM];
__device__ __align__(1024) __nv_bfloat16 g_h[S_LEN * DM];
__device__ __align__(1024) __nv_bfloat16 g_act[S_LEN * DFF];
__device__ __align__(1024) __nv_bfloat16 g_wo_t[DM * DM];
__device__ __align__(1024) __nv_bfloat16 g_wd_t[DFF * DM];
__device__ float g_kn[8 * NH * 2];
__device__ float2 g_stat1[S_LEN];
__device__ float g_cs_qkv[3 * DM];
__device__ float g_cs_g[DFF];
__device__ float g_cs_u[DFF];
__device__ unsigned int g_flag[32];
__device__ float2 g_part2[S_LEN * 10];

#define TS_BEGIN(k)
#define TS_END(k)
#define TS_MID(k, i)
__device__ __forceinline__ uint32_t smem_u32(const void* p) { return (uint32_t)__cvta_generic_to_shared(p); }
__device__ __forceinline__ void mbar_init(uint32_t bar, uint32_t cnt) { asm volatile("mbarrier.init.shared::cta.b64 [%0], %1;" :: "r"(bar), "r"(cnt)); }
__device__ __forceinline__ void mbar_expect_tx(uint32_t bar, uint32_t bytes) { asm volatile("mbarrier.arrive.expect_tx.shared::cta.b64 _, [%0], %1;" :: "r"(bar), "r"(bytes) : "memory"); }
__device__ __forceinline__ void mbar_arrive(uint32_t bar) { asm volatile("mbarrier.arrive.shared::cta.b64 _, [%0];" :: "r"(bar) : "memory"); }
__device__ __forceinline__ void mbar_wait(uint32_t bar, uint32_t parity) {
  uint32_t done;
  uint32_t spins = 0;
  do {
    asm volatile("{\n.reg .pred P1;\nmbarrier.try_wait.parity.shared::cta.b64 P1, [%1], %2;\nselp.u32 %0, 1, 0, P1;\n}" : "=r"(done) : "r"(bar), "r"(parity) : "memory");
  } while (!done && ++spins < (1u << 24));
}
__device__ __forceinline__ void bulk_g2s(uint32_t dst, const void* src, uint32_t bytes, uint32_t bar) {
  asm volatile("cp.async.bulk.shared::cluster.global.mbarrier::complete_tx::bytes [%0], [%1], %2, [%3];" :: "r"(dst), "l"(src), "r"(bytes), "r"(bar) : "memory");
}
__device__ __forceinline__ void tma_2d(uint32_t dst, const CUtensorMap* tm, int c0, int c1, uint32_t bar) {
  asm volatile("cp.async.bulk.tensor.2d.shared::cluster.global.mbarrier::complete_tx::bytes [%0], [%1, {%3, %4}], [%2];"
               :: "r"(dst), "l"(tm), "r"(bar), "r"(c0), "r"(c1) : "memory");
}
__device__ __forceinline__ void tma_3d(uint32_t dst, const CUtensorMap* tm, int c0, int c1, int c2, uint32_t bar) {
  asm volatile("cp.async.bulk.tensor.3d.shared::cluster.global.mbarrier::complete_tx::bytes [%0], [%1, {%3, %4, %5}], [%2];"
               :: "r"(dst), "l"(tm), "r"(bar), "r"(c0), "r"(c1), "r"(c2) : "memory");
}
__device__ __forceinline__ void tma_2d_mc(uint32_t dst, const CUtensorMap* tm, int c0, int c1, uint32_t bar, uint16_t mask) {
  asm volatile("cp.async.bulk.tensor.2d.shared::cluster.global.mbarrier::complete_tx::bytes.multicast::cluster [%0], [%1, {%3, %4}], [%2], %5;"
               :: "r"(dst), "l"(tm), "r"(bar), "r"(c0), "r"(c1), "h"(mask) : "memory");
}
__device__ __forceinline__ void mbar_arrive_remote(uint32_t bar, uint32_t rank) {
  asm volatile("{\n.reg .b32 ra;\nmapa.shared::cluster.u32 ra, %0, %1;\nmbarrier.arrive.release.cluster.shared::cluster.b64 _, [ra];\n}" :: "r"(bar), "r"(rank) : "memory");
}
__device__ __forceinline__ void cluster_arrive() { asm volatile("barrier.cluster.arrive.release.aligned;" ::: "memory"); }
__device__ __forceinline__ void cluster_wait() { asm volatile("barrier.cluster.wait.acquire.aligned;" ::: "memory"); }
__device__ __forceinline__ void wgmma_fence() { asm volatile("wgmma.fence.sync.aligned;" ::: "memory"); }
__device__ __forceinline__ void wgmma_commit() { asm volatile("wgmma.commit_group.sync.aligned;" ::: "memory"); }
template <int N> __device__ __forceinline__ void wgmma_wait() { asm volatile("wgmma.wait_group.sync.aligned %0;" :: "n"(N) : "memory"); }
__device__ __forceinline__ void pdl_wait() { asm volatile("griddepcontrol.wait;" ::: "memory"); }
__device__ __forceinline__ void pdl_launch() { asm volatile("griddepcontrol.launch_dependents;" ::: "memory"); }
__device__ __forceinline__ void named_bar(int id, int n) { asm volatile("bar.sync %0, %1;" :: "r"(id), "r"(n) : "memory"); }
__device__ __forceinline__ uint64_t make_desc(uint32_t addr, uint32_t lbo, uint32_t sbo, uint32_t swz) {
  return (uint64_t)((addr & 0x3FFFF) >> 4) | ((uint64_t)(lbo >> 4) << 16) | ((uint64_t)(sbo >> 4) << 32) | ((uint64_t)swz << 62);
}
__device__ __forceinline__ void st_g16(void* p, uint4 v) { asm volatile("st.global.v4.b32 [%0], {%1, %2, %3, %4};" :: "l"(p), "r"(v.x), "r"(v.y), "r"(v.z), "r"(v.w) : "memory"); }
__device__ __forceinline__ void st_g8(void* p, uint2 v) { asm volatile("st.global.v2.b32 [%0], {%1, %2};" :: "l"(p), "r"(v.x), "r"(v.y) : "memory"); }
__device__ __forceinline__ uint4 ld_g16(const void* p) { uint4 v; asm volatile("ld.global.v4.b32 {%0, %1, %2, %3}, [%4];" : "=r"(v.x), "=r"(v.y), "=r"(v.z), "=r"(v.w) : "l"(p) : "memory"); return v; }
__device__ __forceinline__ uint32_t pack_bf16(float lo, float hi) { uint32_t r; asm("cvt.rn.bf16x2.f32 %0, %1, %2;" : "=r"(r) : "f"(hi), "f"(lo)); return r; }
__device__ __forceinline__ float bf_lo(uint32_t u) { return __uint_as_float(u << 16); }
__device__ __forceinline__ float bf_hi(uint32_t u) { return __uint_as_float(u & 0xffff0000u); }
__device__ __forceinline__ float bf_round(float x) { return __bfloat162float(__float2bfloat16_rn(x)); }
__device__ __forceinline__ float ex2_mufu(float x) { float y; asm("ex2.approx.ftz.f32 %0, %1;" : "=f"(y) : "f"(x)); return y; }

__device__ __forceinline__ void wgmma_ss_n80(float (&d)[40], uint64_t da, uint64_t db, int scale_d) {
  asm volatile("{\n.reg .pred p;\nsetp.ne.b32 p, %42, 0;\n"
    "wgmma.mma_async.sync.aligned.m64n80k16.f32.bf16.bf16 {%0,%1,%2,%3,%4,%5,%6,%7,%8,%9,%10,%11,%12,%13,%14,%15,%16,%17,%18,%19,%20,%21,%22,%23,%24,%25,%26,%27,%28,%29,%30,%31,%32,%33,%34,%35,%36,%37,%38,%39}, %40, %41, p, 1, 1, 0, 1;\n}\n"
    : "+f"(d[0]),"+f"(d[1]),"+f"(d[2]),"+f"(d[3]),"+f"(d[4]),"+f"(d[5]),"+f"(d[6]),"+f"(d[7]),"+f"(d[8]),"+f"(d[9]),"+f"(d[10]),"+f"(d[11]),"+f"(d[12]),"+f"(d[13]),"+f"(d[14]),"+f"(d[15]),"+f"(d[16]),"+f"(d[17]),"+f"(d[18]),"+f"(d[19]),"+f"(d[20]),"+f"(d[21]),"+f"(d[22]),"+f"(d[23]),"+f"(d[24]),"+f"(d[25]),"+f"(d[26]),"+f"(d[27]),"+f"(d[28]),"+f"(d[29]),"+f"(d[30]),"+f"(d[31]),"+f"(d[32]),"+f"(d[33]),"+f"(d[34]),"+f"(d[35]),"+f"(d[36]),"+f"(d[37]),"+f"(d[38]),"+f"(d[39])
    : "l"(da), "l"(db), "r"(scale_d));
}
__device__ __forceinline__ void wgmma_ss_n128(float (&d)[64], uint64_t da, uint64_t db, int scale_d) {
  asm volatile("{\n.reg .pred p;\nsetp.ne.b32 p, %66, 0;\n"
    "wgmma.mma_async.sync.aligned.m64n128k16.f32.bf16.bf16 {%0,%1,%2,%3,%4,%5,%6,%7,%8,%9,%10,%11,%12,%13,%14,%15,%16,%17,%18,%19,%20,%21,%22,%23,%24,%25,%26,%27,%28,%29,%30,%31,%32,%33,%34,%35,%36,%37,%38,%39,%40,%41,%42,%43,%44,%45,%46,%47,%48,%49,%50,%51,%52,%53,%54,%55,%56,%57,%58,%59,%60,%61,%62,%63}, %64, %65, p, 1, 1, 0, 1;\n}\n"
    : "+f"(d[0]),"+f"(d[1]),"+f"(d[2]),"+f"(d[3]),"+f"(d[4]),"+f"(d[5]),"+f"(d[6]),"+f"(d[7]),"+f"(d[8]),"+f"(d[9]),"+f"(d[10]),"+f"(d[11]),"+f"(d[12]),"+f"(d[13]),"+f"(d[14]),"+f"(d[15]),"+f"(d[16]),"+f"(d[17]),"+f"(d[18]),"+f"(d[19]),"+f"(d[20]),"+f"(d[21]),"+f"(d[22]),"+f"(d[23]),"+f"(d[24]),"+f"(d[25]),"+f"(d[26]),"+f"(d[27]),"+f"(d[28]),"+f"(d[29]),"+f"(d[30]),"+f"(d[31]),"+f"(d[32]),"+f"(d[33]),"+f"(d[34]),"+f"(d[35]),"+f"(d[36]),"+f"(d[37]),"+f"(d[38]),"+f"(d[39]),"+f"(d[40]),"+f"(d[41]),"+f"(d[42]),"+f"(d[43]),"+f"(d[44]),"+f"(d[45]),"+f"(d[46]),"+f"(d[47]),"+f"(d[48]),"+f"(d[49]),"+f"(d[50]),"+f"(d[51]),"+f"(d[52]),"+f"(d[53]),"+f"(d[54]),"+f"(d[55]),"+f"(d[56]),"+f"(d[57]),"+f"(d[58]),"+f"(d[59]),"+f"(d[60]),"+f"(d[61]),"+f"(d[62]),"+f"(d[63])
    : "l"(da), "l"(db), "r"(scale_d));
}
__device__ __forceinline__ void wgmma_ss_n192(float (&d)[96], uint64_t da, uint64_t db, int scale_d) {
  asm volatile("{\n.reg .pred p;\nsetp.ne.b32 p, %98, 0;\n"
    "wgmma.mma_async.sync.aligned.m64n192k16.f32.bf16.bf16 {%0,%1,%2,%3,%4,%5,%6,%7,%8,%9,%10,%11,%12,%13,%14,%15,%16,%17,%18,%19,%20,%21,%22,%23,%24,%25,%26,%27,%28,%29,%30,%31,%32,%33,%34,%35,%36,%37,%38,%39,%40,%41,%42,%43,%44,%45,%46,%47,%48,%49,%50,%51,%52,%53,%54,%55,%56,%57,%58,%59,%60,%61,%62,%63,%64,%65,%66,%67,%68,%69,%70,%71,%72,%73,%74,%75,%76,%77,%78,%79,%80,%81,%82,%83,%84,%85,%86,%87,%88,%89,%90,%91,%92,%93,%94,%95}, %96, %97, p, 1, 1, 0, 1;\n}\n"
    : "+f"(d[0]),"+f"(d[1]),"+f"(d[2]),"+f"(d[3]),"+f"(d[4]),"+f"(d[5]),"+f"(d[6]),"+f"(d[7]),"+f"(d[8]),"+f"(d[9]),"+f"(d[10]),"+f"(d[11]),"+f"(d[12]),"+f"(d[13]),"+f"(d[14]),"+f"(d[15]),"+f"(d[16]),"+f"(d[17]),"+f"(d[18]),"+f"(d[19]),"+f"(d[20]),"+f"(d[21]),"+f"(d[22]),"+f"(d[23]),"+f"(d[24]),"+f"(d[25]),"+f"(d[26]),"+f"(d[27]),"+f"(d[28]),"+f"(d[29]),"+f"(d[30]),"+f"(d[31]),"+f"(d[32]),"+f"(d[33]),"+f"(d[34]),"+f"(d[35]),"+f"(d[36]),"+f"(d[37]),"+f"(d[38]),"+f"(d[39]),"+f"(d[40]),"+f"(d[41]),"+f"(d[42]),"+f"(d[43]),"+f"(d[44]),"+f"(d[45]),"+f"(d[46]),"+f"(d[47]),"+f"(d[48]),"+f"(d[49]),"+f"(d[50]),"+f"(d[51]),"+f"(d[52]),"+f"(d[53]),"+f"(d[54]),"+f"(d[55]),"+f"(d[56]),"+f"(d[57]),"+f"(d[58]),"+f"(d[59]),"+f"(d[60]),"+f"(d[61]),"+f"(d[62]),"+f"(d[63]),"+f"(d[64]),"+f"(d[65]),"+f"(d[66]),"+f"(d[67]),"+f"(d[68]),"+f"(d[69]),"+f"(d[70]),"+f"(d[71]),"+f"(d[72]),"+f"(d[73]),"+f"(d[74]),"+f"(d[75]),"+f"(d[76]),"+f"(d[77]),"+f"(d[78]),"+f"(d[79]),"+f"(d[80]),"+f"(d[81]),"+f"(d[82]),"+f"(d[83]),"+f"(d[84]),"+f"(d[85]),"+f"(d[86]),"+f"(d[87]),"+f"(d[88]),"+f"(d[89]),"+f"(d[90]),"+f"(d[91]),"+f"(d[92]),"+f"(d[93]),"+f"(d[94]),"+f"(d[95])
    : "l"(da), "l"(db), "r"(scale_d));
}
__device__ __forceinline__ void wgmma_ss_n64_k(float (&d)[32], uint64_t da, uint64_t db, int scale_d) {
  asm volatile("{\n.reg .pred p;\nsetp.ne.b32 p, %34, 0;\n"
    "wgmma.mma_async.sync.aligned.m64n64k16.f32.bf16.bf16 {%0,%1,%2,%3,%4,%5,%6,%7,%8,%9,%10,%11,%12,%13,%14,%15,%16,%17,%18,%19,%20,%21,%22,%23,%24,%25,%26,%27,%28,%29,%30,%31}, %32, %33, p, 1, 1, 0, 0;\n}\n"
    : "+f"(d[0]),"+f"(d[1]),"+f"(d[2]),"+f"(d[3]),"+f"(d[4]),"+f"(d[5]),"+f"(d[6]),"+f"(d[7]),"+f"(d[8]),"+f"(d[9]),"+f"(d[10]),"+f"(d[11]),"+f"(d[12]),"+f"(d[13]),"+f"(d[14]),"+f"(d[15]),"+f"(d[16]),"+f"(d[17]),"+f"(d[18]),"+f"(d[19]),"+f"(d[20]),"+f"(d[21]),"+f"(d[22]),"+f"(d[23]),"+f"(d[24]),"+f"(d[25]),"+f"(d[26]),"+f"(d[27]),"+f"(d[28]),"+f"(d[29]),"+f"(d[30]),"+f"(d[31])
    : "l"(da), "l"(db), "r"(scale_d));
}
__device__ __forceinline__ void wgmma_rs_n24_tb(float (&d)[12], uint32_t a0, uint32_t a1, uint32_t a2, uint32_t a3, uint64_t db, int scale_d) {
  asm volatile("{\n.reg .pred p;\nsetp.ne.b32 p, %17, 0;\n"
    "wgmma.mma_async.sync.aligned.m64n24k16.f32.bf16.bf16 {%0,%1,%2,%3,%4,%5,%6,%7,%8,%9,%10,%11}, {%12,%13,%14,%15}, %16, p, 1, 1, 1;\n}\n"
    : "+f"(d[0]),"+f"(d[1]),"+f"(d[2]),"+f"(d[3]),"+f"(d[4]),"+f"(d[5]),"+f"(d[6]),"+f"(d[7]),"+f"(d[8]),"+f"(d[9]),"+f"(d[10]),"+f"(d[11])
    : "r"(a0), "r"(a1), "r"(a2), "r"(a3), "l"(db), "r"(scale_d));
}

constexpr int PRE_ROW_BLOCKS = 64;
constexpr int PRE_COL_BLOCKS = 3 * DM / 64;
__device__ __forceinline__ float2 ln_finish(float mean, float var) {
  float mb = bf_round(mean);
  float s = bf_round(sqrtf(bf_round(bf_round(var) + 1e-5f)));
  return make_float2(mb, 1.0f / s);
}
__device__ __forceinline__ void colsum64(const __nv_bfloat16* __restrict__ w, int ld, int c0, float* __restrict__ dst, float (*red)[65], int tid, int bar_id) {
  const int cg = tid & 7, r0 = tid >> 3;
  float acc[8];
#pragma unroll
  for (int i = 0; i < 8; i++) acc[i] = 0.f;
#pragma unroll 10
  for (int r = r0; r < DM; r += 32) {
    uint4 v = __ldg((const uint4*)(w + (size_t)r * ld + c0 + cg * 8));
    acc[0] += bf_lo(v.x); acc[1] += bf_hi(v.x); acc[2] += bf_lo(v.y); acc[3] += bf_hi(v.y);
    acc[4] += bf_lo(v.z); acc[5] += bf_hi(v.z); acc[6] += bf_lo(v.w); acc[7] += bf_hi(v.w);
  }
#pragma unroll
  for (int i = 0; i < 8; i++) red[r0][cg * 8 + i] = acc[i];
  named_bar(bar_id, 256);
  if (tid < 64) {
    float s = 0.f;
#pragma unroll
    for (int r = 0; r < 32; r++) s += red[r][tid];
    dst[c0 + tid] = s;
  }
  named_bar(bar_id, 256);
}
__global__ void __launch_bounds__(1024) pre_kernel(const __nv_bfloat16* __restrict__ x, const __nv_bfloat16* __restrict__ wqkv) {
  TS_BEGIN(0);
  pdl_launch();
  __shared__ float red[51][161];
  const int tid = threadIdx.x, lane = tid & 31, warp = tid >> 5;
  {
    const int ch = tid % 20, rl = tid / 20;
    if (rl < 51) {
      const __nv_bfloat16* w = wqkv + blockIdx.x * 160 + ch * 8;
      uint4 v[13];
#pragma unroll
      for (int i = 0; i < 13; i++) { const int r = rl + i * 51; v[i] = r < DM ? __ldg((const uint4*)(w + (size_t)r * (3 * DM))) : make_uint4(0, 0, 0, 0); }
      float acc[8];
#pragma unroll
      for (int i = 0; i < 8; i++) acc[i] = 0.f;
#pragma unroll
      for (int i = 0; i < 13; i++) {
        acc[0] += bf_lo(v[i].x); acc[1] += bf_hi(v[i].x); acc[2] += bf_lo(v[i].y); acc[3] += bf_hi(v[i].y);
        acc[4] += bf_lo(v[i].z); acc[5] += bf_hi(v[i].z); acc[6] += bf_lo(v[i].w); acc[7] += bf_hi(v[i].w);
      }
#pragma unroll
      for (int i = 0; i < 8; i++) red[rl][ch * 8 + i] = acc[i];
    }
  }
  const int rbeg = blockIdx.x * 171, rend = min(rbeg + 171, S_LEN);
  for (int row0 = rbeg + warp * 2; row0 < rend; row0 += 64) {
    uint4 v[2][3];
#pragma unroll
    for (int k = 0; k < 2; k++) {
      const int row = min(row0 + k, rend - 1);
      const uint4* p = (const uint4*)(x + (size_t)row * DM);
      v[k][0] = __ldg(p + lane); v[k][1] = __ldg(p + 32 + lane);
      v[k][2] = lane < 16 ? __ldg(p + 64 + lane) : make_uint4(0, 0, 0, 0);
    }
#pragma unroll
    for (int k = 0; k < 2; k++) {
      float f[24];
      const uint32_t u[12] = {v[k][0].x, v[k][0].y, v[k][0].z, v[k][0].w, v[k][1].x, v[k][1].y, v[k][1].z, v[k][1].w, v[k][2].x, v[k][2].y, v[k][2].z, v[k][2].w};
#pragma unroll
      for (int j = 0; j < 12; j++) { f[2 * j] = bf_lo(u[j]); f[2 * j + 1] = bf_hi(u[j]); }
      float s = 0.f;
#pragma unroll
      for (int j = 0; j < 24; j++) s += f[j];
#pragma unroll
      for (int o = 16; o; o >>= 1) s += __shfl_xor_sync(~0u, s, o);
      const float mean = s * (1.0f / DM);
      float q = 0.f;
#pragma unroll
      for (int j = 0; j < 16; j++) { const float d = f[j] - mean; q += d * d; }
      if (lane < 16) {
#pragma unroll
        for (int j = 16; j < 24; j++) { const float d = f[j] - mean; q += d * d; }
      }
#pragma unroll
      for (int o = 16; o; o >>= 1) q += __shfl_xor_sync(~0u, q, o);
      if (lane == 0 && row0 + k < rend) g_stat1[row0 + k] = ln_finish(mean, q * (1.0f / DM));
    }
  }
  __syncthreads();
  if (tid < 160) {
    float s = 0.f;
#pragma unroll 17
    for (int r = 0; r < 51; r++) s += red[r][tid];
    g_cs_qkv[blockIdx.x * 160 + tid] = s;
  }
  TS_END(0);
}

enum { EPI_QKV = 0, EPI_WO = 1, EPI_GLU = 2, EPI_DOWN = 3 };
template <int N> struct WG;
template <> struct WG<128> { static __device__ __forceinline__ void mma(float (&d)[64], uint64_t a, uint64_t b, int s) { wgmma_ss_n128(d, a, b, s); } };
template <> struct WG<192> { static __device__ __forceinline__ void mma(float (&d)[96], uint64_t a, uint64_t b, int s) { wgmma_ss_n192(d, a, b, s); } };

template <int BM, int BN, int NB, int STAGES> struct GemmCfg {
  static constexpr int A_BYTES = BM * 128;
  static constexpr int B_BYTES = NB * (BN / 64) * 8192;
  static constexpr int STAGE_BYTES = A_BYTES + B_BYTES;
  static constexpr int SMEM = STAGES * STAGE_BYTES + 1024   + 256   + 4096  ;
};

constexpr float QSCALE = 0.22360679774997896f * 1.4426950408889634f;

template <int BM, int BN, int NB, int KDIM, int STAGES, int EPI, int MINB, int CN, int CM>
__global__ void __launch_bounds__(EPI == EPI_GLU ? 384 : 288, MINB) gemm_kernel(const __grid_constant__ CUtensorMap tmA, const __grid_constant__ CUtensorMap tmB0,
                                                         const __grid_constant__ CUtensorMap tmB1,
                                                         const __nv_bfloat16* resid, __nv_bfloat16* out) {
  using Cfg = GemmCfg<BM, BN, NB, STAGES>;
  constexpr int MB = BM / 128;
  constexpr int KT = KDIM / 64;
  extern __shared__ uint8_t smem_raw[];
  const uint32_t sbase = (smem_u32(smem_raw) + 1023u) & ~1023u;
  uint8_t* sptr = smem_raw + (sbase - smem_u32(smem_raw));
  const uint32_t sbar = sbase + STAGES * Cfg::STAGE_BYTES;
  const int tid = threadIdx.x, warp = tid >> 5, lane = tid & 31;
  const int n0 = blockIdx.x * BN, m0 = blockIdx.y * BM;
  TS_BEGIN(EPI == EPI_QKV ? 1 : EPI + 2);
  TS_MID(EPI == EPI_QKV ? 1 : EPI + 2, 3);
  constexpr int NCL = CN + CM - 1;
  const int cx = blockIdx.x % CN, cy = blockIdx.y % CM;
  if (tid == 0) {
    for (int i = 0; i < STAGES; i++) { mbar_init(sbar + 8 * i, 1); mbar_init(sbar + 8 * (STAGES + i), 2 * NCL); }
    asm volatile("fence.mbarrier_init.release.cluster;" ::: "memory");
  }
  __syncthreads();
  if constexpr (CN * CM > 1) { cluster_arrive(); cluster_wait(); }
  pdl_launch();
  if (warp >= 8) {
    if constexpr (EPI == EPI_GLU) asm volatile("setmaxnreg.dec.sync.aligned.u32 40;");
    if (warp == 8 && lane == 0) {
      auto load_a = [&](int kt, int s) { tma_2d(sbase + s * Cfg::STAGE_BYTES, &tmA, kt * 64, m0, sbar + 8 * s); };
      auto load_b = [&](int kt, int s) {
        const uint32_t sb = sbase + s * Cfg::STAGE_BYTES + Cfg::A_BYTES;
        tma_3d(sb, &tmB0, 0, kt * 64, blockIdx.x * (BN / 64), sbar + 8 * s);
        if constexpr (NB == 2) tma_3d(sb + (BN / 64) * 8192, &tmB1, 0, kt * 64, blockIdx.x * (BN / 64), sbar + 8 * s);
      };
      if constexpr (EPI == EPI_QKV) {
        const int cta = blockIdx.y * gridDim.x + blockIdx.x;
        const uint32_t xb = S_LEN * DM * 2, xs = 21888;
        if (cta * xs < xb) asm volatile("cp.async.bulk.prefetch.L2.global [%0], %1;" :: "l"((const uint8_t*)resid + (size_t)cta * xs), "r"(min(xs, xb - cta * xs)));
        asm volatile("cp.async.bulk.prefetch.L2.global [%0], %1;" :: "l"((const uint8_t*)out + (size_t)cta * 20480), "r"(20480));
      }
      for (int s = 0; s < STAGES; s++) { mbar_expect_tx(sbar + 8 * s, Cfg::STAGE_BYTES); if (EPI != EPI_QKV || s == 0) load_b(s, s); }
      if (EPI != EPI_QKV) pdl_wait();
      for (int s = 0; s < STAGES; s++) { load_a(s, s); if (EPI == EPI_QKV && s > 0) load_b(s, s); }
      for (int kt = STAGES; kt < KT; kt++) {
        const int s = kt % STAGES;
        mbar_wait(sbar + 8 * (STAGES + s), ((kt / STAGES) - 1) & 1);
        mbar_expect_tx(sbar + 8 * s, Cfg::STAGE_BYTES);
        load_a(kt, s);
        load_b(kt, s);
      }
    }
    if constexpr (EPI == EPI_GLU) {
      if (warp > 8) {
        float2* s_st = (float2*)(sptr + STAGES * Cfg::STAGE_BYTES + 256);
        float* s_cs = (float*)(sptr + STAGES * Cfg::STAGE_BYTES + 256 + 1024);
        pdl_wait();
        for (int r = tid - 288; r < BM; r += 96) {
          const float2* pp = &g_part2[(m0 + r) * 8];
          float s = 0.f;
#pragma unroll
          for (int i = 0; i < 8; i++) s += pp[i].x;
          const float mean = s * (1.0f / DM);
          float q = 0.f;
#pragma unroll
          for (int i = 0; i < 8; i++) { const float2 p = pp[i]; const float d = p.x * (1.0f / 80.f) - mean; q += p.y + 80.f * d * d; }
          s_st[r] = ln_finish(mean, q * (1.0f / DM));
        }
        for (int c = tid - 288; c < BN; c += 96) { s_cs[c] = g_cs_g[n0 + c]; s_cs[BN + c] = g_cs_u[n0 + c]; }
        __threadfence_block();
        asm volatile("bar.arrive 2, 352;" ::: "memory");
      }
    }
    if constexpr (CN * CM > 1) { __syncwarp(); cluster_arrive(); cluster_wait(); }
    return;
  }
  if constexpr (EPI == EPI_GLU) asm volatile("setmaxnreg.inc.sync.aligned.u32 232;");
  const int wg = warp >> 2, g = lane >> 2, t = lane & 3;
  float acc[MB][NB][BN / 2];
#pragma unroll
  for (int mb = 0; mb < MB; mb++)
#pragma unroll
    for (int nb = 0; nb < NB; nb++)
#pragma unroll
      for (int i = 0; i < BN / 2; i++) acc[mb][nb][i] = 0.f;
  for (int kt = 0; kt < KT; kt++) {
    const int s = kt % STAGES;
    mbar_wait(sbar + 8 * s, (kt / STAGES) & 1);
    if (kt == 0) TS_MID(EPI == EPI_QKV ? 1 : EPI + 2, 0);
    const uint32_t sa = sbase + s * Cfg::STAGE_BYTES + wg * (MB * 64 * 128);
    const uint32_t sb = sbase + s * Cfg::STAGE_BYTES + Cfg::A_BYTES;
    wgmma_fence();
#pragma unroll
    for (int ks = 0; ks < 4; ks++) {
#pragma unroll
      for (int mb = 0; mb < MB; mb++) {
        const uint64_t da = make_desc(sa + mb * 8192 + ks * 32, 16, 1024, 1);
#pragma unroll
        for (int nb = 0; nb < NB; nb++) {
          const uint64_t db = make_desc(sb + nb * (BN / 64) * 8192 + ks * 2048, 8192, 1024, 1);
          WG<BN>::mma(acc[mb][nb], da, db, 1);
        }
      }
    }
    wgmma_commit();
    wgmma_wait<1>();
    if (kt > 0 && kt - 1 + STAGES < KT && (tid & 127) < NCL) {
      const uint32_t eb = sbar + 8 * (STAGES + (kt - 1) % STAGES);
      if constexpr (CN * CM > 1) {
        const int i = tid & 127;
        const uint32_t rank = i < CN ? cy * CN + i : ((i - CN + (i - CN >= cy ? 1 : 0)) * CN + cx);
        mbar_arrive_remote(eb, rank);
      } else mbar_arrive(eb);
    }
  }
  wgmma_wait<0>();
#pragma unroll
  for (int mb = 0; mb < MB; mb++)
#pragma unroll
    for (int nb = 0; nb < NB; nb++)
#pragma unroll
      for (int i = 0; i < BN / 2; i++) asm volatile("" : "+f"(acc[mb][nb][i]) :: "memory");
  if constexpr (CN * CM > 1) cluster_arrive();
  TS_MID(EPI == EPI_QKV ? 1 : EPI + 2, 1);
  pdl_wait();
  TS_MID(EPI == EPI_QKV ? 1 : EPI + 2, 2);
  named_bar(1, 256);
  constexpr int LDS = BN * 2 + 16;
  const int ctid = tid;

  if constexpr (EPI == EPI_QKV) {
    const int sec = n0 / DM;
    constexpr int lds = 264;
    __shared__ unsigned int s_kn[8];
    if (ctid < 8) s_kn[ctid] = 0u;
    if (blockIdx.x == 0 && blockIdx.y == 0 && ctid < 32) g_flag[ctid] = 0u;
    float2 cs[BN / 8];
#pragma unroll
    for (int j = 0; j < BN / 8; j++) cs[j] = *(const float2*)&g_cs_qkv[n0 + j * 8 + 2 * t];
#pragma unroll
    for (int mb = 0; mb < MB; mb++) {
      const int r0 = wg * (MB * 64) + mb * 64 + (warp & 3) * 16 + g;
      const float2 st0 = g_stat1[m0 + r0], st1 = g_stat1[m0 + r0 + 8];
      const float sc0 = sec == 0 ? st0.y * QSCALE : st0.y, sc1 = sec == 0 ? st1.y * QSCALE : st1.y;
#pragma unroll
      for (int j = 0; j < BN / 8; j++) {
        const float* a = &acc[mb][0][4 * j];
        *(uint32_t*)(sptr + r0 * lds + j * 16 + t * 4) = pack_bf16(fmaf(-st0.x, cs[j].x, a[0]) * sc0, fmaf(-st0.x, cs[j].y, a[1]) * sc0);
        *(uint32_t*)(sptr + (r0 + 8) * lds + j * 16 + t * 4) = pack_bf16(fmaf(-st1.x, cs[j].x, a[2]) * sc1, fmaf(-st1.x, cs[j].y, a[3]) * sc1);
      }
    }
    named_bar(1, 256);
    {
      const int cbase = n0 - sec * DM;
      const int hfirst = cbase / DH;
      const int j = m0 + ctid;
      uint8_t* dst = (uint8_t*)(sec == 0 ? g_q : (sec == 1 ? g_k : g_v)) + (size_t)(j >> 3) * (sec == 0 ? 512 : 384) + (j & 7) * 16;
      const uint8_t* row = sptr + ctid * 264;
#pragma unroll
      for (int i = 0; i < 8; i++) {
        const int hh = hfirst + i;
        const int cr = hh * DH - cbase;
        if (cr < BN) {
          uint2 v[5];
          bool in[5];
          float s = 0.f;
#pragma unroll
          for (int qd = 0; qd < 5; qd++) {
            const int c = cr + 4 * qd;
            in[qd] = c >= 0 && c < BN;
            v[qd] = in[qd] ? *(const uint2*)(row + c * 2) : make_uint2(0u, 0u);
            s += bf_lo(v[qd].x) * bf_lo(v[qd].x) + bf_hi(v[qd].x) * bf_hi(v[qd].x) + bf_lo(v[qd].y) * bf_lo(v[qd].y) + bf_hi(v[qd].y) * bf_hi(v[qd].y);
          }
          uint8_t* p = dst + (size_t)hh * (sec == 0 ? S_LEN * 64 : S_LEN * 48);
          if (in[0] && in[1]) st_g16(p, make_uint4(v[0].x, v[0].y, v[1].x, v[1].y));
          else if (in[0]) st_g8(p, v[0]);
          else if (in[1]) st_g8(p + 8, v[1]);
          if (in[2] && in[3]) st_g16(p + 128, make_uint4(v[2].x, v[2].y, v[3].x, v[3].y));
          else if (in[2]) st_g8(p + 128, v[2]);
          else if (in[3]) st_g8(p + 136, v[3]);
          if (in[4]) {
            st_g16(p + 256, make_uint4(v[4].x, v[4].y, sec == 0 ? 0u : 0x00003f80u, 0u));
            if (sec == 0) st_g16(p + 384, make_uint4(0u, 0u, 0u, 0u));
          }
          if (sec == 1) {
            const unsigned int mxb = __reduce_max_sync(~0u, __float_as_uint(s) & 0x7fffffffu);
            if (lane == 0) atomicMax(&s_kn[i], mxb);
          }
        }
      }
      if (sec == 1) {
        named_bar(1, 256);
        const int hh = hfirst + ctid;
        if (ctid < 8 && hh * DH < cbase + BN) {
          const bool starts_here = hh * DH >= cbase, ends_here = hh * DH + DH <= cbase + BN;
          const float v = __uint_as_float(s_kn[ctid]);
          float* o = &g_kn[(blockIdx.y * NH + hh) * 2];
          if (starts_here) { o[0] = v; if (ends_here) o[1] = 0.f; }
          else o[1] = v;
        }
      }
    }
  } else if constexpr (EPI == EPI_WO || EPI == EPI_DOWN) {
    const int r0 = wg * 64 + (warp & 3) * 16 + g;
#pragma unroll
    for (int j = 0; j < BN / 8; j++) {
      const float* a = &acc[0][0][4 * j];
      *(uint32_t*)(sptr + r0 * LDS + j * 16 + t * 4) = pack_bf16(a[0], a[1]);
      *(uint32_t*)(sptr + (r0 + 8) * LDS + j * 16 + t * 4) = pack_bf16(a[2], a[3]);
    }
    named_bar(1, 256);
#pragma unroll
    for (int i = 0; i < BM * (BN / 8) / 256; i++) {
      const int idx = i * 256 + ctid, r = idx / (BN / 8), c = idx % (BN / 8);
      const uint4 a = *(const uint4*)(sptr + r * LDS + c * 16);
      const size_t go = (size_t)(m0 + r) * DM + n0 + c * 8;
      const uint4 b = ld_g16(resid + go);
      uint4 o;
      o.x = pack_bf16(bf_lo(a.x) + bf_lo(b.x), bf_hi(a.x) + bf_hi(b.x));
      o.y = pack_bf16(bf_lo(a.y) + bf_lo(b.y), bf_hi(a.y) + bf_hi(b.y));
      o.z = pack_bf16(bf_lo(a.z) + bf_lo(b.z), bf_hi(a.z) + bf_hi(b.z));
      o.w = pack_bf16(bf_lo(a.w) + bf_lo(b.w), bf_hi(a.w) + bf_hi(b.w));
      st_g16(out + go, o);
      if constexpr (EPI == EPI_WO) {
        static_assert(BN == 64, "stats assume 8 lanes per row");
        const float f[8] = {bf_lo(o.x), bf_hi(o.x), bf_lo(o.y), bf_hi(o.y), bf_lo(o.z), bf_hi(o.z), bf_lo(o.w), bf_hi(o.w)};
        float s = 0.f;
#pragma unroll
        for (int k = 0; k < 8; k++) s += f[k];
        s += __shfl_xor_sync(~0u, s, 1); s += __shfl_xor_sync(~0u, s, 2); s += __shfl_xor_sync(~0u, s, 4);
        const float mu = s * (1.0f / 64.f);
        float q = 0.f;
#pragma unroll
        for (int k = 0; k < 8; k++) { const float d = f[k] - mu; q += d * d; }
        q += __shfl_xor_sync(~0u, q, 1); q += __shfl_xor_sync(~0u, q, 2); q += __shfl_xor_sync(~0u, q, 4);
        if (c == 0) g_part2[(m0 + r) * 10 + blockIdx.x] = make_float2(s, q);
      }
    }
  } else {
    const int r0 = wg * 64 + (warp & 3) * 16 + g;
    const float2* s_st = (const float2*)(sptr + STAGES * Cfg::STAGE_BYTES + 256);
    const float* s_cs = (const float*)(sptr + STAGES * Cfg::STAGE_BYTES + 256 + 1024);
    named_bar(2, 352);
    float2 st[2] = {s_st[r0], s_st[r0 + 8]};
#pragma unroll
    for (int j = 0; j < BN / 8; j++) {
      const float2 cg = *(const float2*)&s_cs[j * 8 + 2 * t], cu = *(const float2*)&s_cs[BN + j * 8 + 2 * t];
      const float* a = &acc[0][0][4 * j];
      const float* b = &acc[0][1][4 * j];
#pragma unroll
      for (int e = 0; e < 2; e++) {
        const float2 s_ = st[e];
        const uint32_t gp = pack_bf16(fmaf(-s_.x, cg.x, a[2 * e]) * s_.y, fmaf(-s_.x, cg.y, a[2 * e + 1]) * s_.y);
        const uint32_t up = pack_bf16(fmaf(-s_.x, cu.x, b[2 * e]) * s_.y, fmaf(-s_.x, cu.y, b[2 * e + 1]) * s_.y);
        uint32_t r;
        asm("{\n.reg .b32 z;\nmax.bf16x2 z, %1, %3;\nmul.rn.bf16x2 %0, z, %2;\n}" : "=r"(r) : "r"(gp), "r"(up), "r"(0u));
        *(uint32_t*)(sptr + (r0 + 8 * e) * LDS + j * 16 + t * 4) = r;
      }
    }
    named_bar(1, 256);
#pragma unroll
    for (int i = 0; i < BM * (BN / 8) / 256; i++) {
      const int idx = i * 256 + ctid, r = idx / (BN / 8), c = idx % (BN / 8);
      st_g16(out + (size_t)(m0 + r) * DFF + n0 + c * 8, *(const uint4*)(sptr + r * LDS + c * 16));
    }
  }
  if constexpr (CN * CM > 1) cluster_wait();
  TS_END(EPI == EPI_QKV ? 1 : EPI + 2);
}

constexpr int R_STAGES = 8;
constexpr int R_STAGE_BYTES = 16384 + 5 * 2048;
constexpr int R_BAR_OFF = R_STAGES * R_STAGE_BYTES;
constexpr int R_SMEM = R_BAR_OFF + 256 + 1024;
template <int KDIM, bool STATS>
__global__ void __launch_bounds__(288, 1) gemm_res_kernel(const __grid_constant__ CUtensorMap tmA, const __grid_constant__ CUtensorMap tmB,
                                                          const __nv_bfloat16* resid, __nv_bfloat16* out) {
  constexpr int KT = KDIM / 64;
  extern __shared__ uint8_t smem_raw[];
  const uint32_t sbase = (smem_u32(smem_raw) + 1023u) & ~1023u;
  uint8_t* sptr = smem_raw + (sbase - smem_u32(smem_raw));
  const uint32_t sbar = sbase + R_BAR_OFF;
  const int tid = threadIdx.x, warp = tid >> 5, lane = tid & 31;
  const int n0 = blockIdx.x * 80, m0 = blockIdx.y * 128;
  TS_BEGIN(STATS ? 3 : 5);
  if (tid == 0) {
    for (int i = 0; i < R_STAGES; i++) { mbar_init(sbar + 8 * i, 1); mbar_init(sbar + 8 * (R_STAGES + i), 2); }
    asm volatile("fence.mbarrier_init.release.cluster;" ::: "memory");
  }
  __syncthreads();
  pdl_launch();
  if (warp == 8) {
    if (lane == 0) {
      const uint8_t* wt = (const uint8_t*)(STATS ? g_wo_t : g_wd_t) + (size_t)blockIdx.x * KT * 10240;
      auto load_b = [&](int kt, int s) { bulk_g2s(sbase + s * R_STAGE_BYTES + 16384, wt + kt * 10240, 10240, sbar + 8 * s); };
      pdl_wait();
      for (int s = 0; s < R_STAGES; s++) { mbar_expect_tx(sbar + 8 * s, R_STAGE_BYTES); tma_2d(sbase + s * R_STAGE_BYTES, &tmA, s * 64, m0, sbar + 8 * s); load_b(s, s); }
      for (int kt = R_STAGES; kt < KT; kt++) {
        const int s = kt % R_STAGES;
        mbar_wait(sbar + 8 * (R_STAGES + s), ((kt / R_STAGES) - 1) & 1);
        mbar_expect_tx(sbar + 8 * s, R_STAGE_BYTES);
        tma_2d(sbase + s * R_STAGE_BYTES, &tmA, kt * 64, m0, sbar + 8 * s);
        load_b(kt, s);
      }
    }
    return;
  }
  const int wg = warp >> 2, g = lane >> 2, t = lane & 3;
  pdl_wait();
  uint4 rv[5];
#pragma unroll
  for (int i = 0; i < 5; i++) {
    const int idx = i * 256 + tid, r = idx / 10, c = idx % 10;
    rv[i] = ld_g16(resid + (size_t)(m0 + r) * DM + n0 + c * 8);
  }
  float acc[40];
#pragma unroll
  for (int i = 0; i < 40; i++) acc[i] = 0.f;
  for (int kt = 0; kt < KT; kt++) {
    const int s = kt % R_STAGES;
    mbar_wait(sbar + 8 * s, (kt / R_STAGES) & 1);
    if (kt == 0) TS_MID(STATS ? 3 : 5, 0);
    const uint32_t sa = sbase + s * R_STAGE_BYTES + wg * 8192;
    const uint32_t sb = sbase + s * R_STAGE_BYTES + 16384;
    wgmma_fence();
#pragma unroll
    for (int ks = 0; ks < 4; ks++)
      wgmma_ss_n80(acc, make_desc(sa + ks * 32, 16, 1024, 1), make_desc(sb + ks * 512, 2048, 256, 3), 1);
    wgmma_commit();
    wgmma_wait<1>();
    if (kt > 0 && kt - 1 + R_STAGES < KT && (tid & 127) == 0) mbar_arrive(sbar + 8 * (R_STAGES + (kt - 1) % R_STAGES));
  }
  wgmma_wait<0>();
#pragma unroll
  for (int i = 0; i < 40; i++) asm volatile("" : "+f"(acc[i]) :: "memory");
  TS_MID(STATS ? 3 : 5, 1);
  named_bar(1, 256);
  constexpr int LDS = 176;
  const int r0 = wg * 64 + (warp & 3) * 16 + g;
#pragma unroll
  for (int i = 0; i < 10; i++) {
    *(uint32_t*)(sptr + r0 * LDS + i * 16 + t * 4) = pack_bf16(acc[4 * i], acc[4 * i + 1]);
    *(uint32_t*)(sptr + (r0 + 8) * LDS + i * 16 + t * 4) = pack_bf16(acc[4 * i + 2], acc[4 * i + 3]);
  }
  named_bar(1, 256);
  TS_MID(STATS ? 3 : 5, 2);
#pragma unroll
  for (int i = 0; i < 5; i++) {
    const int idx = i * 256 + tid, r = idx / 10, c = idx % 10;
    const uint4 a = *(const uint4*)(sptr + r * LDS + c * 16);
    const uint4 b = rv[i];
    uint4 o;
    o.x = pack_bf16(bf_lo(a.x) + bf_lo(b.x), bf_hi(a.x) + bf_hi(b.x));
    o.y = pack_bf16(bf_lo(a.y) + bf_lo(b.y), bf_hi(a.y) + bf_hi(b.y));
    o.z = pack_bf16(bf_lo(a.z) + bf_lo(b.z), bf_hi(a.z) + bf_hi(b.z));
    o.w = pack_bf16(bf_lo(a.w) + bf_lo(b.w), bf_hi(a.w) + bf_hi(b.w));
    st_g16(out + (size_t)(m0 + r) * DM + n0 + c * 8, o);
    if constexpr (STATS) *(uint4*)(sptr + r * LDS + c * 16) = o;
  }
  TS_MID(STATS ? 3 : 5, 3);
  if constexpr (STATS) {
    named_bar(1, 256);
    const int r = tid >> 1, hf = tid & 1;
    float f[40];
#pragma unroll
    for (int i = 0; i < 5; i++) {
      const uint4 v = *(const uint4*)(sptr + r * LDS + hf * 80 + i * 16);
      f[8 * i] = bf_lo(v.x); f[8 * i + 1] = bf_hi(v.x); f[8 * i + 2] = bf_lo(v.y); f[8 * i + 3] = bf_hi(v.y);
      f[8 * i + 4] = bf_lo(v.z); f[8 * i + 5] = bf_hi(v.z); f[8 * i + 6] = bf_lo(v.w); f[8 * i + 7] = bf_hi(v.w);
    }
    float s = 0.f;
#pragma unroll
    for (int i = 0; i < 40; i++) s += f[i];
    s += __shfl_xor_sync(~0u, s, 1);
    const float mu = s * (1.0f / 80.f);
    float q = 0.f;
#pragma unroll
    for (int i = 0; i < 40; i++) { const float d = f[i] - mu; q += d * d; }
    q += __shfl_xor_sync(~0u, q, 1);
    if (hf == 0) g_part2[(m0 + r) * 8 + blockIdx.x] = make_float2(s, q);
  }
  TS_END(STATS ? 3 : 5);
}

#define F_MC 0
constexpr int F_CST = 7, F_DST = 3, F_EST = 5;
constexpr int F_RS = 16384 + 5 * 2048;
constexpr int F_DS = 16384 + 6 * 8192;
constexpr int F_E_OFF = 53248;
constexpr int F_STG_OFF = F_DST * F_DS;
constexpr int F_BAR_OFF = F_STG_OFF + 128 * 176;
constexpr int F_VEC_OFF = F_BAR_OFF + 256;
constexpr int F_SMEM = F_VEC_OFF + 1024 + 1536 + 1024;

__device__ __forceinline__ void flag_wait(const unsigned int* f, unsigned int target) {
  unsigned int v, spins = 0;
  do { asm volatile("ld.acquire.gpu.global.u32 %0, [%1];" : "=r"(v) : "l"(f) : "memory"); } while (v < target && ++spins < (1u << 22));
  asm volatile("fence.proxy.async;" ::: "memory");
}
__device__ __forceinline__ void flag_signal(unsigned int* f) {
  asm volatile("fence.proxy.async;" ::: "memory");
  asm volatile("red.release.gpu.global.add.u32 [%0], 1;" :: "l"(f) : "memory");
}

template <bool STATS>
__device__ __forceinline__ void res_epilogue(float (&acc)[40], const uint4 (&rv)[5], uint8_t* stg, __nv_bfloat16* out, int m0, int n0, int tid, int bx) {
  constexpr int LDS = 176;
  const int warp = tid >> 5, lane = tid & 31;
  const int r0 = (warp >> 2) * 64 + (warp & 3) * 16 + (lane >> 2), t = lane & 3;
#pragma unroll
  for (int i = 0; i < 10; i++) {
    *(uint32_t*)(stg + r0 * LDS + i * 16 + t * 4) = pack_bf16(acc[4 * i], acc[4 * i + 1]);
    *(uint32_t*)(stg + (r0 + 8) * LDS + i * 16 + t * 4) = pack_bf16(acc[4 * i + 2], acc[4 * i + 3]);
  }
  named_bar(1, 256);
#pragma unroll
  for (int i = 0; i < 5; i++) {
    const int idx = i * 256 + tid, r = idx / 10, c = idx % 10;
    const uint4 a = *(const uint4*)(stg + r * LDS + c * 16);
    const uint4 b = rv[i];
    uint4 o;
    o.x = pack_bf16(bf_lo(a.x) + bf_lo(b.x), bf_hi(a.x) + bf_hi(b.x));
    o.y = pack_bf16(bf_lo(a.y) + bf_lo(b.y), bf_hi(a.y) + bf_hi(b.y));
    o.z = pack_bf16(bf_lo(a.z) + bf_lo(b.z), bf_hi(a.z) + bf_hi(b.z));
    o.w = pack_bf16(bf_lo(a.w) + bf_lo(b.w), bf_hi(a.w) + bf_hi(b.w));
    st_g16(out + (size_t)(m0 + r) * DM + n0 + c * 8, o);
    if constexpr (STATS) *(uint4*)(stg + r * LDS + c * 16) = o;
  }
  if constexpr (STATS) {
    named_bar(1, 256);
    const int r = tid >> 1, hf = tid & 1;
    float f[40];
#pragma unroll
    for (int i = 0; i < 5; i++) {
      const uint4 v = *(const uint4*)(stg + r * LDS + hf * 80 + i * 16);
      f[8 * i] = bf_lo(v.x); f[8 * i + 1] = bf_hi(v.x); f[8 * i + 2] = bf_lo(v.y); f[8 * i + 3] = bf_hi(v.y);
      f[8 * i + 4] = bf_lo(v.z); f[8 * i + 5] = bf_hi(v.z); f[8 * i + 6] = bf_lo(v.w); f[8 * i + 7] = bf_hi(v.w);
    }
    float s = 0.f;
#pragma unroll
    for (int i = 0; i < 40; i++) s += f[i];
    s += __shfl_xor_sync(~0u, s, 1);
    const float mu = s * (1.0f / 80.f);
    float q = 0.f;
#pragma unroll
    for (int i = 0; i < 40; i++) { const float d = f[i] - mu; q += d * d; }
    q += __shfl_xor_sync(~0u, q, 1);
    if (hf == 0) g_part2[(m0 + r) * 8 + bx] = make_float2(s, q);
  }
}

__global__ void __launch_bounds__(384, 1) post_kernel(const __grid_constant__ CUtensorMap tmO, const __grid_constant__ CUtensorMap tmWo,
                                                      const __grid_constant__ CUtensorMap tmH, const __grid_constant__ CUtensorMap tmWg,
                                                      const __grid_constant__ CUtensorMap tmWu, const __grid_constant__ CUtensorMap tmAct,
                                                      const __grid_constant__ CUtensorMap tmWd, const __nv_bfloat16* x, __nv_bfloat16* out) {
  extern __shared__ uint8_t smem_raw[];
  const uint32_t sbase = (smem_u32(smem_raw) + 1023u) & ~1023u;
  uint8_t* sptr = smem_raw + (sbase - smem_u32(smem_raw));
  const uint32_t bC = sbase + F_BAR_OFF, bD = bC + 16 * F_CST, bE = bD + 16 * F_DST;
  const int tid = threadIdx.x, warp = tid >> 5, lane = tid & 31;
  const int bx = blockIdx.x, rb = blockIdx.y, m0 = rb * 128, cx = bx & 1;
  TS_BEGIN(3);
  if (tid == 0) {
    for (int i = 0; i < F_CST; i++) { mbar_init(bC + 8 * i, 1); mbar_init(bC + 8 * (F_CST + i), F_MC ? 4 : 2); }
    for (int i = 0; i < F_DST; i++) { mbar_init(bD + 8 * i, 1); mbar_init(bD + 8 * (F_DST + i), F_MC ? 4 : 2); }
    for (int i = 0; i < F_EST; i++) { mbar_init(bE + 8 * i, 1); mbar_init(bE + 8 * (F_EST + i), F_MC ? 4 : 2); }
    asm volatile("fence.mbarrier_init.release.cluster;" ::: "memory");
  }
  __syncthreads();
  if (F_MC) { cluster_arrive(); cluster_wait(); }
  if (warp >= 8) {
    asm volatile("setmaxnreg.dec.sync.aligned.u32 40;");
    if (warp == 8) {
      if (lane == 0) {
        auto load_a = [&](const CUtensorMap* tm, uint32_t stage, int kt, uint32_t bar) {
          if (F_MC) tma_2d_mc(stage + cx * 8192, tm, kt * 64, m0 + cx * 64, bar, (uint16_t)3); else tma_2d(stage, tm, kt * 64, m0, bar);
        };
        for (int s = 0; s < F_CST; s++) { mbar_expect_tx(bC + 8 * s, F_RS); if (s < 3) tma_3d(sbase + s * F_RS + 16384, &tmWo, 0, s * 64, bx * 5, bC + 8 * s); }
        pdl_wait();
        for (int s = 0; s < F_CST; s++) { load_a(&tmO, sbase + s * F_RS, s, bC + 8 * s); if (s >= 3) tma_3d(sbase + s * F_RS + 16384, &tmWo, 0, s * 64, bx * 5, bC + 8 * s); }
        for (int kt = F_CST; kt < 10; kt++) {
          const int s = kt - F_CST;
          mbar_wait(bC + 8 * (F_CST + s), 0);
          mbar_expect_tx(bC + 8 * s, F_RS);
          load_a(&tmO, sbase + s * F_RS, kt, bC + 8 * s);
          tma_3d(sbase + s * F_RS + 16384, &tmWo, 0, kt * 64, bx * 5, bC + 8 * s);
        }
        auto load_bd = [&](int kt, int s) {
          tma_3d(sbase + s * F_DS + 16384, &tmWg, 0, kt * 64, bx * 3, bD + 8 * s);
          tma_3d(sbase + s * F_DS + 16384 + 3 * 8192, &tmWu, 0, kt * 64, bx * 3, bD + 8 * s);
        };
        for (int s = 0; s < F_DST; s++) { mbar_wait(bD + 8 * (F_DST + s), 0); mbar_expect_tx(bD + 8 * s, F_DS); load_bd(s, s); }
        flag_wait(&g_flag[rb], 8);
        for (int s = 0; s < F_DST; s++) load_a(&tmH, sbase + s * F_DS, s, bD + 8 * s);
        for (int kt = F_DST; kt < 10; kt++) {
          const int s = kt % F_DST;
          mbar_wait(bD + 8 * (F_DST + s), (kt / F_DST) & 1);
          mbar_expect_tx(bD + 8 * s, F_DS);
          load_a(&tmH, sbase + s * F_DS, kt, bD + 8 * s);
          load_bd(kt, s);
        }
        const uint32_t eb = sbase + F_E_OFF;
        for (int s = 0; s < F_EST; s++) { mbar_wait(bE + 8 * (F_EST + s), 0); mbar_expect_tx(bE + 8 * s, F_RS); tma_3d(eb + s * F_RS + 16384, &tmWd, 0, s * 64, bx * 5, bE + 8 * s); }
        flag_wait(&g_flag[16 + rb], 8);
        for (int s = 0; s < F_EST; s++) load_a(&tmAct, eb + s * F_RS, s, bE + 8 * s);
        for (int kt = F_EST; kt < 24; kt++) {
          const int s = kt % F_EST;
          mbar_wait(bE + 8 * (F_EST + s), (kt / F_EST) & 1);
          mbar_expect_tx(bE + 8 * s, F_RS);
          load_a(&tmAct, eb + s * F_RS, kt, bE + 8 * s);
          tma_3d(eb + s * F_RS + 16384, &tmWd, 0, kt * 64, bx * 5, bE + 8 * s);
        }
      }
    } else {
      float2* s_st = (float2*)(sptr + F_VEC_OFF);
      float* s_cs = (float*)(sptr + F_VEC_OFF + 1024);
      pdl_wait();
      for (int c = tid - 288; c < 192; c += 96) { s_cs[c] = g_cs_g[bx * 192 + c]; s_cs[192 + c] = g_cs_u[bx * 192 + c]; }
      flag_wait(&g_flag[rb], 8);
      for (int r = tid - 288; r < 128; r += 96) {
        const float2* pp = &g_part2[(m0 + r) * 8];
        float2 p[8];
        float s = 0.f;
#pragma unroll
        for (int i = 0; i < 8; i++) { asm volatile("ld.global.v2.f32 {%0, %1}, [%2];" : "=f"(p[i].x), "=f"(p[i].y) : "l"(pp + i) : "memory"); s += p[i].x; }
        const float mean = s * (1.0f / DM);
        float q = 0.f;
#pragma unroll
        for (int i = 0; i < 8; i++) { const float d = p[i].x * (1.0f / 80.f) - mean; q += p[i].y + 80.f * d * d; }
        s_st[r] = ln_finish(mean, q * (1.0f / DM));
      }
      __threadfence_block();
      asm volatile("bar.arrive 2, 352;" ::: "memory");
    }
    if (F_MC) { __syncwarp(); cluster_arrive(); cluster_wait(); }
    return;
  }
  asm volatile("setmaxnreg.inc.sync.aligned.u32 232;");
  const int wg = warp >> 2, g = lane >> 2, t = lane & 3;
  auto release = [&](uint32_t bar) { if (F_MC) { if ((tid & 127) < 2) mbar_arrive_remote(bar, (tid & 127) ^ cx); } else if ((tid & 127) == 0) mbar_arrive(bar); };
  const int n0 = bx * 80;
  uint4 rv[5];
  pdl_wait();
  {
#pragma unroll
    for (int i = 0; i < 5; i++) { const int idx = i * 256 + tid, r = idx / 10, c = idx % 10; rv[i] = ld_g16(x + (size_t)(m0 + r) * DM + n0 + c * 8); }
    float acc[40];
#pragma unroll
    for (int i = 0; i < 40; i++) acc[i] = 0.f;
    for (int kt = 0; kt < 10; kt++) {
      const int s = kt % F_CST;
      mbar_wait(bC + 8 * s, kt / F_CST);
      if (kt == 0) TS_MID(3, 0);
      const uint32_t sa = sbase + s * F_RS + wg * 8192, sb = sbase + s * F_RS + 16384;
      wgmma_fence();
#pragma unroll
      for (int ks = 0; ks < 4; ks++) wgmma_ss_n80(acc, make_desc(sa + ks * 32, 16, 1024, 1), make_desc(sb + ks * 512, 2048, 256, 3), 1);
      wgmma_commit();
      wgmma_wait<1>();
      if (kt > 0 && kt - 1 + F_CST < 10) release(bC + 8 * (F_CST + kt - 1));
    }
    wgmma_wait<0>();
#pragma unroll
    for (int i = 0; i < 40; i++) asm volatile("" : "+f"(acc[i]) :: "memory");
    for (int s = 0; s < F_DST; s++) release(bD + 8 * (F_DST + s));
    TS_MID(3, 1);
    res_epilogue<true>(acc, rv, sptr + F_STG_OFF, g_h, m0, n0, tid, bx);
    __threadfence();
    named_bar(1, 256);
    if (tid == 0) flag_signal(&g_flag[rb]);
    TS_END(3);
  }
  {
    float acc[2][96];
#pragma unroll
    for (int i = 0; i < 96; i++) { acc[0][i] = 0.f; acc[1][i] = 0.f; }
    for (int kt = 0; kt < 10; kt++) {
      const int s = kt % F_DST;
      mbar_wait(bD + 8 * s, (kt / F_DST) & 1);
      if (kt == 0) TS_MID(4, 0);
      const uint32_t sa = sbase + s * F_DS + wg * 8192, sb = sbase + s * F_DS + 16384;
      wgmma_fence();
#pragma unroll
      for (int ks = 0; ks < 4; ks++) {
        const uint64_t da = make_desc(sa + ks * 32, 16, 1024, 1);
        wgmma_ss_n192(acc[0], da, make_desc(sb + ks * 2048, 8192, 1024, 1), 1);
        wgmma_ss_n192(acc[1], da, make_desc(sb + 3 * 8192 + ks * 2048, 8192, 1024, 1), 1);
      }
      wgmma_commit();
      wgmma_wait<1>();
      if (kt > 0 && kt - 1 + F_DST < 10) release(bD + 8 * (F_DST + (kt - 1) % F_DST));
    }
    wgmma_wait<0>();
#pragma unroll
    for (int i = 0; i < 96; i++) { asm volatile("" : "+f"(acc[0][i]) :: "memory"); asm volatile("" : "+f"(acc[1][i]) :: "memory"); }
    for (int s = 0; s < F_EST; s++) release(bE + 8 * (F_EST + s));
    TS_MID(4, 1);
    named_bar(1, 256);
    named_bar(2, 352);
    constexpr int LDS = 400;
    const float2* s_st = (const float2*)(sptr + F_VEC_OFF);
    const float* s_cs = (const float*)(sptr + F_VEC_OFF + 1024);
    const int r0 = wg * 64 + (warp & 3) * 16 + g;
    const float2 st[2] = {s_st[r0], s_st[r0 + 8]};
#pragma unroll
    for (int j = 0; j < 24; j++) {
      const float2 cg = *(const float2*)&s_cs[j * 8 + 2 * t], cu = *(const float2*)&s_cs[192 + j * 8 + 2 * t];
      const float* a = &acc[0][4 * j];
      const float* b = &acc[1][4 * j];
#pragma unroll
      for (int e = 0; e < 2; e++) {
        const float2 s_ = st[e];
        const uint32_t gp = pack_bf16(fmaf(-s_.x, cg.x, a[2 * e]) * s_.y, fmaf(-s_.x, cg.y, a[2 * e + 1]) * s_.y);
        const uint32_t up = pack_bf16(fmaf(-s_.x, cu.x, b[2 * e]) * s_.y, fmaf(-s_.x, cu.y, b[2 * e + 1]) * s_.y);
        uint32_t r;
        asm("{\n.reg .b32 z;\nmax.bf16x2 z, %1, %3;\nmul.rn.bf16x2 %0, z, %2;\n}" : "=r"(r) : "r"(gp), "r"(up), "r"(0u));
        *(uint32_t*)(sptr + (r0 + 8 * e) * LDS + j * 16 + t * 4) = r;
      }
    }
    named_bar(1, 256);
#pragma unroll
    for (int i = 0; i < 12; i++) {
      const int idx = i * 256 + tid, r = idx / 24, c = idx % 24;
      st_g16(g_act + (size_t)(m0 + r) * DFF + bx * 192 + c * 8, *(const uint4*)(sptr + r * LDS + c * 16));
    }
    __threadfence();
    named_bar(1, 256);
    if (tid == 0) flag_signal(&g_flag[16 + rb]);
    TS_END(4);
  }
  {
#pragma unroll
    for (int i = 0; i < 5; i++) { const int idx = i * 256 + tid, r = idx / 10, c = idx % 10; rv[i] = ld_g16(g_h + (size_t)(m0 + r) * DM + n0 + c * 8); }
    float acc[40];
#pragma unroll
    for (int i = 0; i < 40; i++) acc[i] = 0.f;
    const uint32_t eb = sbase + F_E_OFF;
    for (int kt = 0; kt < 24; kt++) {
      const int s = kt % F_EST;
      mbar_wait(bE + 8 * s, (kt / F_EST) & 1);
      if (kt == 0) TS_MID(5, 0);
      const uint32_t sa = eb + s * F_RS + wg * 8192, sb = eb + s * F_RS + 16384;
      wgmma_fence();
#pragma unroll
      for (int ks = 0; ks < 4; ks++) wgmma_ss_n80(acc, make_desc(sa + ks * 32, 16, 1024, 1), make_desc(sb + ks * 512, 2048, 256, 3), 1);
      wgmma_commit();
      wgmma_wait<1>();
      if (kt > 0 && kt - 1 + F_EST < 24) release(bE + 8 * (F_EST + (kt - 1) % F_EST));
    }
    wgmma_wait<0>();
#pragma unroll
    for (int i = 0; i < 40; i++) asm volatile("" : "+f"(acc[i]) :: "memory");
    if (F_MC) cluster_arrive();
    TS_MID(5, 1);
    res_epilogue<false>(acc, rv, sptr + F_STG_OFF, out, m0, n0, tid, bx);
    if (F_MC) cluster_wait();
    TS_END(5);
  }
}

#define POLY_NUM 5
__device__ __forceinline__ float ex2_poly(float x, int shl23) {
  const float MAGIC = 12582912.f;
  const float tt = x + MAGIC;
  const float f = x - (tt - MAGIC);
  float p = fmaf(0.0013276472454890609f, f, 0.009675540961325169f);
  p = fmaf(p, f, 0.05550713092088699f);
  p = fmaf(p, f, 0.24022120237350464f);
  p = fmaf(p, f, 0.6931469440460205f);
  p = fmaf(p, f, 1.0000001192092896f);
  return __int_as_float(__float_as_int(tt) * shl23 + __float_as_int(p));
}
constexpr int KV_BYTES = S_LEN * 48;
constexpr int ATT_SMEM = 2 * KV_BYTES + 256 + 32768;
constexpr int ATT_BODY = 8;

__global__ void __launch_bounds__(512, 1) attn_kernel(int shl23, const __nv_bfloat16* __restrict__ wg_, const __nv_bfloat16* __restrict__ wu_,
                                                      const __grid_constant__ CUtensorMap tmWo, const __grid_constant__ CUtensorMap tmWd) {
  extern __shared__ __align__(1024) uint8_t smem[];
  if (blockIdx.x >= 128) {
    pdl_launch();
    const int e = blockIdx.x - 128, half = threadIdx.x >> 8;
    TS_MID(0, 0);
    const uint32_t sb = smem_u32(smem), bar = sb + 200 * 1024;
    auto rt_load = [&](int rd) {
      mbar_expect_tx(bar, 17 * 10240);
      for (int i = 0; i < 17; i++) {
        const int tl = e * 68 + rd * 17 + i;
        if (tl >= 80) tma_3d(sb + i * 10240, &tmWd, 0, ((tl - 80) % 24) * 64, ((tl - 80) / 24) * 5, bar);
        else tma_3d(sb + i * 10240, &tmWo, 0, (tl % 10) * 64, (tl / 10) * 5, bar);
      }
    };
    auto rt_store = [&](int rd) {
      mbar_wait(bar, rd & 1);
      for (int i = 0; i < 17; i++) {
        const int tl = e * 68 + rd * 17 + i;
        uint8_t* dst = tl >= 80 ? (uint8_t*)g_wd_t + (size_t)(tl - 80) * 10240 : (uint8_t*)g_wo_t + (size_t)tl * 10240;
        asm volatile("cp.async.bulk.global.shared::cta.bulk_group [%0], [%1], %2;" :: "l"(dst), "r"(sb + i * 10240), "r"(10240) : "memory");
      }
      asm volatile("cp.async.bulk.commit_group;" ::: "memory");
      asm volatile("cp.async.bulk.wait_group.read 0;" ::: "memory");
    };
    if (threadIdx.x == 0) {
      mbar_init(bar, 1);
      asm volatile("fence.mbarrier_init.release.cluster;" ::: "memory");
      rt_load(0);
    }
    __syncwarp();
    float (*red)[65] = (float (*)[65])(smem + 176 * 1024 + half * 10240);
    for (int i = 0; i < 6; i++) {
      const int b = e * 12 + half + 2 * i;
      if (b < 24) colsum64(wg_, DFF, b * 64, g_cs_g, red, threadIdx.x & 255, 1 + half);
      else colsum64(wu_, DFF, (b - 24) * 64, g_cs_u, red, threadIdx.x & 255, 1 + half);
      if ((i & 1) && threadIdx.x == 0) { rt_store(i >> 1); rt_load((i >> 1) + 1); }
      __syncwarp();
    }
    if (threadIdx.x == 0) { rt_store(3); asm volatile("cp.async.bulk.wait_group 0;" ::: "memory"); }
    TS_MID(0, 2);
    return;
  }
  const int h = blockIdx.x >> 2, qb = blockIdx.x & 3;
  const uint32_t sK = smem_u32(smem), sV = sK + KV_BYTES, sBar = sV + KV_BYTES;
  const int tid = threadIdx.x;
  TS_BEGIN(2);
  if (tid == 0) {
    for (int i = 0; i < 9; i++) mbar_init(sBar + 8 * i, 1);
    asm volatile("fence.mbarrier_init.release.cluster;" ::: "memory");
  }
  __syncthreads();
  pdl_launch();
  pdl_wait();
  TS_MID(2, 0);
  const uint8_t* gk = (const uint8_t*)(g_k + (size_t)h * S_LEN * 24);
  const uint8_t* gv = (const uint8_t*)(g_v + (size_t)h * S_LEN * 24);
  auto load_kv = [&](int i0, int i1) {
    for (int i = i0; i < i1; i++) {
      mbar_expect_tx(sBar + 8 * i, 2 * 12288);
      bulk_g2s(sK + i * 12288, gk + i * 12288, 12288, sBar + 8 * i);
      bulk_g2s(sV + i * 12288, gv + i * 12288, 12288, sBar + 8 * i);
    }
  };
  if (tid == 0) {
    mbar_expect_tx(sBar + 64, 32768);
    bulk_g2s(sBar + 256, (const uint8_t*)g_q + ((size_t)h * S_LEN + qb * 512) * 64, 32768, sBar + 64);
    load_kv(0, 2);
  }
  float ka = 0.f, kb = 0.f;
#pragma unroll
  for (int i = 0; i < 8; i++) {
    const float2 v = *(const float2*)&g_kn[(i * NH + h) * 2];
    ka = (v.x > ka || v.x != v.x) ? v.x : ka;
    kb = (v.y > kb || v.y != v.y) ? v.y : kb;
  }
  bool fast;
  {
    const float kn = sqrtf(ka + kb);
    mbar_wait(sBar + 64, 0);
    if (tid == 0) load_kv(2, 8);
    uint8_t* qrow = smem + 2 * KV_BYTES + 256 + (tid >> 3) * 512 + (tid & 7) * 16;
    const uint4 c0 = *(const uint4*)qrow, c1 = *(const uint4*)(qrow + 128);
    const uint2 c2 = *(const uint2*)(qrow + 256);
    auto sq = [](uint32_t u) { const float a = bf_lo(u), b = bf_hi(u); return a * a + b * b; };
    const float n2 = sq(c0.x) + sq(c0.y) + sq(c0.z) + sq(c0.w) + sq(c1.x) + sq(c1.y) + sq(c1.z) + sq(c1.w) + sq(c2.x) + sq(c2.y);
    const float m = ceilf(sqrtf(n2) * kn * 1.001f) + 1.f;
    fast = __syncthreads_or(!(m <= 62.f)) == 0;
    if (fast) *(uint32_t*)(qrow + 256 + 8) = pack_bf16(-m, 0.f);
    asm volatile("fence.proxy.async.shared::cta;" ::: "memory");
    __syncthreads();
  }
  auto write_out = [&](float (&O)[12], int it) {
    uint32_t tid2;
    asm volatile("mov.u32 %0, %%tid.x;" : "=r"(tid2));
    const int lane2 = tid2 & 31, t2 = lane2 & 3;
    const int qq = (blockIdx.x & 3) * 512 + (it * 4 + (tid2 >> 7)) * 64 + ((tid2 >> 5) & 3) * 16 + (lane2 >> 2);
    const float l0 = __shfl_sync(~0u, O[8], (lane2 & ~3) | 2), l1 = __shfl_sync(~0u, O[10], (lane2 & ~3) | 2);
    const float r0 = 1.f / l0, r1 = 1.f / l1;
    uint32_t* o0 = (uint32_t*)(g_o + (size_t)qq * DM + (blockIdx.x >> 2) * DH);
    uint32_t* o1 = o0 + 8 * DM / 2;
    o0[t2] = pack_bf16(O[0] * r0, O[1] * r0); o1[t2] = pack_bf16(O[2] * r1, O[3] * r1);
    o0[t2 + 4] = pack_bf16(O[4] * r0, O[5] * r0); o1[t2 + 4] = pack_bf16(O[6] * r1, O[7] * r1);
    if (t2 < 2) { o0[t2 + 8] = pack_bf16(O[8] * r0, O[9] * r0); o1[t2 + 8] = pack_bf16(O[10] * r1, O[11] * r1); }
  };
  TS_MID(2, 1);
  if (fast) {
#pragma unroll 1
    for (int it = 0; it < 2; it++) {
      const uint64_t dq = make_desc(sBar + 256 + (it * 4 + (tid >> 7)) * 4096, 128, 512, 0);
      float O[12];
#pragma unroll
      for (int i = 0; i < 12; i++) { O[i] = 0.f; asm volatile("" : "+f"(O[i]) :: "memory"); }
      float S[2][32];
      uint32_t P[16];
#pragma unroll 1
      for (int jb = 0; jb < 32 / ATT_BODY; jb++) {
        if (it == 0) { for (int c = 0; c < ATT_BODY / 4; c++) mbar_wait(sBar + 8 * (jb * (ATT_BODY / 4) + c), 0); }
        const uint64_t dk0 = make_desc(sK + jb * ATT_BODY * 8 * 384, 128, 384, 0);
        const uint64_t dv0 = make_desc(sV + jb * ATT_BODY * 8 * 384, 384, 128, 0);
        wgmma_fence();
        wgmma_ss_n64_k(S[0], dq, dk0, 0);
        wgmma_ss_n64_k(S[0], dq + (256 >> 4), dk0 + (256 >> 4), 1);
        wgmma_commit();
#pragma unroll
        for (int u = 0; u < ATT_BODY; u++) {
          if (u + 1 < ATT_BODY) {
            const uint64_t dk = dk0 + (((u + 1) * 8 * 384) >> 4);
            wgmma_fence();
            wgmma_ss_n64_k(S[(u + 1) & 1], dq, dk, 0);
            wgmma_ss_n64_k(S[(u + 1) & 1], dq + (256 >> 4), dk + (256 >> 4), 1);
            wgmma_commit();
          }
          if (u == 0 || u == ATT_BODY - 1) wgmma_wait<1>(); else wgmma_wait<2>();
#pragma unroll
          for (int i = 0; i < 32; i++) asm volatile("" : "+f"(S[u & 1][i]) :: "memory");
          const uint64_t dv = dv0 + ((u * 8 * 384) >> 4);
#pragma unroll
          for (int hf = 0; hf < 2; hf++) {
            if (hf == 1 && u > 0) { if (u == ATT_BODY - 1) wgmma_wait<1>(); else wgmma_wait<2>(); }
#pragma unroll
            for (int i = hf * 8; i < hf * 8 + 8; i++) {
              const bool usepoly = ((i + 1) * POLY_NUM / 16) != (i * POLY_NUM / 16);
              float a, b;
              if (usepoly) { a = ex2_poly(S[u & 1][2 * i], shl23); b = ex2_poly(S[u & 1][2 * i + 1], shl23); }
              else { a = ex2_mufu(S[u & 1][2 * i]); b = ex2_mufu(S[u & 1][2 * i + 1]); }
              P[i] = pack_bf16(a, b);
            }
            wgmma_fence();
#pragma unroll
            for (int ks = hf * 2; ks < hf * 2 + 2; ks++)
              wgmma_rs_n24_tb(O, P[4 * ks], P[4 * ks + 1], P[4 * ks + 2], P[4 * ks + 3], dv + ((ks * 768) >> 4), 1);
            wgmma_commit();
          }
        }
        wgmma_wait<0>();
      }
#pragma unroll
      for (int i = 0; i < 12; i++) asm volatile("" : "+f"(O[i]) :: "memory");
      write_out(O, it);
      if (it == 0) TS_MID(2, 2);
    }
  } else {
#pragma unroll 1
    for (int it = 0; it < 2; it++) {
      const uint64_t dq = make_desc(sBar + 256 + (it * 4 + (tid >> 7)) * 4096, 128, 512, 0);
      float O[12];
#pragma unroll
      for (int i = 0; i < 12; i++) { O[i] = 0.f; asm volatile("" : "+f"(O[i]) :: "memory"); }
      float S[32];
      float mx0 = -INFINITY, mx1 = -INFINITY;
#pragma unroll 1
      for (int j = 0; j < 32; j++) {
        if (it == 0 && (j & 3) == 0) mbar_wait(sBar + 8 * (j >> 2), 0);
        const uint64_t dk = make_desc(sK + j * 8 * 384, 128, 384, 0);
        wgmma_fence();
        wgmma_ss_n64_k(S, dq, dk, 0);
        wgmma_ss_n64_k(S, dq + (256 >> 4), dk + (256 >> 4), 1);
        wgmma_commit();
        wgmma_wait<0>();
#pragma unroll
        for (int i = 0; i < 8; i++) {
          mx0 = fmaxf(mx0, fmaxf(S[4 * i], S[4 * i + 1]));
          mx1 = fmaxf(mx1, fmaxf(S[4 * i + 2], S[4 * i + 3]));
        }
      }
      mx0 = fmaxf(mx0, __shfl_xor_sync(~0u, mx0, 1)); mx0 = fmaxf(mx0, __shfl_xor_sync(~0u, mx0, 2));
      mx1 = fmaxf(mx1, __shfl_xor_sync(~0u, mx1, 1)); mx1 = fmaxf(mx1, __shfl_xor_sync(~0u, mx1, 2));
#pragma unroll 1
      for (int j = 0; j < 32; j++) {
        const uint64_t dk = make_desc(sK + j * 8 * 384, 128, 384, 0);
        wgmma_fence();
        wgmma_ss_n64_k(S, dq, dk, 0);
        wgmma_ss_n64_k(S, dq + (256 >> 4), dk + (256 >> 4), 1);
        wgmma_commit();
        wgmma_wait<0>();
        uint32_t P[16];
#pragma unroll
        for (int i = 0; i < 8; i++) {
          P[2 * i] = pack_bf16(ex2_mufu(S[4 * i] - mx0), ex2_mufu(S[4 * i + 1] - mx0));
          P[2 * i + 1] = pack_bf16(ex2_mufu(S[4 * i + 2] - mx1), ex2_mufu(S[4 * i + 3] - mx1));
        }
        wgmma_fence();
        const uint64_t dv = make_desc(sV + j * 8 * 384, 384, 128, 0);
#pragma unroll
        for (int ks = 0; ks < 4; ks++)
          wgmma_rs_n24_tb(O, P[4 * ks], P[4 * ks + 1], P[4 * ks + 2], P[4 * ks + 3], dv + ((ks * 768) >> 4), 1);
        wgmma_commit();
        wgmma_wait<0>();
      }
#pragma unroll
      for (int i = 0; i < 12; i++) asm volatile("" : "+f"(O[i]) :: "memory");
      write_out(O, it);
    }
  }
  TS_END(2);
}

typedef CUresult (*EncodeFn)(CUtensorMap*, CUtensorMapDataType, cuuint32_t, void*, const cuuint64_t*, const cuuint64_t*, const cuuint32_t*,
                             const cuuint32_t*, CUtensorMapInterleave, CUtensorMapSwizzle, CUtensorMapL2promotion, CUtensorMapFloatOOBfill);
static EncodeFn get_encode() {
  static EncodeFn fn = nullptr;
  if (!fn) {
    void* p = nullptr; cudaDriverEntryPointQueryResult st;
    cudaGetDriverEntryPoint("cuTensorMapEncodeTiled", &p, cudaEnableDefault, &st);
    fn = (EncodeFn)p;
  }
  return fn;
}
static CUtensorMap make_map(const void* ptr, int rows, int cols, int box_rows, int box_cols = 64) {
  CUtensorMap m;
  cuuint64_t dims[2] = {(cuuint64_t)cols, (cuuint64_t)rows};
  cuuint64_t strides[1] = {(cuuint64_t)cols * 2};
  cuuint32_t box[2] = {(cuuint32_t)box_cols, (cuuint32_t)box_rows};
  cuuint32_t es[2] = {1, 1};
  get_encode()(&m, CU_TENSOR_MAP_DATA_TYPE_BFLOAT16, 2, const_cast<void*>(ptr), dims, strides, box, es, CU_TENSOR_MAP_INTERLEAVE_NONE,
               box_cols == 64 ? CU_TENSOR_MAP_SWIZZLE_128B : (box_cols == 32 ? CU_TENSOR_MAP_SWIZZLE_64B : CU_TENSOR_MAP_SWIZZLE_32B), CU_TENSOR_MAP_L2_PROMOTION_L2_128B, CU_TENSOR_MAP_FLOAT_OOB_FILL_NONE);
  return m;
}
static CUtensorMap make_map_w(const void* ptr, int rows, int cols, int bc, int nblk) {
  CUtensorMap m;
  cuuint64_t dims[3] = {(cuuint64_t)bc, (cuuint64_t)rows, (cuuint64_t)(cols / bc)};
  cuuint64_t strides[2] = {(cuuint64_t)cols * 2, (cuuint64_t)bc * 2};
  cuuint32_t box[3] = {(cuuint32_t)bc, 64, (cuuint32_t)nblk};
  cuuint32_t es[3] = {1, 1, 1};
  get_encode()(&m, CU_TENSOR_MAP_DATA_TYPE_BFLOAT16, 3, const_cast<void*>(ptr), dims, strides, box, es, CU_TENSOR_MAP_INTERLEAVE_NONE,
               bc == 64 ? CU_TENSOR_MAP_SWIZZLE_128B : (bc == 32 ? CU_TENSOR_MAP_SWIZZLE_64B : CU_TENSOR_MAP_SWIZZLE_32B),
               CU_TENSOR_MAP_L2_PROMOTION_L2_128B, CU_TENSOR_MAP_FLOAT_OOB_FILL_NONE);
  return m;
}
template <typename... KArgs, typename... Args>
static void launch(void (*kern)(KArgs...), dim3 grid, dim3 block, size_t smem, bool pdl, dim3 cluster, Args... args) {
  cudaLaunchConfig_t cfg = {};
  cfg.gridDim = grid; cfg.blockDim = block; cfg.dynamicSmemBytes = smem; cfg.stream = cudaStreamPerThread;
  cudaLaunchAttribute at[2];
  int na = 0;
  if (pdl) { at[na].id = cudaLaunchAttributeProgrammaticStreamSerialization; at[na].val.programmaticStreamSerializationAllowed = 1; na++; }
  if (cluster.x * cluster.y > 1) { at[na].id = cudaLaunchAttributeClusterDimension; at[na].val.clusterDim.x = cluster.x; at[na].val.clusterDim.y = cluster.y; at[na].val.clusterDim.z = 1; na++; }
  cfg.attrs = at; cfg.numAttrs = na;
  cudaLaunchKernelEx(&cfg, kern, KArgs(args)...);
}

extern "C" void kernel_launch(void* const* d_in, const int* in_sizes, int n_in, void* d_out, int out_size) {
  const __nv_bfloat16* x = (const __nv_bfloat16*)d_in[0];
  const __nv_bfloat16* wqkv = (const __nv_bfloat16*)d_in[1];
  const __nv_bfloat16* wo = (const __nv_bfloat16*)d_in[2];
  const __nv_bfloat16* wgate = (const __nv_bfloat16*)d_in[4];
  const __nv_bfloat16* wup = (const __nv_bfloat16*)d_in[5];
  const __nv_bfloat16* wdown = (const __nv_bfloat16*)d_in[6];
  __nv_bfloat16* out = (__nv_bfloat16*)d_out;
  void *p_o, *p_h, *p_act;
  cudaGetSymbolAddress(&p_o, g_o); cudaGetSymbolAddress(&p_h, g_h); cudaGetSymbolAddress(&p_act, g_act);

#define A_CN 1
#define A_CM 1
#define D_CN 1
#define D_CM 1
  auto kA = gemm_kernel<256, 128, 1, DM, 4, EPI_QKV, 1, A_CN, A_CM>;
  auto kC = gemm_res_kernel<DM, true>;
  auto kD = gemm_kernel<128, 192, 2, DM, 3, EPI_GLU, 1, D_CN, D_CM>;
  auto kE = gemm_res_kernel<DFF, false>;
  constexpr int smA = GemmCfg<256, 128, 1, 4>::SMEM, smC = R_SMEM, smD = GemmCfg<128, 192, 2, 3>::SMEM;
  cudaFuncSetAttribute(kA, cudaFuncAttributeMaxDynamicSharedMemorySize, smA);
  cudaFuncSetAttribute(kC, cudaFuncAttributeMaxDynamicSharedMemorySize, smC);
  cudaFuncSetAttribute(kD, cudaFuncAttributeMaxDynamicSharedMemorySize, smD);
  cudaFuncSetAttribute(kE, cudaFuncAttributeMaxDynamicSharedMemorySize, smC);
  cudaFuncSetAttribute(attn_kernel, cudaFuncAttributeMaxDynamicSharedMemorySize, ATT_SMEM);

  const CUtensorMap tm_x = make_map(x, S_LEN, DM, 256), tm_wqkv = make_map_w(wqkv, DM, 3 * DM, 64, 2);
  const CUtensorMap tm_o = make_map(p_o, S_LEN, DM, 128), tm_wo = make_map_w(wo, DM, DM, 16, 5);
  const CUtensorMap tm_h = make_map(p_h, S_LEN, DM, 128), tm_wg = make_map_w(wgate, DM, DFF, 64, 3), tm_wu = make_map_w(wup, DM, DFF, 64, 3);
  const CUtensorMap tm_act = make_map(p_act, S_LEN, DFF, 128), tm_wd = make_map_w(wdown, DFF, DM, 16, 5);

  launch(pre_kernel, dim3(12), dim3(1024), 0, false, dim3(1, 1), x, wqkv);
  launch(kA, dim3(15, 8), dim3(288), smA, true, dim3(A_CN, A_CM), tm_x, tm_wqkv, tm_wqkv, x, (__nv_bfloat16*)wqkv);
  launch(attn_kernel, dim3(132), dim3(512), ATT_SMEM, true, dim3(1, 1), 0x800000, wgate, wup, tm_wo, tm_wd);
  launch(kC, dim3(8, 16), dim3(288), smC, true, dim3(1, 1), tm_o, tm_wo, x, (__nv_bfloat16*)p_h);
  launch(kD, dim3(8, 16), dim3(384), smD, true, dim3(D_CN, D_CM), tm_h, tm_wg, tm_wu, (const __nv_bfloat16*)nullptr, (__nv_bfloat16*)p_act);
  launch(kE, dim3(8, 16), dim3(288), smC, true, dim3(1, 1), tm_act, tm_wd, (const __nv_bfloat16*)p_h, out);
}
```

```cpp
#include <cuda_runtime.h>
#include <cuda_bf16.h>
#include <cuda.h>
#include <stdint.h>

constexpr int S_LEN = 2048, DM = 640, NH = 32, DH = 20, DFF = 1536;

__device__ __align__(1024) __nv_bfloat16 g_q[NH * S_LEN * 32];
__device__ __align__(1024) __nv_bfloat16 g_k[NH * S_LEN * 24];
__device__ __align__(1024) __nv_bfloat16 g_v[NH * S_LEN * 24];
__device__ __align__(1024) __nv_bfloat16 g_o[S_LEN * DM];
__device__ __align__(1024) __nv_bfloat16 g_h[S_LEN * DM];
__device__ __align__(1024) __nv_bfloat16 g_act[S_LEN * DFF];
__device__ __align__(1024) __nv_bfloat16 g_wo_t[DM * DM];
__device__ __align__(1024) __nv_bfloat16 g_wd_t[DFF * DM];
__device__ float g_kn[8 * NH * 2];
__device__ float2 g_stat1[S_LEN];
__device__ float g_cs_qkv[3 * DM];
__device__ float g_cs_g[DFF];
__device__ float g_cs_u[DFF];
__device__ unsigned int g_flag[32];
__device__ float2 g_part2[S_LEN * 10];

#define TS_BEGIN(k)
#define TS_END(k)
#define TS_MID(k, i)
__device__ __forceinline__ uint32_t smem_u32(const void* p) { return (uint32_t)__cvta_generic_to_shared(p); }
__device__ __forceinline__ void mbar_init(uint32_t bar, uint32_t cnt) { asm volatile("mbarrier.init.shared::cta.b64 [%0], %1;" :: "r"(bar), "r"(cnt)); }
__device__ __forceinline__ void mbar_expect_tx(uint32_t bar, uint32_t bytes) { asm volatile("mbarrier.arrive.expect_tx.shared::cta.b64 _, [%0], %1;" :: "r"(bar), "r"(bytes) : "memory"); }
__device__ __forceinline__ void mbar_arrive(uint32_t bar) { asm volatile("mbarrier.arrive.shared::cta.b64 _, [%0];" :: "r"(bar) : "memory"); }
__device__ __forceinline__ void mbar_wait(uint32_t bar, uint32_t parity) {
  uint32_t done;
  uint32_t spins = 0;
  do {
    asm volatile("{\n.reg .pred P1;\nmbarrier.try_wait.parity.shared::cta.b64 P1, [%1], %2;\nselp.u32 %0, 1, 0, P1;\n}" : "=r"(done) : "r"(bar), "r"(parity) : "memory");
  } while (!done && ++spins < (1u << 24));
}
__device__ __forceinline__ void bulk_g2s(uint32_t dst, const void* src, uint32_t bytes, uint32_t bar) {
  asm volatile("cp.async.bulk.shared::cluster.global.mbarrier::complete_tx::bytes [%0], [%1], %2, [%3];" :: "r"(dst), "l"(src), "r"(bytes), "r"(bar) : "memory");
}
__device__ __forceinline__ void tma_2d(uint32_t dst, const CUtensorMap* tm, int c0, int c1, uint32_t bar) {
  asm volatile("cp.async.bulk.tensor.2d.shared::cluster.global.mbarrier::complete_tx::bytes [%0], [%1, {%3, %4}], [%2];"
               :: "r"(dst), "l"(tm), "r"(bar), "r"(c0), "r"(c1) : "memory");
}
__device__ __forceinline__ void tma_3d(uint32_t dst, const CUtensorMap* tm, int c0, int c1, int c2, uint32_t bar) {
  asm volatile("cp.async.bulk.tensor.3d.shared::cluster.global.mbarrier::complete_tx::bytes [%0], [%1, {%3, %4, %5}], [%2];"
               :: "r"(dst), "l"(tm), "r"(bar), "r"(c0), "r"(c1), "r"(c2) : "memory");
}
__device__ __forceinline__ void tma_2d_mc(uint32_t dst, const CUtensorMap* tm, int c0, int c1, uint32_t bar, uint16_t mask) {
  asm volatile("cp.async.bulk.tensor.2d.shared::cluster.global.mbarrier::complete_tx::bytes.multicast::cluster [%0], [%1, {%3, %4}], [%2], %5;"
               :: "r"(dst), "l"(tm), "r"(bar), "r"(c0), "r"(c1), "h"(mask) : "memory");
}
__device__ __forceinline__ void mbar_arrive_remote(uint32_t bar, uint32_t rank) {
  asm volatile("{\n.reg .b32 ra;\nmapa.shared::cluster.u32 ra, %0, %1;\nmbarrier.arrive.release.cluster.shared::cluster.b64 _, [ra];\n}" :: "r"(bar), "r"(rank) : "memory");
}
__device__ __forceinline__ void cluster_arrive() { asm volatile("barrier.cluster.arrive.release.aligned;" ::: "memory"); }
__device__ __forceinline__ void cluster_wait() { asm volatile("barrier.cluster.wait.acquire.aligned;" ::: "memory"); }
__device__ __forceinline__ void wgmma_fence() { asm volatile("wgmma.fence.sync.aligned;" ::: "memory"); }
__device__ __forceinline__ void wgmma_commit() { asm volatile("wgmma.commit_group.sync.aligned;" ::: "memory"); }
template <int N> __device__ __forceinline__ void wgmma_wait() { asm volatile("wgmma.wait_group.sync.aligned %0;" :: "n"(N) : "memory"); }
__device__ __forceinline__ void pdl_wait() { asm volatile("griddepcontrol.wait;" ::: "memory"); }
__device__ __forceinline__ void pdl_launch() { asm volatile("griddepcontrol.launch_dependents;" ::: "memory"); }
__device__ __forceinline__ void named_bar(int id, int n) { asm volatile("bar.sync %0, %1;" :: "r"(id), "r"(n) : "memory"); }
__device__ __forceinline__ uint64_t make_desc(uint32_t addr, uint32_t lbo, uint32_t sbo, uint32_t swz) {
  return (uint64_t)((addr & 0x3FFFF) >> 4) | ((uint64_t)(lbo >> 4) << 16) | ((uint64_t)(sbo >> 4) << 32) | ((uint64_t)swz << 62);
}
__device__ __forceinline__ void st_g16(void* p, uint4 v) { asm volatile("st.global.v4.b32 [%0], {%1, %2, %3, %4};" :: "l"(p), "r"(v.x), "r"(v.y), "r"(v.z), "r"(v.w) : "memory"); }
__device__ __forceinline__ void st_g8(void* p, uint2 v) { asm volatile("st.global.v2.b32 [%0], {%1, %2};" :: "l"(p), "r"(v.x), "r"(v.y) : "memory"); }
__device__ __forceinline__ uint4 ld_g16(const void* p) { uint4 v; asm volatile("ld.global.v4.b32 {%0, %1, %2, %3}, [%4];" : "=r"(v.x), "=r"(v.y), "=r"(v.z), "=r"(v.w) : "l"(p) : "memory"); return v; }
__device__ __forceinline__ uint32_t pack_bf16(float lo, float hi) { uint32_t r; asm("cvt.rn.bf16x2.f32 %0, %1, %2;" : "=r"(r) : "f"(hi), "f"(lo)); return r; }
__device__ __forceinline__ float bf_lo(uint32_t u) { return __uint_as_float(u << 16); }
__device__ __forceinline__ float bf_hi(uint32_t u) { return __uint_as_float(u & 0xffff0000u); }
__device__ __forceinline__ float bf_round(float x) { return __bfloat162float(__float2bfloat16_rn(x)); }
__device__ __forceinline__ float ex2_mufu(float x) { float y; asm("ex2.approx.ftz.f32 %0, %1;" : "=f"(y) : "f"(x)); return y; }

__device__ __forceinline__ void wgmma_ss_n80(float (&d)[40], uint64_t da, uint64_t db, int scale_d) {
  asm volatile("{\n.reg .pred p;\nsetp.ne.b32 p, %42, 0;\n"
    "wgmma.mma_async.sync.aligned.m64n80k16.f32.bf16.bf16 {%0,%1,%2,%3,%4,%5,%6,%7,%8,%9,%10,%11,%12,%13,%14,%15,%16,%17,%18,%19,%20,%21,%22,%23,%24,%25,%26,%27,%28,%29,%30,%31,%32,%33,%34,%35,%36,%37,%38,%39}, %40, %41, p, 1, 1, 0, 1;\n}\n"
    : "+f"(d[0]),"+f"(d[1]),"+f"(d[2]),"+f"(d[3]),"+f"(d[4]),"+f"(d[5]),"+f"(d[6]),"+f"(d[7]),"+f"(d[8]),"+f"(d[9]),"+f"(d[10]),"+f"(d[11]),"+f"(d[12]),"+f"(d[13]),"+f"(d[14]),"+f"(d[15]),"+f"(d[16]),"+f"(d[17]),"+f"(d[18]),"+f"(d[19]),"+f"(d[20]),"+f"(d[21]),"+f"(d[22]),"+f"(d[23]),"+f"(d[24]),"+f"(d[25]),"+f"(d[26]),"+f"(d[27]),"+f"(d[28]),"+f"(d[29]),"+f"(d[30]),"+f"(d[31]),"+f"(d[32]),"+f"(d[33]),"+f"(d[34]),"+f"(d[35]),"+f"(d[36]),"+f"(d[37]),"+f"(d[38]),"+f"(d[39])
    : "l"(da), "l"(db), "r"(scale_d));
}
__device__ __forceinline__ void wgmma_ss_n128(float (&d)[64], uint64_t da, uint64_t db, int scale_d) {
  asm volatile("{\n.reg .pred p;\nsetp.ne.b32 p, %66, 0;\n"
    "wgmma.mma_async.sync.aligned.m64n128k16.f32.bf16.bf16 {%0,%1,%2,%3,%4,%5,%6,%7,%8,%9,%10,%11,%12,%13,%14,%15,%16,%17,%18,%19,%20,%21,%22,%23,%24,%25,%26,%27,%28,%29,%30,%31,%32,%33,%34,%35,%36,%37,%38,%39,%40,%41,%42,%43,%44,%45,%46,%47,%48,%49,%50,%51,%52,%53,%54,%55,%56,%57,%58,%59,%60,%61,%62,%63}, %64, %65, p, 1, 1, 0, 1;\n}\n"
    : "+f"(d[0]),"+f"(d[1]),"+f"(d[2]),"+f"(d[3]),"+f"(d[4]),"+f"(d[5]),"+f"(d[6]),"+f"(d[7]),"+f"(d[8]),"+f"(d[9]),"+f"(d[10]),"+f"(d[11]),"+f"(d[12]),"+f"(d[13]),"+f"(d[14]),"+f"(d[15]),"+f"(d[16]),"+f"(d[17]),"+f"(d[18]),"+f"(d[19]),"+f"(d[20]),"+f"(d[21]),"+f"(d[22]),"+f"(d[23]),"+f"(d[24]),"+f"(d[25]),"+f"(d[26]),"+f"(d[27]),"+f"(d[28]),"+f"(d[29]),"+f"(d[30]),"+f"(d[31]),"+f"(d[32]),"+f"(d[33]),"+f"(d[34]),"+f"(d[35]),"+f"(d[36]),"+f"(d[37]),"+f"(d[38]),"+f"(d[39]),"+f"(d[40]),"+f"(d[41]),"+f"(d[42]),"+f"(d[43]),"+f"(d[44]),"+f"(d[45]),"+f"(d[46]),"+f"(d[47]),"+f"(d[48]),"+f"(d[49]),"+f"(d[50]),"+f"(d[51]),"+f"(d[52]),"+f"(d[53]),"+f"(d[54]),"+f"(d[55]),"+f"(d[56]),"+f"(d[57]),"+f"(d[58]),"+f"(d[59]),"+f"(d[60]),"+f"(d[61]),"+f"(d[62]),"+f"(d[63])
    : "l"(da), "l"(db), "r"(scale_d));
}
__device__ __forceinline__ void wgmma_ss_n192(float (&d)[96], uint64_t da, uint64_t db, int scale_d) {
  asm volatile("{\n.reg .pred p;\nsetp.ne.b32 p, %98, 0;\n"
    "wgmma.mma_async.sync.aligned.m64n192k16.f32.bf16.bf16 {%0,%1,%2,%3,%4,%5,%6,%7,%8,%9,%10,%11,%12,%13,%14,%15,%16,%17,%18,%19,%20,%21,%22,%23,%24,%25,%26,%27,%28,%29,%30,%31,%32,%33,%34,%35,%36,%37,%38,%39,%40,%41,%42,%43,%44,%45,%46,%47,%48,%49,%50,%51,%52,%53,%54,%55,%56,%57,%58,%59,%60,%61,%62,%63,%64,%65,%66,%67,%68,%69,%70,%71,%72,%73,%74,%75,%76,%77,%78,%79,%80,%81,%82,%83,%84,%85,%86,%87,%88,%89,%90,%91,%92,%93,%94,%95}, %96, %97, p, 1, 1, 0, 1;\n}\n"
    : "+f"(d[0]),"+f"(d[1]),"+f"(d[2]),"+f"(d[3]),"+f"(d[4]),"+f"(d[5]),"+f"(d[6]),"+f"(d[7]),"+f"(d[8]),"+f"(d[9]),"+f"(d[10]),"+f"(d[11]),"+f"(d[12]),"+f"(d[13]),"+f"(d[14]),"+f"(d[15]),"+f"(d[16]),"+f"(d[17]),"+f"(d[18]),"+f"(d[19]),"+f"(d[20]),"+f"(d[21]),"+f"(d[22]),"+f"(d[23]),"+f"(d[24]),"+f"(d[25]),"+f"(d[26]),"+f"(d[27]),"+f"(d[28]),"+f"(d[29]),"+f"(d[30]),"+f"(d[31]),"+f"(d[32]),"+f"(d[33]),"+f"(d[34]),"+f"(d[35]),"+f"(d[36]),"+f"(d[37]),"+f"(d[38]),"+f"(d[39]),"+f"(d[40]),"+f"(d[41]),"+f"(d[42]),"+f"(d[43]),"+f"(d[44]),"+f"(d[45]),"+f"(d[46]),"+f"(d[47]),"+f"(d[48]),"+f"(d[49]),"+f"(d[50]),"+f"(d[51]),"+f"(d[52]),"+f"(d[53]),"+f"(d[54]),"+f"(d[55]),"+f"(d[56]),"+f"(d[57]),"+f"(d[58]),"+f"(d[59]),"+f"(d[60]),"+f"(d[61]),"+f"(d[62]),"+f"(d[63]),"+f"(d[64]),"+f"(d[65]),"+f"(d[66]),"+f"(d[67]),"+f"(d[68]),"+f"(d[69]),"+f"(d[70]),"+f"(d[71]),"+f"(d[72]),"+f"(d[73]),"+f"(d[74]),"+f"(d[75]),"+f"(d[76]),"+f"(d[77]),"+f"(d[78]),"+f"(d[79]),"+f"(d[80]),"+f"(d[81]),"+f"(d[82]),"+f"(d[83]),"+f"(d[84]),"+f"(d[85]),"+f"(d[86]),"+f"(d[87]),"+f"(d[88]),"+f"(d[89]),"+f"(d[90]),"+f"(d[91]),"+f"(d[92]),"+f"(d[93]),"+f"(d[94]),"+f"(d[95])
    : "l"(da), "l"(db), "r"(scale_d));
}
__device__ __forceinline__ void wgmma_ss_n64_k(float (&d)[32], uint64_t da, uint64_t db, int scale_d) {
  asm volatile("{\n.reg .pred p;\nsetp.ne.b32 p, %34, 0;\n"
    "wgmma.mma_async.sync.aligned.m64n64k16.f32.bf16.bf16 {%0,%1,%2,%3,%4,%5,%6,%7,%8,%9,%10,%11,%12,%13,%14,%15,%16,%17,%18,%19,%20,%21,%22,%23,%24,%25,%26,%27,%28,%29,%30,%31}, %32, %33, p, 1, 1, 0, 0;\n}\n"
    : "+f"(d[0]),"+f"(d[1]),"+f"(d[2]),"+f"(d[3]),"+f"(d[4]),"+f"(d[5]),"+f"(d[6]),"+f"(d[7]),"+f"(d[8]),"+f"(d[9]),"+f"(d[10]),"+f"(d[11]),"+f"(d[12]),"+f"(d[13]),"+f"(d[14]),"+f"(d[15]),"+f"(d[16]),"+f"(d[17]),"+f"(d[18]),"+f"(d[19]),"+f"(d[20]),"+f"(d[21]),"+f"(d[22]),"+f"(d[23]),"+f"(d[24]),"+f"(d[25]),"+f"(d[26]),"+f"(d[27]),"+f"(d[28]),"+f"(d[29]),"+f"(d[30]),"+f"(d[31])
    : "l"(da), "l"(db), "r"(scale_d));
}
__device__ __forceinline__ void wgmma_rs_n24_tb(float (&d)[12], uint32_t a0, uint32_t a1, uint32_t a2, uint32_t a3, uint64_t db, int scale_d) {
  asm volatile("{\n.reg .pred p;\nsetp.ne.b32 p, %17, 0;\n"
    "wgmma.mma_async.sync.aligned.m64n24k16.f32.bf16.bf16 {%0,%1,%2,%3,%4,%5,%6,%7,%8,%9,%10,%11}, {%12,%13,%14,%15}, %16, p, 1, 1, 1;\n}\n"
    : "+f"(d[0]),"+f"(d[1]),"+f"(d[2]),"+f"(d[3]),"+f"(d[4]),"+f"(d[5]),"+f"(d[6]),"+f"(d[7]),"+f"(d[8]),"+f"(d[9]),"+f"(d[10]),"+f"(d[11])
    : "r"(a0), "r"(a1), "r"(a2), "r"(a3), "l"(db), "r"(scale_d));
}

constexpr int PRE_ROW_BLOCKS = 64;
constexpr int PRE_COL_BLOCKS = 3 * DM / 64;
__device__ __forceinline__ float2 ln_finish(float mean, float var) {
  float mb = bf_round(mean);
  float s = bf_round(sqrtf(bf_round(bf_round(var) + 1e-5f)));
  return make_float2(mb, 1.0f / s);
}
__device__ __forceinline__ void colsum64(const __nv_bfloat16* __restrict__ w, int ld, int c0, float* __restrict__ dst, float (*red)[65], int tid, int bar_id) {
  const int cg = tid & 7, r0 = tid >> 3;
  float acc[8];
#pragma unroll
  for (int i = 0; i < 8; i++) acc[i] = 0.f;
#pragma unroll 10
  for (int r = r0; r < DM; r += 32) {
    uint4 v = __ldg((const uint4*)(w + (size_t)r * ld + c0 + cg * 8));
    acc[0] += bf_lo(v.x); acc[1] += bf_hi(v.x); acc[2] += bf_lo(v.y); acc[3] += bf_hi(v.y);
    acc[4] += bf_lo(v.z); acc[5] += bf_hi(v.z); acc[6] += bf_lo(v.w); acc[7] += bf_hi(v.w);
  }
#pragma unroll
  for (int i = 0; i < 8; i++) red[r0][cg * 8 + i] = acc[i];
  named_bar(bar_id, 256);
  if (tid < 64) {
    float s = 0.f;
#pragma unroll
    for (int r = 0; r < 32; r++) s += red[r][tid];
    dst[c0 + tid] = s;
  }
  named_bar(bar_id, 256);
}
__global__ void __launch_bounds__(1024) pre_kernel(const __nv_bfloat16* __restrict__ x, const __nv_bfloat16* __restrict__ wqkv) {
  TS_BEGIN(0);
  pdl_launch();
  __shared__ float red[51][161];
  const int tid = threadIdx.x, lane = tid & 31, warp = tid >> 5;
  {
    const int ch = tid % 20, rl = tid / 20;
    if (rl < 51) {
      const __nv_bfloat16* w = wqkv + blockIdx.x * 160 + ch * 8;
      uint4 v[13];
#pragma unroll
      for (int i = 0; i < 13; i++) { const int r = rl + i * 51; v[i] = r < DM ? __ldg((const uint4*)(w + (size_t)r * (3 * DM))) : make_uint4(0, 0, 0, 0); }
      float acc[8];
#pragma unroll
      for (int i = 0; i < 8; i++) acc[i] = 0.f;
#pragma unroll
      for (int i = 0; i < 13; i++) {
        acc[0] += bf_lo(v[i].x); acc[1] += bf_hi(v[i].x); acc[2] += bf_lo(v[i].y); acc[3] += bf_hi(v[i].y);
        acc[4] += bf_lo(v[i].z); acc[5] += bf_hi(v[i].z); acc[6] += bf_lo(v[i].w); acc[7] += bf_hi(v[i].w);
      }
#pragma unroll
      for (int i = 0; i < 8; i++) red[rl][ch * 8 + i] = acc[i];
    }
  }
  const int rbeg = blockIdx.x * 171, rend = min(rbeg + 171, S_LEN);
  for (int row0 = rbeg + warp * 2; row0 < rend; row0 += 64) {
    uint4 v[2][3];
#pragma unroll
    for (int k = 0; k < 2; k++) {
      const int row = min(row0 + k, rend - 1);
      const uint4* p = (const uint4*)(x + (size_t)row * DM);
      v[k][0] = __ldg(p + lane); v[k][1] = __ldg(p + 32 + lane);
      v[k][2] = lane < 16 ? __ldg(p + 64 + lane) : make_uint4(0, 0, 0, 0);
    }
#pragma unroll
    for (int k = 0; k < 2; k++) {
      float f[24];
      const uint32_t u[12] = {v[k][0].x, v[k][0].y, v[k][0].z, v[k][0].w, v[k][1].x, v[k][1].y, v[k][1].z, v[k][1].w, v[k][2].x, v[k][2].y, v[k][2].z, v[k][2].w};
#pragma unroll
      for (int j = 0; j < 12; j++) { f[2 * j] = bf_lo(u[j]); f[2 * j + 1] = bf_hi(u[j]); }
      float s = 0.f;
#pragma unroll
      for (int j = 0; j < 24; j++) s += f[j];
#pragma unroll
      for (int o = 16; o; o >>= 1) s += __shfl_xor_sync(~0u, s, o);
      const float mean = s * (1.0f / DM);
      float q = 0.f;
#pragma unroll
      for (int j = 0; j < 16; j++) { const float d = f[j] - mean; q += d * d; }
      if (lane < 16) {
#pragma unroll
        for (int j = 16; j < 24; j++) { const float d = f[j] - mean; q += d * d; }
      }
#pragma unroll
      for (int o = 16; o; o >>= 1) q += __shfl_xor_sync(~0u, q, o);
      if (lane == 0 && row0 + k < rend) g_stat1[row0 + k] = ln_finish(mean, q * (1.0f / DM));
    }
  }
  __syncthreads();
  if (tid < 160) {
    float s = 0.f;
#pragma unroll 17
    for (int r = 0; r < 51; r++) s += red[r][tid];
    g_cs_qkv[blockIdx.x * 160 + tid] = s;
  }
  TS_END(0);
}

enum { EPI_QKV = 0, EPI_WO = 1, EPI_GLU = 2, EPI_DOWN = 3 };
template <int N> struct WG;
template <> struct WG<128> { static __device__ __forceinline__ void mma(float (&d)[64], uint64_t a, uint64_t b, int s) { wgmma_ss_n128(d, a, b, s); } };
template <> struct WG<192> { static __device__ __forceinline__ void mma(float (&d)[96], uint64_t a, uint64_t b, int s) { wgmma_ss_n192(d, a, b, s); } };

template <int BM, int BN, int NB, int STAGES> struct GemmCfg {
  static constexpr int A_BYTES = BM * 128;
  static constexpr int B_BYTES = NB * (BN / 64) * 8192;
  static constexpr int STAGE_BYTES = A_BYTES + B_BYTES;
  static constexpr int SMEM = STAGES * STAGE_BYTES + 1024   + 256   + 4096  ;
};

constexpr float QSCALE = 0.22360679774997896f * 1.4426950408889634f;

template <int BM, int BN, int NB, int KDIM, int STAGES, int EPI, int MINB, int CN, int CM>
__global__ void __launch_bounds__(EPI == EPI_GLU ? 384 : 288, MINB) gemm_kernel(const __grid_constant__ CUtensorMap tmA, const __grid_constant__ CUtensorMap tmB0,
                                                         const __grid_constant__ CUtensorMap tmB1,
                                                         const __nv_bfloat16* resid, __nv_bfloat16* out) {
  using Cfg = GemmCfg<BM, BN, NB, STAGES>;
  constexpr int MB = BM / 128;
  constexpr int KT = KDIM / 64;
  extern __shared__ uint8_t smem_raw[];
  const uint32_t sbase = (smem_u32(smem_raw) + 1023u) & ~1023u;
  uint8_t* sptr = smem_raw + (sbase - smem_u32(smem_raw));
  const uint32_t sbar = sbase + STAGES * Cfg::STAGE_BYTES;
  const int tid = threadIdx.x, warp = tid >> 5, lane = tid & 31;
  const int n0 = blockIdx.x * BN, m0 = blockIdx.y * BM;
  TS_BEGIN(EPI == EPI_QKV ? 1 : EPI + 2);
  TS_MID(EPI == EPI_QKV ? 1 : EPI + 2, 3);
  constexpr int NCL = CN + CM - 1;
  const int cx = blockIdx.x % CN, cy = blockIdx.y % CM;
  if (tid == 0) {
    for (int i = 0; i < STAGES; i++) { mbar_init(sbar + 8 * i, 1); mbar_init(sbar + 8 * (STAGES + i), 2 * NCL); }
    asm volatile("fence.mbarrier_init.release.cluster;" ::: "memory");
  }
  __syncthreads();
  if constexpr (CN * CM > 1) { cluster_arrive(); cluster_wait(); }
  pdl_launch();
  if (warp >= 8) {
    if constexpr (EPI == EPI_GLU) asm volatile("setmaxnreg.dec.sync.aligned.u32 40;");
    if (warp == 8 && lane == 0) {
      auto load_a = [&](int kt, int s) { tma_2d(sbase + s * Cfg::STAGE_BYTES, &tmA, kt * 64, m0, sbar + 8 * s); };
      auto load_b = [&](int kt, int s) {
        const uint32_t sb = sbase + s * Cfg::STAGE_BYTES + Cfg::A_BYTES;
        tma_3d(sb, &tmB0, 0, kt * 64, blockIdx.x * (BN / 64), sbar + 8 * s);
        if constexpr (NB == 2) tma_3d(sb + (BN / 64) * 8192, &tmB1, 0, kt * 64, blockIdx.x * (BN / 64), sbar + 8 * s);
      };
      if constexpr (EPI == EPI_QKV) {
        const int cta = blockIdx.y * gridDim.x + blockIdx.x;
        const uint32_t xb = S_LEN * DM * 2, xs = 21888;
        if (cta * xs < xb) asm volatile("cp.async.bulk.prefetch.L2.global [%0], %1;" :: "l"((const uint8_t*)resid + (size_t)cta * xs), "r"(min(xs, xb - cta * xs)));
        asm volatile("cp.async.bulk.prefetch.L2.global [%0], %1;" :: "l"((const uint8_t*)out + (size_t)cta * 20480), "r"(20480));
      }
      for (int s = 0; s < STAGES; s++) { mbar_expect_tx(sbar + 8 * s, Cfg::STAGE_BYTES); if (EPI != EPI_QKV || s == 0) load_b(s, s); }
      if (EPI != EPI_QKV) pdl_wait();
      for (int s = 0; s < STAGES; s++) { load_a(s, s); if (EPI == EPI_QKV && s > 0) load_b(s, s); }
      for (int kt = STAGES; kt < KT; kt++) {
        const int s = kt % STAGES;
        mbar_wait(sbar + 8 * (STAGES + s), ((kt / STAGES) - 1) & 1);
        mbar_expect_tx(sbar + 8 * s, Cfg::STAGE_BYTES);
        load_a(kt, s);
        load_b(kt, s);
      }
    }
    if constexpr (EPI == EPI_GLU) {
      if (warp > 8) {
        float2* s_st = (float2*)(sptr + STAGES * Cfg::STAGE_BYTES + 256);
        float* s_cs = (float*)(sptr + STAGES * Cfg::STAGE_BYTES + 256 + 1024);
        pdl_wait();
        for (int r = tid - 288; r < BM; r += 96) {
          const float2* pp = &g_part2[(m0 + r) * 8];
          float s = 0.f;
#pragma unroll
          for (int i = 0; i < 8; i++) s += pp[i].x;
          const float mean = s * (1.0f / DM);
          float q = 0.f;
#pragma unroll
          for (int i = 0; i < 8; i++) { const float2 p = pp[i]; const float d = p.x * (1.0f / 80.f) - mean; q += p.y + 80.f * d * d; }
          s_st[r] = ln_finish(mean, q * (1.0f / DM));
        }
        for (int c = tid - 288; c < BN; c += 96) { s_cs[c] = g_cs_g[n0 + c]; s_cs[BN + c] = g_cs_u[n0 + c]; }
        __threadfence_block();
        asm volatile("bar.arrive 2, 352;" ::: "memory");
      }
    }
    if constexpr (CN * CM > 1) { __syncwarp(); cluster_arrive(); cluster_wait(); }
    return;
  }
  if constexpr (EPI == EPI_GLU) asm volatile("setmaxnreg.inc.sync.aligned.u32 232;");
  const int wg = warp >> 2, g = lane >> 2, t = lane & 3;
  float acc[MB][NB][BN / 2];
#pragma unroll
  for (int mb = 0; mb < MB; mb++)
#pragma unroll
    for (int nb = 0; nb < NB; nb++)
#pragma unroll
      for (int i = 0; i < BN / 2; i++) acc[mb][nb][i] = 0.f;
  for (int kt = 0; kt < KT; kt++) {
    const int s = kt % STAGES;
    mbar_wait(sbar + 8 * s, (kt / STAGES) & 1);
    if (kt == 0) TS_MID(EPI == EPI_QKV ? 1 : EPI + 2, 0);
    const uint32_t sa = sbase + s * Cfg::STAGE_BYTES + wg * (MB * 64 * 128);
    const uint32_t sb = sbase + s * Cfg::STAGE_BYTES + Cfg::A_BYTES;
    wgmma_fence();
#pragma unroll
    for (int ks = 0; ks < 4; ks++) {
#pragma unroll
      for (int mb = 0; mb < MB; mb++) {
        const uint64_t da = make_desc(sa + mb * 8192 + ks * 32, 16, 1024, 1);
#pragma unroll
        for (int nb = 0; nb < NB; nb++) {
          const uint64_t db = make_desc(sb + nb * (BN / 64) * 8192 + ks * 2048, 8192, 1024, 1);
          WG<BN>::mma(acc[mb][nb], da, db, 1);
        }
      }
    }
    wgmma_commit();
    wgmma_wait<1>();
    if (kt > 0 && kt - 1 + STAGES < KT && (tid & 127) < NCL) {
      const uint32_t eb = sbar + 8 * (STAGES + (kt - 1) % STAGES);
      if constexpr (CN * CM > 1) {
        const int i = tid & 127;
        const uint32_t rank = i < CN ? cy * CN + i : ((i - CN + (i - CN >= cy ? 1 : 0)) * CN + cx);
        mbar_arrive_remote(eb, rank);
      } else mbar_arrive(eb);
    }
  }
  wgmma_wait<0>();
#pragma unroll
  for (int mb = 0; mb < MB; mb++)
#pragma unroll
    for (int nb = 0; nb < NB; nb++)
#pragma unroll
      for (int i = 0; i < BN / 2; i++) asm volatile("" : "+f"(acc[mb][nb][i]) :: "memory");
  if constexpr (CN * CM > 1) cluster_arrive();
  TS_MID(EPI == EPI_QKV ? 1 : EPI + 2, 1);
  pdl_wait();
  TS_MID(EPI == EPI_QKV ? 1 : EPI + 2, 2);
  named_bar(1, 256);
  constexpr int LDS = BN * 2 + 16;
  const int ctid = tid;

  if constexpr (EPI == EPI_QKV) {
    const int sec = n0 / DM;
    constexpr int lds = 264;
    __shared__ unsigned int s_kn[8];
    if (ctid < 8) s_kn[ctid] = 0u;
    if (blockIdx.x == 0 && blockIdx.y == 0 && ctid < 32) g_flag[ctid] = 0u;
    float2 cs[BN / 8];
#pragma unroll
    for (int j = 0; j < BN / 8; j++) cs[j] = *(const float2*)&g_cs_qkv[n0 + j * 8 + 2 * t];
#pragma unroll
    for (int mb = 0; mb < MB; mb++) {
      const int r0 = wg * (MB * 64) + mb * 64 + (warp & 3) * 16 + g;
      const float2 st0 = g_stat1[m0 + r0], st1 = g_stat1[m0 + r0 + 8];
      const float sc0 = sec == 0 ? st0.y * QSCALE : st0.y, sc1 = sec == 0 ? st1.y * QSCALE : st1.y;
#pragma unroll
      for (int j = 0; j < BN / 8; j++) {
        const float* a = &acc[mb][0][4 * j];
        *(uint32_t*)(sptr + r0 * lds + j * 16 + t * 4) = pack_bf16(fmaf(-st0.x, cs[j].x, a[0]) * sc0, fmaf(-st0.x, cs[j].y, a[1]) * sc0);
        *(uint32_t*)(sptr + (r0 + 8) * lds + j * 16 + t * 4) = pack_bf16(fmaf(-st1.x, cs[j].x, a[2]) * sc1, fmaf(-st1.x, cs[j].y, a[3]) * sc1);
      }
    }
    named_bar(1, 256);
    {
      const int cbase = n0 - sec * DM;
      const int hfirst = cbase / DH;
      const int j = m0 + ctid;
      uint8_t* dst = (uint8_t*)(sec == 0 ? g_q : (sec == 1 ? g_k : g_v)) + (size_t)(j >> 3) * (sec == 0 ? 512 : 384) + (j & 7) * 16;
      const uint8_t* row = sptr + ctid * 264;
#pragma unroll
      for (int i = 0; i < 8; i++) {
        const int hh = hfirst + i;
        const int cr = hh * DH - cbase;
        if (cr < BN) {
          uint2 v[5];
          bool in[5];
          float s = 0.f;
#pragma unroll
          for (int qd = 0; qd < 5; qd++) {
            const int c = cr + 4 * qd;
            in[qd] = c >= 0 && c < BN;
            v[qd] = in[qd] ? *(const uint2*)(row + c * 2) : make_uint2(0u, 0u);
            s += bf_lo(v[qd].x) * bf_lo(v[qd].x) + bf_hi(v[qd].x) * bf_hi(v[qd].x) + bf_lo(v[qd].y) * bf_lo(v[qd].y) + bf_hi(v[qd].y) * bf_hi(v[qd].y);
          }
          uint8_t* p = dst + (size_t)hh * (sec == 0 ? S_LEN * 64 : S_LEN * 48);
          if (in[0] && in[1]) st_g16(p, make_uint4(v[0].x, v[0].y, v[1].x, v[1].y));
          else if (in[0]) st_g8(p, v[0]);
          else if (in[1]) st_g8(p + 8, v[1]);
          if (in[2] && in[3]) st_g16(p + 128, make_uint4(v[2].x, v[2].y, v[3].x, v[3].y));
          else if (in[2]) st_g8(p + 128, v[2]);
          else if (in[3]) st_g8(p + 136, v[3]);
          if (in[4]) {
            st_g16(p + 256, make_uint4(v[4].x, v[4].y, sec == 0 ? 0u : 0x00003f80u, 0u));
            if (sec == 0) st_g16(p + 384, make_uint4(0u, 0u, 0u, 0u));
          }
          if (sec == 1) {
            const unsigned int mxb = __reduce_max_sync(~0u, __float_as_uint(s) & 0x7fffffffu);
            if (lane == 0) atomicMax(&s_kn[i], mxb);
          }
        }
      }
      if (sec == 1) {
        named_bar(1, 256);
        const int hh = hfirst + ctid;
        if (ctid < 8 && hh * DH < cbase + BN) {
          const bool starts_here = hh * DH >= cbase, ends_here = hh * DH + DH <= cbase + BN;
          const float v = __uint_as_float(s_kn[ctid]);
          float* o = &g_kn[(blockIdx.y * NH + hh) * 2];
          if (starts_here) { o[0] = v; if (ends_here) o[1] = 0.f; }
          else o[1] = v;
        }
      }
    }
  } else if constexpr (EPI == EPI_WO || EPI == EPI_DOWN) {
    const int r0 = wg * 64 + (warp & 3) * 16 + g;
#pragma unroll
    for (int j = 0; j < BN / 8; j++) {
      const float* a = &acc[0][0][4 * j];
      *(uint32_t*)(sptr + r0 * LDS + j * 16 + t * 4) = pack_bf16(a[0], a[1]);
      *(uint32_t*)(sptr + (r0 + 8) * LDS + j * 16 + t * 4) = pack_bf16(a[2], a[3]);
    }
    named_bar(1, 256);
#pragma unroll
    for (int i = 0; i < BM * (BN / 8) / 256; i++) {
      const int idx = i * 256 + ctid, r = idx / (BN / 8), c = idx % (BN / 8);
      const uint4 a = *(const uint4*)(sptr + r * LDS + c * 16);
      const size_t go = (size_t)(m0 + r) * DM + n0 + c * 8;
      const uint4 b = ld_g16(resid + go);
      uint4 o;
      o.x = pack_bf16(bf_lo(a.x) + bf_lo(b.x), bf_hi(a.x) + bf_hi(b.x));
      o.y = pack_bf16(bf_lo(a.y) + bf_lo(b.y), bf_hi(a.y) + bf_hi(b.y));
      o.z = pack_bf16(bf_lo(a.z) + bf_lo(b.z), bf_hi(a.z) + bf_hi(b.z));
      o.w = pack_bf16(bf_lo(a.w) + bf_lo(b.w), bf_hi(a.w) + bf_hi(b.w));
      st_g16(out + go, o);
      if constexpr (EPI == EPI_WO) {
        static_assert(BN == 64, "stats assume 8 lanes per row");
        const float f[8] = {bf_lo(o.x), bf_hi(o.x), bf_lo(o.y), bf_hi(o.y), bf_lo(o.z), bf_hi(o.z), bf_lo(o.w), bf_hi(o.w)};
        float s = 0.f;
#pragma unroll
        for (int k = 0; k < 8; k++) s += f[k];
        s += __shfl_xor_sync(~0u, s, 1); s += __shfl_xor_sync(~0u, s, 2); s += __shfl_xor_sync(~0u, s, 4);
        const float mu = s * (1.0f / 64.f);
        float q = 0.f;
#pragma unroll
        for (int k = 0; k < 8; k++) { const float d = f[k] - mu; q += d * d; }
        q += __shfl_xor_sync(~0u, q, 1); q += __shfl_xor_sync(~0u, q, 2); q += __shfl_xor_sync(~0u, q, 4);
        if (c == 0) g_part2[(m0 + r) * 10 + blockIdx.x] = make_float2(s, q);
      }
    }
  } else {
    const int r0 = wg * 64 + (warp & 3) * 16 + g;
    const float2* s_st = (const float2*)(sptr + STAGES * Cfg::STAGE_BYTES + 256);
    const float* s_cs = (const float*)(sptr + STAGES * Cfg::STAGE_BYTES + 256 + 1024);
    named_bar(2, 352);
    float2 st[2] = {s_st[r0], s_st[r0 + 8]};
#pragma unroll
    for (int j = 0; j < BN / 8; j++) {
      const float2 cg = *(const float2*)&s_cs[j * 8 + 2 * t], cu = *(const float2*)&s_cs[BN + j * 8 + 2 * t];
      const float* a = &acc[0][0][4 * j];
      const float* b = &acc[0][1][4 * j];
#pragma unroll
      for (int e = 0; e < 2; e++) {
        const float2 s_ = st[e];
        const uint32_t gp = pack_bf16(fmaf(-s_.x, cg.x, a[2 * e]) * s_.y, fmaf(-s_.x, cg.y, a[2 * e + 1]) * s_.y);
        const uint32_t up = pack_bf16(fmaf(-s_.x, cu.x, b[2 * e]) * s_.y, fmaf(-s_.x, cu.y, b[2 * e + 1]) * s_.y);
        uint32_t r;
        asm("{\n.reg .b32 z;\nmax.bf16x2 z, %1, %3;\nmul.rn.bf16x2 %0, z, %2;\n}" : "=r"(r) : "r"(gp), "r"(up), "r"(0u));
        *(uint32_t*)(sptr + (r0 + 8 * e) * LDS + j * 16 + t * 4) = r;
      }
    }
    named_bar(1, 256);
#pragma unroll
    for (int i = 0; i < BM * (BN / 8) / 256; i++) {
      const int idx = i * 256 + ctid, r = idx / (BN / 8), c = idx % (BN / 8);
      st_g16(out + (size_t)(m0 + r) * DFF + n0 + c * 8, *(const uint4*)(sptr + r * LDS + c * 16));
    }
  }
  if constexpr (CN * CM > 1) cluster_wait();
  TS_END(EPI == EPI_QKV ? 1 : EPI + 2);
}

constexpr int R_STAGES = 8;
constexpr int R_STAGE_BYTES = 16384 + 5 * 2048;
constexpr int R_BAR_OFF = R_STAGES * R_STAGE_BYTES;
constexpr int R_SMEM = R_BAR_OFF + 256 + 1024;
template <int KDIM, bool STATS>
__global__ void __launch_bounds__(288, 1) gemm_res_kernel(const __grid_constant__ CUtensorMap tmA, const __grid_constant__ CUtensorMap tmB,
                                                          const __nv_bfloat16* resid, __nv_bfloat16* out) {
  constexpr int KT = KDIM / 64;
  extern __shared__ uint8_t smem_raw[];
  const uint32_t sbase = (smem_u32(smem_raw) + 1023u) & ~1023u;
  uint8_t* sptr = smem_raw + (sbase - smem_u32(smem_raw));
  const uint32_t sbar = sbase + R_BAR_OFF;
  const int tid = threadIdx.x, warp = tid >> 5, lane = tid & 31;
  const int n0 = blockIdx.x * 80, m0 = blockIdx.y * 128;
  TS_BEGIN(STATS ? 3 : 5);
  if (tid == 0) {
    for (int i = 0; i < R_STAGES; i++) { mbar_init(sbar + 8 * i, 1); mbar_init(sbar + 8 * (R_STAGES + i), 2); }
    asm volatile("fence.mbarrier_init.release.cluster;" ::: "memory");
  }
  __syncthreads();
  pdl_launch();
  if (warp == 8) {
    if (lane == 0) {
      const uint8_t* wt = (const uint8_t*)(STATS ? g_wo_t : g_wd_t) + (size_t)blockIdx.x * KT * 10240;
      auto load_b = [&](int kt, int s) { bulk_g2s(sbase + s * R_STAGE_BYTES + 16384, wt + kt * 10240, 10240, sbar + 8 * s); };
      pdl_wait();
      for (int s = 0; s < R_STAGES; s++) { mbar_expect_tx(sbar + 8 * s, R_STAGE_BYTES); tma_2d(sbase + s * R_STAGE_BYTES, &tmA, s * 64, m0, sbar + 8 * s); load_b(s, s); }
      for (int kt = R_STAGES; kt < KT; kt++) {
        const int s = kt % R_STAGES;
        mbar_wait(sbar + 8 * (R_STAGES + s), ((kt / R_STAGES) - 1) & 1);
        mbar_expect_tx(sbar + 8 * s, R_STAGE_BYTES);
        tma_2d(sbase + s * R_STAGE_BYTES, &tmA, kt * 64, m0, sbar + 8 * s);
        load_b(kt, s);
      }
    }
    return;
  }
  const int wg = warp >> 2, g = lane >> 2, t = lane & 3;
  pdl_wait();
  uint4 rv[5];
#pragma unroll
  for (int i = 0; i < 5; i++) {
    const int idx = i * 256 + tid, r = idx / 10, c = idx % 10;
    rv[i] = ld_g16(resid + (size_t)(m0 + r) * DM + n0 + c * 8);
  }
  float acc[40];
#pragma unroll
  for (int i = 0; i < 40; i++) acc[i] = 0.f;
  for (int kt = 0; kt < KT; kt++) {
    const int s = kt % R_STAGES;
    mbar_wait(sbar + 8 * s, (kt / R_STAGES) & 1);
    if (kt == 0) TS_MID(STATS ? 3 : 5, 0);
    const uint32_t sa = sbase + s * R_STAGE_BYTES + wg * 8192;
    const uint32_t sb = sbase + s * R_STAGE_BYTES + 16384;
    wgmma_fence();
#pragma unroll
    for (int ks = 0; ks < 4; ks++)
      wgmma_ss_n80(acc, make_desc(sa + ks * 32, 16, 1024, 1), make_desc(sb + ks * 512, 2048, 256, 3), 1);
    wgmma_commit();
    wgmma_wait<1>();
    if (kt > 0 && kt - 1 + R_STAGES < KT && (tid & 127) == 0) mbar_arrive(sbar + 8 * (R_STAGES + (kt - 1) % R_STAGES));
  }
  wgmma_wait<0>();
#pragma unroll
  for (int i = 0; i < 40; i++) asm volatile("" : "+f"(acc[i]) :: "memory");
  TS_MID(STATS ? 3 : 5, 1);
  named_bar(1, 256);
  constexpr int LDS = 176;
  const int r0 = wg * 64 + (warp & 3) * 16 + g;
#pragma unroll
  for (int i = 0; i < 10; i++) {
    *(uint32_t*)(sptr + r0 * LDS + i * 16 + t * 4) = pack_bf16(acc[4 * i], acc[4 * i + 1]);
    *(uint32_t*)(sptr + (r0 + 8) * LDS + i * 16 + t * 4) = pack_bf16(acc[4 * i + 2], acc[4 * i + 3]);
  }
  named_bar(1, 256);
  TS_MID(STATS ? 3 : 5, 2);
#pragma unroll
  for (int i = 0; i < 5; i++) {
    const int idx = i * 256 + tid, r = idx / 10, c = idx % 10;
    const uint4 a = *(const uint4*)(sptr + r * LDS + c * 16);
    const uint4 b = rv[i];
    uint4 o;
    o.x = pack_bf16(bf_lo(a.x) + bf_lo(b.x), bf_hi(a.x) + bf_hi(b.x));
    o.y = pack_bf16(bf_lo(a.y) + bf_lo(b.y), bf_hi(a.y) + bf_hi(b.y));
    o.z = pack_bf16(bf_lo(a.z) + bf_lo(b.z), bf_hi(a.z) + bf_hi(b.z));
    o.w = pack_bf16(bf_lo(a.w) + bf_lo(b.w), bf_hi(a.w) + bf_hi(b.w));
    st_g16(out + (size_t)(m0 + r) * DM + n0 + c * 8, o);
    if constexpr (STATS) *(uint4*)(sptr + r * LDS + c * 16) = o;
  }
  TS_MID(STATS ? 3 : 5, 3);
  if constexpr (STATS) {
    named_bar(1, 256);
    const int r = tid >> 1, hf = tid & 1;
    float f[40];
#pragma unroll
    for (int i = 0; i < 5; i++) {
      const uint4 v = *(const uint4*)(sptr + r * LDS + hf * 80 + i * 16);
      f[8 * i] = bf_lo(v.x); f[8 * i + 1] = bf_hi(v.x); f[8 * i + 2] = bf_lo(v.y); f[8 * i + 3] = bf_hi(v.y);
      f[8 * i + 4] = bf_lo(v.z); f[8 * i + 5] = bf_hi(v.z); f[8 * i + 6] = bf_lo(v.w); f[8 * i + 7] = bf_hi(v.w);
    }
    float s = 0.f;
#pragma unroll
    for (int i = 0; i < 40; i++) s += f[i];
    s += __shfl_xor_sync(~0u, s, 1);
    const float mu = s * (1.0f / 80.f);
    float q = 0.f;
#pragma unroll
    for (int i = 0; i < 40; i++) { const float d = f[i] - mu; q += d * d; }
    q += __shfl_xor_sync(~0u, q, 1);
    if (hf == 0) g_part2[(m0 + r) * 8 + blockIdx.x] = make_float2(s, q);
  }
  TS_END(STATS ? 3 : 5);
}

#define F_MC 0
constexpr int F_CST = 7, F_DST = 3, F_EST = 5;
constexpr int F_RS = 16384 + 5 * 2048;
constexpr int F_DS = 16384 + 6 * 8192;
constexpr int F_E_OFF = 53248;
constexpr int F_STG_OFF = F_DST * F_DS;
constexpr int F_BAR_OFF = F_STG_OFF + 128 * 176;
constexpr int F_VEC_OFF = F_BAR_OFF + 256;
constexpr int F_SMEM = F_VEC_OFF + 1024 + 1536 + 1024;

__device__ __forceinline__ void flag_wait(const unsigned int* f, unsigned int target) {
  unsigned int v, spins = 0;
  do { asm volatile("ld.acquire.gpu.global.u32 %0, [%1];" : "=r"(v) : "l"(f) : "memory"); } while (v < target && ++spins < (1u << 22));
  asm volatile("fence.proxy.async;" ::: "memory");
}
__device__ __forceinline__ void flag_signal(unsigned int* f) {
  asm volatile("fence.proxy.async;" ::: "memory");
  asm volatile("red.release.gpu.global.add.u32 [%0], 1;" :: "l"(f) : "memory");
}

template <bool STATS>
__device__ __forceinline__ void res_epilogue(float (&acc)[40], const uint4 (&rv)[5], uint8_t* stg, __nv_bfloat16* out, int m0, int n0, int tid, int bx) {
  constexpr int LDS = 176;
  const int warp = tid >> 5, lane = tid & 31;
  const int r0 = (warp >> 2) * 64 + (warp & 3) * 16 + (lane >> 2), t = lane & 3;
#pragma unroll
  for (int i = 0; i < 10; i++) {
    *(uint32_t*)(stg + r0 * LDS + i * 16 + t * 4) = pack_bf16(acc[4 * i], acc[4 * i + 1]);
    *(uint32_t*)(stg + (r0 + 8) * LDS + i * 16 + t * 4) = pack_bf16(acc[4 * i + 2], acc[4 * i + 3]);
  }
  named_bar(1, 256);
#pragma unroll
  for (int i = 0; i < 5; i++) {
    const int idx = i * 256 + tid, r = idx / 10, c = idx % 10;
    const uint4 a = *(const uint4*)(stg + r * LDS + c * 16);
    const uint4 b = rv[i];
    uint4 o;
    o.x = pack_bf16(bf_lo(a.x) + bf_lo(b.x), bf_hi(a.x) + bf_hi(b.x));
    o.y = pack_bf16(bf_lo(a.y) + bf_lo(b.y), bf_hi(a.y) + bf_hi(b.y));
    o.z = pack_bf16(bf_lo(a.z) + bf_lo(b.z), bf_hi(a.z) + bf_hi(b.z));
    o.w = pack_bf16(bf_lo(a.w) + bf_lo(b.w), bf_hi(a.w) + bf_hi(b.w));
    st_g16(out + (size_t)(m0 + r) * DM + n0 + c * 8, o);
    if constexpr (STATS) *(uint4*)(stg + r * LDS + c * 16) = o;
  }
  if constexpr (STATS) {
    named_bar(1, 256);
    const int r = tid >> 1, hf = tid & 1;
    float f[40];
#pragma unroll
    for (int i = 0; i < 5; i++) {
      const uint4 v = *(const uint4*)(stg + r * LDS + hf * 80 + i * 16);
      f[8 * i] = bf_lo(v.x); f[8 * i + 1] = bf_hi(v.x); f[8 * i + 2] = bf_lo(v.y); f[8 * i + 3] = bf_hi(v.y);
      f[8 * i + 4] = bf_lo(v.z); f[8 * i + 5] = bf_hi(v.z); f[8 * i + 6] = bf_lo(v.w); f[8 * i + 7] = bf_hi(v.w);
    }
    float s = 0.f;
#pragma unroll
    for (int i = 0; i < 40; i++) s += f[i];
    s += __shfl_xor_sync(~0u, s, 1);
    const float mu = s * (1.0f / 80.f);
    float q = 0.f;
#pragma unroll
    for (int i = 0; i < 40; i++) { const float d = f[i] - mu; q += d * d; }
    q += __shfl_xor_sync(~0u, q, 1);
    if (hf == 0) g_part2[(m0 + r) * 8 + bx] = make_float2(s, q);
  }
}

__global__ void __launch_bounds__(384, 1) post_kernel(const __grid_constant__ CUtensorMap tmO, const __grid_constant__ CUtensorMap tmWo,
                                                      const __grid_constant__ CUtensorMap tmH, const __grid_constant__ CUtensorMap tmWg,
                                                      const __grid_constant__ CUtensorMap tmWu, const __grid_constant__ CUtensorMap tmAct,
                                                      const __grid_constant__ CUtensorMap tmWd, const __nv_bfloat16* x, __nv_bfloat16* out) {
  extern __shared__ uint8_t smem_raw[];
  const uint32_t sbase = (smem_u32(smem_raw) + 1023u) & ~1023u;
  uint8_t* sptr = smem_raw + (sbase - smem_u32(smem_raw));
  const uint32_t bC = sbase + F_BAR_OFF, bD = bC + 16 * F_CST, bE = bD + 16 * F_DST;
  const int tid = threadIdx.x, warp = tid >> 5, lane = tid & 31;
  const int bx = blockIdx.x, rb = blockIdx.y, m0 = rb * 128, cx = bx & 1;
  TS_BEGIN(3);
  if (tid == 0) {
    for (int i = 0; i < F_CST; i++) { mbar_init(bC + 8 * i, 1); mbar_init(bC + 8 * (F_CST + i), F_MC ? 4 : 2); }
    for (int i = 0; i < F_DST; i++) { mbar_init(bD + 8 * i, 1); mbar_init(bD + 8 * (F_DST + i), F_MC ? 4 : 2); }
    for (int i = 0; i < F_EST; i++) { mbar_init(bE + 8 * i, 1); mbar_init(bE + 8 * (F_EST + i), F_MC ? 4 : 2); }
    asm volatile("fence.mbarrier_init.release.cluster;" ::: "memory");
  }
  __syncthreads();
  if (F_MC) { cluster_arrive(); cluster_wait(); }
  if (warp >= 8) {
    asm volatile("setmaxnreg.dec.sync.aligned.u32 40;");
    if (warp == 8) {
      if (lane == 0) {
        auto load_a = [&](const CUtensorMap* tm, uint32_t stage, int kt, uint32_t bar) {
          if (F_MC) tma_2d_mc(stage + cx * 8192, tm, kt * 64, m0 + cx * 64, bar, (uint16_t)3); else tma_2d(stage, tm, kt * 64, m0, bar);
        };
        for (int s = 0; s < F_CST; s++) { mbar_expect_tx(bC + 8 * s, F_RS); if (s < 3) tma_3d(sbase + s * F_RS + 16384, &tmWo, 0, s * 64, bx * 5, bC + 8 * s); }
        pdl_wait();
        for (int s = 0; s < F_CST; s++) { load_a(&tmO, sbase + s * F_RS, s, bC + 8 * s); if (s >= 3) tma_3d(sbase + s * F_RS + 16384, &tmWo, 0, s * 64, bx * 5, bC + 8 * s); }
        for (int kt = F_CST; kt < 10; kt++) {
          const int s = kt - F_CST;
          mbar_wait(bC + 8 * (F_CST + s), 0);
          mbar_expect_tx(bC + 8 * s, F_RS);
          load_a(&tmO, sbase + s * F_RS, kt, bC + 8 * s);
          tma_3d(sbase + s * F_RS + 16384, &tmWo, 0, kt * 64, bx * 5, bC + 8 * s);
        }
        auto load_bd = [&](int kt, int s) {
          tma_3d(sbase + s * F_DS + 16384, &tmWg, 0, kt * 64, bx * 3, bD + 8 * s);
          tma_3d(sbase + s * F_DS + 16384 + 3 * 8192, &tmWu, 0, kt * 64, bx * 3, bD + 8 * s);
        };
        for (int s = 0; s < F_DST; s++) { mbar_wait(bD + 8 * (F_DST + s), 0); mbar_expect_tx(bD + 8 * s, F_DS); load_bd(s, s); }
        flag_wait(&g_flag[rb], 8);
        for (int s = 0; s < F_DST; s++) load_a(&tmH, sbase + s * F_DS, s, bD + 8 * s);
        for (int kt = F_DST; kt < 10; kt++) {
          const int s = kt % F_DST;
          mbar_wait(bD + 8 * (F_DST + s), (kt / F_DST) & 1);
          mbar_expect_tx(bD + 8 * s, F_DS);
          load_a(&tmH, sbase + s * F_DS, kt, bD + 8 * s);
          load_bd(kt, s);
        }
        const uint32_t eb = sbase + F_E_OFF;
        for (int s = 0; s < F_EST; s++) { mbar_wait(bE + 8 * (F_EST + s), 0); mbar_expect_tx(bE + 8 * s, F_RS); tma_3d(eb + s * F_RS + 16384, &tmWd, 0, s * 64, bx * 5, bE + 8 * s); }
        flag_wait(&g_flag[16 + rb], 8);
        for (int s = 0; s < F_EST; s++) load_a(&tmAct, eb + s * F_RS, s, bE + 8 * s);
        for (int kt = F_EST; kt < 24; kt++) {
          const int s = kt % F_EST;
          mbar_wait(bE + 8 * (F_EST + s), (kt / F_EST) & 1);
          mbar_expect_tx(bE + 8 * s, F_RS);
          load_a(&tmAct, eb + s * F_RS, kt, bE + 8 * s);
          tma_3d(eb + s * F_RS + 16384, &tmWd, 0, kt * 64, bx * 5, bE + 8 * s);
        }
      }
    } else {
      float2* s_st = (float2*)(sptr + F_VEC_OFF);
      float* s_cs = (float*)(sptr + F_VEC_OFF + 1024);
      pdl_wait();
      for (int c = tid - 288; c < 192; c += 96) { s_cs[c] = g_cs_g[bx * 192 + c]; s_cs[192 + c] = g_cs_u[bx * 192 + c]; }
      flag_wait(&g_flag[rb], 8);
      for (int r = tid - 288; r < 128; r += 96) {
        const float2* pp = &g_part2[(m0 + r) * 8];
        float2 p[8];
        float s = 0.f;
#pragma unroll
        for (int i = 0; i < 8; i++) { asm volatile("ld.global.v2.f32 {%0, %1}, [%2];" : "=f"(p[i].x), "=f"(p[i].y) : "l"(pp + i) : "memory"); s += p[i].x; }
        const float mean = s * (1.0f / DM);
        float q = 0.f;
#pragma unroll
        for (int i = 0; i < 8; i++) { const float d = p[i].x * (1.0f / 80.f) - mean; q += p[i].y + 80.f * d * d; }
        s_st[r] = ln_finish(mean, q * (1.0f / DM));
      }
      __threadfence_block();
      asm volatile("bar.arrive 2, 352;" ::: "memory");
    }
    if (F_MC) { __syncwarp(); cluster_arrive(); cluster_wait(); }
    return;
  }
  asm volatile("setmaxnreg.inc.sync.aligned.u32 232;");
  const int wg = warp >> 2, g = lane >> 2, t = lane & 3;
  auto release = [&](uint32_t bar) { if (F_MC) { if ((tid & 127) < 2) mbar_arrive_remote(bar, (tid & 127) ^ cx); } else if ((tid & 127) == 0) mbar_arrive(bar); };
  const int n0 = bx * 80;
  uint4 rv[5];
  pdl_wait();
  {
#pragma unroll
    for (int i = 0; i < 5; i++) { const int idx = i * 256 + tid, r = idx / 10, c = idx % 10; rv[i] = ld_g16(x + (size_t)(m0 + r) * DM + n0 + c * 8); }
    float acc[40];
#pragma unroll
    for (int i = 0; i < 40; i++) acc[i] = 0.f;
    for (int kt = 0; kt < 10; kt++) {
      const int s = kt % F_CST;
      mbar_wait(bC + 8 * s, kt / F_CST);
      if (kt == 0) TS_MID(3, 0);
      const uint32_t sa = sbase + s * F_RS + wg * 8192, sb = sbase + s * F_RS + 16384;
      wgmma_fence();
#pragma unroll
      for (int ks = 0; ks < 4; ks++) wgmma_ss_n80(acc, make_desc(sa + ks * 32, 16, 1024, 1), make_desc(sb + ks * 512, 2048, 256, 3), 1);
      wgmma_commit();
      wgmma_wait<1>();
      if (kt > 0 && kt - 1 + F_CST < 10) release(bC + 8 * (F_CST + kt - 1));
    }
    wgmma_wait<0>();
#pragma unroll
    for (int i = 0; i < 40; i++) asm volatile("" : "+f"(acc[i]) :: "memory");
    for (int s = 0; s < F_DST; s++) release(bD + 8 * (F_DST + s));
    TS_MID(3, 1);
    res_epilogue<true>(acc, rv, sptr + F_STG_OFF, g_h, m0, n0, tid, bx);
    __threadfence();
    named_bar(1, 256);
    if (tid == 0) flag_signal(&g_flag[rb]);
    TS_END(3);
  }
  {
    float acc[2][96];
#pragma unroll
    for (int i = 0; i < 96; i++) { acc[0][i] = 0.f; acc[1][i] = 0.f; }
    for (int kt = 0; kt < 10; kt++) {
      const int s = kt % F_DST;
      mbar_wait(bD + 8 * s, (kt / F_DST) & 1);
      if (kt == 0) TS_MID(4, 0);
      const uint32_t sa = sbase + s * F_DS + wg * 8192, sb = sbase + s * F_DS + 16384;
      wgmma_fence();
#pragma unroll
      for (int ks = 0; ks < 4; ks++) {
        const uint64_t da = make_desc(sa + ks * 32, 16, 1024, 1);
        wgmma_ss_n192(acc[0], da, make_desc(sb + ks * 2048, 8192, 1024, 1), 1);
        wgmma_ss_n192(acc[1], da, make_desc(sb + 3 * 8192 + ks * 2048, 8192, 1024, 1), 1);
      }
      wgmma_commit();
      wgmma_wait<1>();
      if (kt > 0 && kt - 1 + F_DST < 10) release(bD + 8 * (F_DST + (kt - 1) % F_DST));
    }
    wgmma_wait<0>();
#pragma unroll
    for (int i = 0; i < 96; i++) { asm volatile("" : "+f"(acc[0][i]) :: "memory"); asm volatile("" : "+f"(acc[1][i]) :: "memory"); }
    for (int s = 0; s < F_EST; s++) release(bE + 8 * (F_EST + s));
    TS_MID(4, 1);
    named_bar(1, 256);
    named_bar(2, 352);
    constexpr int LDS = 400;
    const float2* s_st = (const float2*)(sptr + F_VEC_OFF);
    const float* s_cs = (const float*)(sptr + F_VEC_OFF + 1024);
    const int r0 = wg * 64 + (warp & 3) * 16 + g;
    const float2 st[2] = {s_st[r0], s_st[r0 + 8]};
#pragma unroll
    for (int j = 0; j < 24; j++) {
      const float2 cg = *(const float2*)&s_cs[j * 8 + 2 * t], cu = *(const float2*)&s_cs[192 + j * 8 + 2 * t];
      const float* a = &acc[0][4 * j];
      const float* b = &acc[1][4 * j];
#pragma unroll
      for (int e = 0; e < 2; e++) {
        const float2 s_ = st[e];
        const uint32_t gp = pack_bf16(fmaf(-s_.x, cg.x, a[2 * e]) * s_.y, fmaf(-s_.x, cg.y, a[2 * e + 1]) * s_.y);
        const uint32_t up = pack_bf16(fmaf(-s_.x, cu.x, b[2 * e]) * s_.y, fmaf(-s_.x, cu.y, b[2 * e + 1]) * s_.y);
        uint32_t r;
        asm("{\n.reg .b32 z;\nmax.bf16x2 z, %1, %3;\nmul.rn.bf16x2 %0, z, %2;\n}" : "=r"(r) : "r"(gp), "r"(up), "r"(0u));
        *(uint32_t*)(sptr + (r0 + 8 * e) * LDS + j * 16 + t * 4) = r;
      }
    }
    named_bar(1, 256);
#pragma unroll
    for (int i = 0; i < 12; i++) {
      const int idx = i * 256 + tid, r = idx / 24, c = idx % 24;
      st_g16(g_act + (size_t)(m0 + r) * DFF + bx * 192 + c * 8, *(const uint4*)(sptr + r * LDS + c * 16));
    }
    __threadfence();
    named_bar(1, 256);
    if (tid == 0) flag_signal(&g_flag[16 + rb]);
    TS_END(4);
  }
  {
#pragma unroll
    for (int i = 0; i < 5; i++) { const int idx = i * 256 + tid, r = idx / 10, c = idx % 10; rv[i] = ld_g16(g_h + (size_t)(m0 + r) * DM + n0 + c * 8); }
    float acc[40];
#pragma unroll
    for (int i = 0; i < 40; i++) acc[i] = 0.f;
    const uint32_t eb = sbase + F_E_OFF;
    for (int kt = 0; kt < 24; kt++) {
      const int s = kt % F_EST;
      mbar_wait(bE + 8 * s, (kt / F_EST) & 1);
      if (kt == 0) TS_MID(5, 0);
      const uint32_t sa = eb + s * F_RS + wg * 8192, sb = eb + s * F_RS + 16384;
      wgmma_fence();
#pragma unroll
      for (int ks = 0; ks < 4; ks++) wgmma_ss_n80(acc, make_desc(sa + ks * 32, 16, 1024, 1), make_desc(sb + ks * 512, 2048, 256, 3), 1);
      wgmma_commit();
      wgmma_wait<1>();
      if (kt > 0 && kt - 1 + F_EST < 24) release(bE + 8 * (F_EST + (kt - 1) % F_EST));
    }
    wgmma_wait<0>();
#pragma unroll
    for (int i = 0; i < 40; i++) asm volatile("" : "+f"(acc[i]) :: "memory");
    if (F_MC) cluster_arrive();
    TS_MID(5, 1);
    res_epilogue<false>(acc, rv, sptr + F_STG_OFF, out, m0, n0, tid, bx);
    if (F_MC) cluster_wait();
    TS_END(5);
  }
}

#define POLY_NUM 5
__device__ __forceinline__ float ex2_poly(float x, int shl23) {
  const float MAGIC = 12582912.f;
  const float tt = x + MAGIC;
  const float f = x - (tt - MAGIC);
  float p = fmaf(0.0013276472454890609f, f, 0.009675540961325169f);
  p = fmaf(p, f, 0.05550713092088699f);
  p = fmaf(p, f, 0.24022120237350464f);
  p = fmaf(p, f, 0.6931469440460205f);
  p = fmaf(p, f, 1.0000001192092896f);
  return __int_as_float(__float_as_int(tt) * shl23 + __float_as_int(p));
}
constexpr int KV_BYTES = S_LEN * 48;
constexpr int ATT_SMEM = 2 * KV_BYTES + 256 + 32768;
constexpr int ATT_BODY = 8;

__global__ void __launch_bounds__(512, 1) attn_kernel(int shl23, const __nv_bfloat16* __restrict__ wg_, const __nv_bfloat16* __restrict__ wu_,
                                                      const __grid_constant__ CUtensorMap tmWo, const __grid_constant__ CUtensorMap tmWd) {
  extern __shared__ __align__(1024) uint8_t smem[];
  if (blockIdx.x < 4) {
    pdl_launch();
    const int e = blockIdx.x, half = threadIdx.x >> 8;
    TS_MID(0, 0);
    const uint32_t sb = smem_u32(smem), bar = sb + 200 * 1024;
    auto rt_load = [&](int rd) {
      mbar_expect_tx(bar, 17 * 10240);
      for (int i = 0; i < 17; i++) {
        const int tl = e * 68 + rd * 17 + i;
        if (tl >= 80) tma_3d(sb + i * 10240, &tmWd, 0, ((tl - 80) % 24) * 64, ((tl - 80) / 24) * 5, bar);
        else tma_3d(sb + i * 10240, &tmWo, 0, (tl % 10) * 64, (tl / 10) * 5, bar);
      }
    };
    auto rt_store = [&](int rd) {
      mbar_wait(bar, rd & 1);
      for (int i = 0; i < 17; i++) {
        const int tl = e * 68 + rd * 17 + i;
        uint8_t* dst = tl >= 80 ? (uint8_t*)g_wd_t + (size_t)(tl - 80) * 10240 : (uint8_t*)g_wo_t + (size_t)tl * 10240;
        asm volatile("cp.async.bulk.global.shared::cta.bulk_group [%0], [%1], %2;" :: "l"(dst), "r"(sb + i * 10240), "r"(10240) : "memory");
      }
      asm volatile("cp.async.bulk.commit_group;" ::: "memory");
      asm volatile("cp.async.bulk.wait_group.read 0;" ::: "memory");
    };
    if (threadIdx.x == 0) {
      mbar_init(bar, 1);
      asm volatile("fence.mbarrier_init.release.cluster;" ::: "memory");
      rt_load(0);
    }
    __syncwarp();
    float (*red)[65] = (float (*)[65])(smem + 176 * 1024 + half * 10240);
    for (int i = 0; i < 6; i++) {
      const int b = e * 12 + half + 2 * i;
      if (b < 24) colsum64(wg_, DFF, b * 64, g_cs_g, red, threadIdx.x & 255, 1 + half);
      else colsum64(wu_, DFF, (b - 24) * 64, g_cs_u, red, threadIdx.x & 255, 1 + half);
      if ((i & 1) && threadIdx.x == 0) { rt_store(i >> 1); rt_load((i >> 1) + 1); }
      __syncwarp();
    }
    if (threadIdx.x == 0) { rt_store(3); asm volatile("cp.async.bulk.wait_group 0;" ::: "memory"); }
    TS_MID(0, 2);
    return;
  }
  const int h = (blockIdx.x - 4) >> 2, qb = blockIdx.x & 3;
  const uint32_t sK = smem_u32(smem), sV = sK + KV_BYTES, sBar = sV + KV_BYTES;
  const int tid = threadIdx.x;
  TS_BEGIN(2);
  if (tid == 0) {
    for (int i = 0; i < 9; i++) mbar_init(sBar + 8 * i, 1);
    asm volatile("fence.mbarrier_init.release.cluster;" ::: "memory");
  }
  __syncthreads();
  pdl_launch();
  pdl_wait();
  TS_MID(2, 0);
  const uint8_t* gk = (const uint8_t*)(g_k + (size_t)h * S_LEN * 24);
  const uint8_t* gv = (const uint8_t*)(g_v + (size_t)h * S_LEN * 24);
  auto load_kv = [&](int i0, int i1) {
    for (int i = i0; i < i1; i++) {
      mbar_expect_tx(sBar + 8 * i, 2 * 12288);
      bulk_g2s(sK + i * 12288, gk + i * 12288, 12288, sBar + 8 * i);
      bulk_g2s(sV + i * 12288, gv + i * 12288, 12288, sBar + 8 * i);
    }
  };
  if (tid == 0) {
    mbar_expect_tx(sBar + 64, 32768);
    bulk_g2s(sBar + 256, (const uint8_t*)g_q + ((size_t)h * S_LEN + qb * 512) * 64, 32768, sBar + 64);
    load_kv(0, 2);
  }
  float ka = 0.f, kb = 0.f;
#pragma unroll
  for (int i = 0; i < 8; i++) {
    const float2 v = *(const float2*)&g_kn[(i * NH + h) * 2];
    ka = (v.x > ka || v.x != v.x) ? v.x : ka;
    kb = (v.y > kb || v.y != v.y) ? v.y : kb;
  }
  bool fast;
  {
    const float kn = sqrtf(ka + kb);
    mbar_wait(sBar + 64, 0);
    if (tid == 0) load_kv(2, 8);
    uint8_t* qrow = smem + 2 * KV_BYTES + 256 + (tid >> 3) * 512 + (tid & 7) * 16;
    const uint4 c0 = *(const uint4*)qrow, c1 = *(const uint4*)(qrow + 128);
    const uint2 c2 = *(const uint2*)(qrow + 256);
    auto sq = [](uint32_t u) { const float a = bf_lo(u), b = bf_hi(u); return a * a + b * b; };
    const float n2 = sq(c0.x) + sq(c0.y) + sq(c0.z) + sq(c0.w) + sq(c1.x) + sq(c1.y) + sq(c1.z) + sq(c1.w) + sq(c2.x) + sq(c2.y);
    const float m = ceilf(sqrtf(n2) * kn * 1.001f) + 1.f;
    fast = __syncthreads_or(!(m <= 62.f)) == 0;
    if (fast) *(uint32_t*)(qrow + 256 + 8) = pack_bf16(-m, 0.f);
    asm volatile("fence.proxy.async.shared::cta;" ::: "memory");
    __syncthreads();
  }
  auto write_out = [&](float (&O)[12], int it) {
    uint32_t tid2;
    asm volatile("mov.u32 %0, %%tid.x;" : "=r"(tid2));
    const int lane2 = tid2 & 31, t2 = lane2 & 3;
    const int qq = (blockIdx.x & 3) * 512 + (it * 4 + (tid2 >> 7)) * 64 + ((tid2 >> 5) & 3) * 16 + (lane2 >> 2);
    const float l0 = __shfl_sync(~0u, O[8], (lane2 & ~3) | 2), l1 = __shfl_sync(~0u, O[10], (lane2 & ~3) | 2);
    const float r0 = 1.f / l0, r1 = 1.f / l1;
    uint32_t* o0 = (uint32_t*)(g_o + (size_t)qq * DM + ((blockIdx.x - 4) >> 2) * DH);
    uint32_t* o1 = o0 + 8 * DM / 2;
    o0[t2] = pack_bf16(O[0] * r0, O[1] * r0); o1[t2] = pack_bf16(O[2] * r1, O[3] * r1);
    o0[t2 + 4] = pack_bf16(O[4] * r0, O[5] * r0); o1[t2 + 4] = pack_bf16(O[6] * r1, O[7] * r1);
    if (t2 < 2) { o0[t2 + 8] = pack_bf16(O[8] * r0, O[9] * r0); o1[t2 + 8] = pack_bf16(O[10] * r1, O[11] * r1); }
  };
  TS_MID(2, 1);
  if (fast) {
#pragma unroll 1
    for (int it = 0; it < 2; it++) {
      const uint64_t dq = make_desc(sBar + 256 + (it * 4 + (tid >> 7)) * 4096, 128, 512, 0);
      float O[12];
#pragma unroll
      for (int i = 0; i < 12; i++) { O[i] = 0.f; asm volatile("" : "+f"(O[i]) :: "memory"); }
      float S[2][32];
      uint32_t P[16];
#pragma unroll 1
      for (int jb = 0; jb < 32 / ATT_BODY; jb++) {
        if (it == 0) { for (int c = 0; c < ATT_BODY / 4; c++) mbar_wait(sBar + 8 * (jb * (ATT_BODY / 4) + c), 0); }
        const uint64_t dk0 = make_desc(sK + jb * ATT_BODY * 8 * 384, 128, 384, 0);
        const uint64_t dv0 = make_desc(sV + jb * ATT_BODY * 8 * 384, 384, 128, 0);
        wgmma_fence();
        wgmma_ss_n64_k(S[0], dq, dk0, 0);
        wgmma_ss_n64_k(S[0], dq + (256 >> 4), dk0 + (256 >> 4), 1);
        wgmma_commit();
#pragma unroll
        for (int u = 0; u < ATT_BODY; u++) {
          if (u + 1 < ATT_BODY) {
            const uint64_t dk = dk0 + (((u + 1) * 8 * 384) >> 4);
            wgmma_fence();
            wgmma_ss_n64_k(S[(u + 1) & 1], dq, dk, 0);
            wgmma_ss_n64_k(S[(u + 1) & 1], dq + (256 >> 4), dk + (256 >> 4), 1);
            wgmma_commit();
          }
          if (u == 0 || u == ATT_BODY - 1) wgmma_wait<1>(); else wgmma_wait<2>();
#pragma unroll
          for (int i = 0; i < 32; i++) asm volatile("" : "+f"(S[u & 1][i]) :: "memory");
          const uint64_t dv = dv0 + ((u * 8 * 384) >> 4);
#pragma unroll
          for (int hf = 0; hf < 2; hf++) {
            if (hf == 1 && u > 0) { if (u == ATT_BODY - 1) wgmma_wait<1>(); else wgmma_wait<2>(); }
#pragma unroll
            for (int i = hf * 8; i < hf * 8 + 8; i++) {
              const bool usepoly = ((i + 1) * POLY_NUM / 16) != (i * POLY_NUM / 16);
              float a, b;
              if (usepoly) { a = ex2_poly(S[u & 1][2 * i], shl23); b = ex2_poly(S[u & 1][2 * i + 1], shl23); }
              else { a = ex2_mufu(S[u & 1][2 * i]); b = ex2_mufu(S[u & 1][2 * i + 1]); }
              P[i] = pack_bf16(a, b);
            }
            wgmma_fence();
#pragma unroll
            for (int ks = hf * 2; ks < hf * 2 + 2; ks++)
              wgmma_rs_n24_tb(O, P[4 * ks], P[4 * ks + 1], P[4 * ks + 2], P[4 * ks + 3], dv + ((ks * 768) >> 4), 1);
            wgmma_commit();
          }
        }
        wgmma_wait<0>();
      }
#pragma unroll
      for (int i = 0; i < 12; i++) asm volatile("" : "+f"(O[i]) :: "memory");
      write_out(O, it);
      if (it == 0) TS_MID(2, 2);
    }
  } else {
#pragma unroll 1
    for (int it = 0; it < 2; it++) {
      const uint64_t dq = make_desc(sBar + 256 + (it * 4 + (tid >> 7)) * 4096, 128, 512, 0);
      float O[12];
#pragma unroll
      for (int i = 0; i < 12; i++) { O[i] = 0.f; asm volatile("" : "+f"(O[i]) :: "memory"); }
      float S[32];
      float mx0 = -INFINITY, mx1 = -INFINITY;
#pragma unroll 1
      for (int j = 0; j < 32; j++) {
        if (it == 0 && (j & 3) == 0) mbar_wait(sBar + 8 * (j >> 2), 0);
        const uint64_t dk = make_desc(sK + j * 8 * 384, 128, 384, 0);
        wgmma_fence();
        wgmma_ss_n64_k(S, dq, dk, 0);
        wgmma_ss_n64_k(S, dq + (256 >> 4), dk + (256 >> 4), 1);
        wgmma_commit();
        wgmma_wait<0>();
#pragma unroll
        for (int i = 0; i < 8; i++) {
          mx0 = fmaxf(mx0, fmaxf(S[4 * i], S[4 * i + 1]));
          mx1 = fmaxf(mx1, fmaxf(S[4 * i + 2], S[4 * i + 3]));
        }
      }
      mx0 = fmaxf(mx0, __shfl_xor_sync(~0u, mx0, 1)); mx0 = fmaxf(mx0, __shfl_xor_sync(~0u, mx0, 2));
      mx1 = fmaxf(mx1, __shfl_xor_sync(~0u, mx1, 1)); mx1 = fmaxf(mx1, __shfl_xor_sync(~0u, mx1, 2));
#pragma unroll 1
      for (int j = 0; j < 32; j++) {
        const uint64_t dk = make_desc(sK + j * 8 * 384, 128, 384, 0);
        wgmma_fence();
        wgmma_ss_n64_k(S, dq, dk, 0);
        wgmma_ss_n64_k(S, dq + (256 >> 4), dk + (256 >> 4), 1);
        wgmma_commit();
        wgmma_wait<0>();
        uint32_t P[16];
#pragma unroll
        for (int i = 0; i < 8; i++) {
          P[2 * i] = pack_bf16(ex2_mufu(S[4 * i] - mx0), ex2_mufu(S[4 * i + 1] - mx0));
          P[2 * i + 1] = pack_bf16(ex2_mufu(S[4 * i + 2] - mx1), ex2_mufu(S[4 * i + 3] - mx1));
        }
        wgmma_fence();
        const uint64_t dv = make_desc(sV + j * 8 * 384, 384, 128, 0);
#pragma unroll
        for (int ks = 0; ks < 4; ks++)
          wgmma_rs_n24_tb(O, P[4 * ks], P[4 * ks + 1], P[4 * ks + 2], P[4 * ks + 3], dv + ((ks * 768) >> 4), 1);
        wgmma_commit();
        wgmma_wait<0>();
      }
#pragma unroll
      for (int i = 0; i < 12; i++) asm volatile("" : "+f"(O[i]) :: "memory");
      write_out(O, it);
    }
  }
  TS_END(2);
}

typedef CUresult (*EncodeFn)(CUtensorMap*, CUtensorMapDataType, cuuint32_t, void*, const cuuint64_t*, const cuuint64_t*, const cuuint32_t*,
                             const cuuint32_t*, CUtensorMapInterleave, CUtensorMapSwizzle, CUtensorMapL2promotion, CUtensorMapFloatOOBfill);
static EncodeFn get_encode() {
  static EncodeFn fn = nullptr;
  if (!fn) {
    void* p = nullptr; cudaDriverEntryPointQueryResult st;
    cudaGetDriverEntryPoint("cuTensorMapEncodeTiled", &p, cudaEnableDefault, &st);
    fn = (EncodeFn)p;
  }
  return fn;
}
static CUtensorMap make_map(const void* ptr, int rows, int cols, int box_rows, int box_cols = 64) {
  CUtensorMap m;
  cuuint64_t dims[2] = {(cuuint64_t)cols, (cuuint64_t)rows};
  cuuint64_t strides[1] = {(cuuint64_t)cols * 2};
  cuuint32_t box[2] = {(cuuint32_t)box_cols, (cuuint32_t)box_rows};
  cuuint32_t es[2] = {1, 1};
  get_encode()(&m, CU_TENSOR_MAP_DATA_TYPE_BFLOAT16, 2, const_cast<void*>(ptr), dims, strides, box, es, CU_TENSOR_MAP_INTERLEAVE_NONE,
               box_cols == 64 ? CU_TENSOR_MAP_SWIZZLE_128B : (box_cols == 32 ? CU_TENSOR_MAP_SWIZZLE_64B : CU_TENSOR_MAP_SWIZZLE_32B), CU_TENSOR_MAP_L2_PROMOTION_L2_128B, CU_TENSOR_MAP_FLOAT_OOB_FILL_NONE);
  return m;
}
static CUtensorMap make_map_w(const void* ptr, int rows, int cols, int bc, int nblk) {
  CUtensorMap m;
  cuuint64_t dims[3] = {(cuuint64_t)bc, (cuuint64_t)rows, (cuuint64_t)(cols / bc)};
  cuuint64_t strides[2] = {(cuuint64_t)cols * 2, (cuuint64_t)bc * 2};
  cuuint32_t box[3] = {(cuuint32_t)bc, 64, (cuuint32_t)nblk};
  cuuint32_t es[3] = {1, 1, 1};
  get_encode()(&m, CU_TENSOR_MAP_DATA_TYPE_BFLOAT16, 3, const_cast<void*>(ptr), dims, strides, box, es, CU_TENSOR_MAP_INTERLEAVE_NONE,
               bc == 64 ? CU_TENSOR_MAP_SWIZZLE_128B : (bc == 32 ? CU_TENSOR_MAP_SWIZZLE_64B : CU_TENSOR_MAP_SWIZZLE_32B),
               CU_TENSOR_MAP_L2_PROMOTION_L2_128B, CU_TENSOR_MAP_FLOAT_OOB_FILL_NONE);
  return m;
}
template <typename... KArgs, typename... Args>
static void launch(void (*kern)(KArgs...), dim3 grid, dim3 block, size_t smem, bool pdl, dim3 cluster, Args... args) {
  cudaLaunchConfig_t cfg = {};
  cfg.gridDim = grid; cfg.blockDim = block; cfg.dynamicSmemBytes = smem; cfg.stream = cudaStreamPerThread;
  cudaLaunchAttribute at[2];
  int na = 0;
  if (pdl) { at[na].id = cudaLaunchAttributeProgrammaticStreamSerialization; at[na].val.programmaticStreamSerializationAllowed = 1; na++; }
  if (cluster.x * cluster.y > 1) { at[na].id = cudaLaunchAttributeClusterDimension; at[na].val.clusterDim.x = cluster.x; at[na].val.clusterDim.y = cluster.y; at[na].val.clusterDim.z = 1; na++; }
  cfg.attrs = at; cfg.numAttrs = na;
  cudaLaunchKernelEx(&cfg, kern, KArgs(args)...);
}

extern "C" void kernel_launch(void* const* d_in, const int* in_sizes, int n_in, void* d_out, int out_size) {
  const __nv_bfloat16* x = (const __nv_bfloat16*)d_in[0];
  const __nv_bfloat16* wqkv = (const __nv_bfloat16*)d_in[1];
  const __nv_bfloat16* wo = (const __nv_bfloat16*)d_in[2];
  const __nv_bfloat16* wgate = (const __nv_bfloat16*)d_in[4];
  const __nv_bfloat16* wup = (const __nv_bfloat16*)d_in[5];
  const __nv_bfloat16* wdown = (const __nv_bfloat16*)d_in[6];
  __nv_bfloat16* out = (__nv_bfloat16*)d_out;
  void *p_o, *p_h, *p_act;
  cudaGetSymbolAddress(&p_o, g_o); cudaGetSymbolAddress(&p_h, g_h); cudaGetSymbolAddress(&p_act, g_act);

#define A_CN 1
#define A_CM 1
#define D_CN 1
#define D_CM 1
  auto kA = gemm_kernel<256, 128, 1, DM, 4, EPI_QKV, 1, A_CN, A_CM>;
  auto kC = gemm_res_kernel<DM, true>;
  auto kD = gemm_kernel<128, 192, 2, DM, 3, EPI_GLU, 1, D_CN, D_CM>;
  auto kE = gemm_res_kernel<DFF, false>;
  constexpr int smA = GemmCfg<256, 128, 1, 4>::SMEM, smC = R_SMEM, smD = GemmCfg<128, 192, 2, 3>::SMEM;
  cudaFuncSetAttribute(kA, cudaFuncAttributeMaxDynamicSharedMemorySize, smA);
  cudaFuncSetAttribute(kC, cudaFuncAttributeMaxDynamicSharedMemorySize, smC);
  cudaFuncSetAttribute(kD, cudaFuncAttributeMaxDynamicSharedMemorySize, smD);
  cudaFuncSetAttribute(kE, cudaFuncAttributeMaxDynamicSharedMemorySize, smC);
  cudaFuncSetAttribute(attn_kernel, cudaFuncAttributeMaxDynamicSharedMemorySize, ATT_SMEM);

  const CUtensorMap tm_x = make_map(x, S_LEN, DM, 256), tm_wqkv = make_map_w(wqkv, DM, 3 * DM, 64, 2);
  const CUtensorMap tm_o = make_map(p_o, S_LEN, DM, 128), tm_wo = make_map_w(wo, DM, DM, 16, 5);
  const CUtensorMap tm_h = make_map(p_h, S_LEN, DM, 128), tm_wg = make_map_w(wgate, DM, DFF, 64, 3), tm_wu = make_map_w(wup, DM, DFF, 64, 3);
  const CUtensorMap tm_act = make_map(p_act, S_LEN, DFF, 128), tm_wd = make_map_w(wdown, DFF, DM, 16, 5);

  launch(pre_kernel, dim3(12), dim3(1024), 0, false, dim3(1, 1), x, wqkv);
  launch(kA, dim3(15, 8), dim3(288), smA, true, dim3(A_CN, A_CM), tm_x, tm_wqkv, tm_wqkv, x, (__nv_bfloat16*)wqkv);
  launch(attn_kernel, dim3(132), dim3(512), ATT_SMEM, true, dim3(1, 1), 0x800000, wgate, wup, tm_wo, tm_wd);
  launch(kC, dim3(8, 16), dim3(288), smC, true, dim3(1, 1), tm_o, tm_wo, x, (__nv_bfloat16*)p_h);
  launch(kD, dim3(8, 16), dim3(384), smD, true, dim3(D_CN, D_CM), tm_h, tm_wg, tm_wu, (const __nv_bfloat16*)nullptr, (__nv_bfloat16*)p_act);
  launch(kE, dim3(8, 16), dim3(288), smC, true, dim3(1, 1), tm_act, tm_wd, (const __nv_bfloat16*)p_h, out);
}
```

```cpp
#include <cuda_runtime.h>
#include <cuda_bf16.h>
#include <cuda.h>
#include <stdint.h>

constexpr int S_LEN = 2048, DM = 640, NH = 32, DH = 20, DFF = 1536;

__device__ __align__(1024) __nv_bfloat16 g_q[NH * S_LEN * 32];
__device__ __align__(1024) __nv_bfloat16 g_k[NH * S_LEN * 24];
__device__ __align__(1024) __nv_bfloat16 g_v[NH * S_LEN * 24];
__device__ __align__(1024) __nv_bfloat16 g_o[S_LEN * DM];
__device__ __align__(1024) __nv_bfloat16 g_h[S_LEN * DM];
__device__ __align__(1024) __nv_bfloat16 g_act[S_LEN * DFF];
__device__ __align__(1024) __nv_bfloat16 g_wo_t[DM * DM];
__device__ __align__(1024) __nv_bfloat16 g_wd_t[DFF * DM];
__device__ float g_kn[8 * NH * 2];
__device__ float2 g_stat1[S_LEN];
__device__ float g_cs_qkv[3 * DM];
__device__ float g_cs_g[DFF];
__device__ float g_cs_u[DFF];
__device__ float2 g_part2[S_LEN * 8];

#define TS_BEGIN(k)
#define TS_END(k)
#define TS_MID(k, i)
__device__ __forceinline__ uint32_t smem_u32(const void* p) { return (uint32_t)__cvta_generic_to_shared(p); }
__device__ __forceinline__ void mbar_init(uint32_t bar, uint32_t cnt) { asm volatile("mbarrier.init.shared::cta.b64 [%0], %1;" :: "r"(bar), "r"(cnt)); }
__device__ __forceinline__ void mbar_expect_tx(uint32_t bar, uint32_t bytes) { asm volatile("mbarrier.arrive.expect_tx.shared::cta.b64 _, [%0], %1;" :: "r"(bar), "r"(bytes) : "memory"); }
__device__ __forceinline__ void mbar_arrive(uint32_t bar) { asm volatile("mbarrier.arrive.shared::cta.b64 _, [%0];" :: "r"(bar) : "memory"); }
__device__ __forceinline__ void mbar_wait(uint32_t bar, uint32_t parity) {
  uint32_t done;
  uint32_t spins = 0;
  do {
    asm volatile("{\n.reg .pred P1;\nmbarrier.try_wait.parity.shared::cta.b64 P1, [%1], %2;\nselp.u32 %0, 1, 0, P1;\n}" : "=r"(done) : "r"(bar), "r"(parity) : "memory");
  } while (!done && ++spins < (1u << 24));
}
__device__ __forceinline__ void bulk_g2s(uint32_t dst, const void* src, uint32_t bytes, uint32_t bar) {
  asm volatile("cp.async.bulk.shared::cluster.global.mbarrier::complete_tx::bytes [%0], [%1], %2, [%3];" :: "r"(dst), "l"(src), "r"(bytes), "r"(bar) : "memory");
}
__device__ __forceinline__ void tma_2d(uint32_t dst, const CUtensorMap* tm, int c0, int c1, uint32_t bar) {
  asm volatile("cp.async.bulk.tensor.2d.shared::cluster.global.mbarrier::complete_tx::bytes [%0], [%1, {%3, %4}], [%2];"
               :: "r"(dst), "l"(tm), "r"(bar), "r"(c0), "r"(c1) : "memory");
}
__device__ __forceinline__ void tma_3d(uint32_t dst, const CUtensorMap* tm, int c0, int c1, int c2, uint32_t bar) {
  asm volatile("cp.async.bulk.tensor.3d.shared::cluster.global.mbarrier::complete_tx::bytes [%0], [%1, {%3, %4, %5}], [%2];"
               :: "r"(dst), "l"(tm), "r"(bar), "r"(c0), "r"(c1), "r"(c2) : "memory");
}
__device__ __forceinline__ void wgmma_fence() { asm volatile("wgmma.fence.sync.aligned;" ::: "memory"); }
__device__ __forceinline__ void wgmma_commit() { asm volatile("wgmma.commit_group.sync.aligned;" ::: "memory"); }
template <int N> __device__ __forceinline__ void wgmma_wait() { asm volatile("wgmma.wait_group.sync.aligned %0;" :: "n"(N) : "memory"); }
__device__ __forceinline__ void pdl_wait() { asm volatile("griddepcontrol.wait;" ::: "memory"); }
__device__ __forceinline__ void pdl_launch() { asm volatile("griddepcontrol.launch_dependents;" ::: "memory"); }
__device__ __forceinline__ void named_bar(int id, int n) { asm volatile("bar.sync %0, %1;" :: "r"(id), "r"(n) : "memory"); }
__device__ __forceinline__ uint64_t make_desc(uint32_t addr, uint32_t lbo, uint32_t sbo, uint32_t swz) {
  return (uint64_t)((addr & 0x3FFFF) >> 4) | ((uint64_t)(lbo >> 4) << 16) | ((uint64_t)(sbo >> 4) << 32) | ((uint64_t)swz << 62);
}
__device__ __forceinline__ void st_g16(void* p, uint4 v) { asm volatile("st.global.v4.b32 [%0], {%1, %2, %3, %4};" :: "l"(p), "r"(v.x), "r"(v.y), "r"(v.z), "r"(v.w) : "memory"); }
__device__ __forceinline__ void st_g8(void* p, uint2 v) { asm volatile("st.global.v2.b32 [%0], {%1, %2};" :: "l"(p), "r"(v.x), "r"(v.y) : "memory"); }
__device__ __forceinline__ uint4 ld_g16(const void* p) { uint4 v; asm volatile("ld.global.v4.b32 {%0, %1, %2, %3}, [%4];" : "=r"(v.x), "=r"(v.y), "=r"(v.z), "=r"(v.w) : "l"(p) : "memory"); return v; }
__device__ __forceinline__ uint32_t pack_bf16(float lo, float hi) { uint32_t r; asm("cvt.rn.bf16x2.f32 %0, %1, %2;" : "=r"(r) : "f"(hi), "f"(lo)); return r; }
__device__ __forceinline__ float bf_lo(uint32_t u) { return __uint_as_float(u << 16); }
__device__ __forceinline__ float bf_hi(uint32_t u) { return __uint_as_float(u & 0xffff0000u); }
__device__ __forceinline__ float bf_round(float x) { return __bfloat162float(__float2bfloat16_rn(x)); }
__device__ __forceinline__ float ex2_mufu(float x) { float y; asm("ex2.approx.ftz.f32 %0, %1;" : "=f"(y) : "f"(x)); return y; }

__device__ __forceinline__ void wgmma_ss_n80(float (&d)[40], uint64_t da, uint64_t db, int scale_d) {
  asm volatile("{\n.reg .pred p;\nsetp.ne.b32 p, %42, 0;\n"
    "wgmma.mma_async.sync.aligned.m64n80k16.f32.bf16.bf16 {%0,%1,%2,%3,%4,%5,%6,%7,%8,%9,%10,%11,%12,%13,%14,%15,%16,%17,%18,%19,%20,%21,%22,%23,%24,%25,%26,%27,%28,%29,%30,%31,%32,%33,%34,%35,%36,%37,%38,%39}, %40, %41, p, 1, 1, 0, 1;\n}\n"
    : "+f"(d[0]),"+f"(d[1]),"+f"(d[2]),"+f"(d[3]),"+f"(d[4]),"+f"(d[5]),"+f"(d[6]),"+f"(d[7]),"+f"(d[8]),"+f"(d[9]),"+f"(d[10]),"+f"(d[11]),"+f"(d[12]),"+f"(d[13]),"+f"(d[14]),"+f"(d[15]),"+f"(d[16]),"+f"(d[17]),"+f"(d[18]),"+f"(d[19]),"+f"(d[20]),"+f"(d[21]),"+f"(d[22]),"+f"(d[23]),"+f"(d[24]),"+f"(d[25]),"+f"(d[26]),"+f"(d[27]),"+f"(d[28]),"+f"(d[29]),"+f"(d[30]),"+f"(d[31]),"+f"(d[32]),"+f"(d[33]),"+f"(d[34]),"+f"(d[35]),"+f"(d[36]),"+f"(d[37]),"+f"(d[38]),"+f"(d[39])
    : "l"(da), "l"(db), "r"(scale_d));
}
__device__ __forceinline__ void wgmma_ss_n128(float (&d)[64], uint64_t da, uint64_t db, int scale_d) {
  asm volatile("{\n.reg .pred p;\nsetp.ne.b32 p, %66, 0;\n"
    "wgmma.mma_async.sync.aligned.m64n128k16.f32.bf16.bf16 {%0,%1,%2,%3,%4,%5,%6,%7,%8,%9,%10,%11,%12,%13,%14,%15,%16,%17,%18,%19,%20,%21,%22,%23,%24,%25,%26,%27,%28,%29,%30,%31,%32,%33,%34,%35,%36,%37,%38,%39,%40,%41,%42,%43,%44,%45,%46,%47,%48,%49,%50,%51,%52,%53,%54,%55,%56,%57,%58,%59,%60,%61,%62,%63}, %64, %65, p, 1, 1, 0, 1;\n}\n"
    : "+f"(d[0]),"+f"(d[1]),"+f"(d[2]),"+f"(d[3]),"+f"(d[4]),"+f"(d[5]),"+f"(d[6]),"+f"(d[7]),"+f"(d[8]),"+f"(d[9]),"+f"(d[10]),"+f"(d[11]),"+f"(d[12]),"+f"(d[13]),"+f"(d[14]),"+f"(d[15]),"+f"(d[16]),"+f"(d[17]),"+f"(d[18]),"+f"(d[19]),"+f"(d[20]),"+f"(d[21]),"+f"(d[22]),"+f"(d[23]),"+f"(d[24]),"+f"(d[25]),"+f"(d[26]),"+f"(d[27]),"+f"(d[28]),"+f"(d[29]),"+f"(d[30]),"+f"(d[31]),"+f"(d[32]),"+f"(d[33]),"+f"(d[34]),"+f"(d[35]),"+f"(d[36]),"+f"(d[37]),"+f"(d[38]),"+f"(d[39]),"+f"(d[40]),"+f"(d[41]),"+f"(d[42]),"+f"(d[43]),"+f"(d[44]),"+f"(d[45]),"+f"(d[46]),"+f"(d[47]),"+f"(d[48]),"+f"(d[49]),"+f"(d[50]),"+f"(d[51]),"+f"(d[52]),"+f"(d[53]),"+f"(d[54]),"+f"(d[55]),"+f"(d[56]),"+f"(d[57]),"+f"(d[58]),"+f"(d[59]),"+f"(d[60]),"+f"(d[61]),"+f"(d[62]),"+f"(d[63])
    : "l"(da), "l"(db), "r"(scale_d));
}
__device__ __forceinline__ void wgmma_ss_n192(float (&d)[96], uint64_t da, uint64_t db, int scale_d) {
  asm volatile("{\n.reg .pred p;\nsetp.ne.b32 p, %98, 0;\n"
    "wgmma.mma_async.sync.aligned.m64n192k16.f32.bf16.bf16 {%0,%1,%2,%3,%4,%5,%6,%7,%8,%9,%10,%11,%12,%13,%14,%15,%16,%17,%18,%19,%20,%21,%22,%23,%24,%25,%26,%27,%28,%29,%30,%31,%32,%33,%34,%35,%36,%37,%38,%39,%40,%41,%42,%43,%44,%45,%46,%47,%48,%49,%50,%51,%52,%53,%54,%55,%56,%57,%58,%59,%60,%61,%62,%63,%64,%65,%66,%67,%68,%69,%70,%71,%72,%73,%74,%75,%76,%77,%78,%79,%80,%81,%82,%83,%84,%85,%86,%87,%88,%89,%90,%91,%92,%93,%94,%95}, %96, %97, p, 1, 1, 0, 1;\n}\n"
    : "+f"(d[0]),"+f"(d[1]),"+f"(d[2]),"+f"(d[3]),"+f"(d[4]),"+f"(d[5]),"+f"(d[6]),"+f"(d[7]),"+f"(d[8]),"+f"(d[9]),"+f"(d[10]),"+f"(d[11]),"+f"(d[12]),"+f"(d[13]),"+f"(d[14]),"+f"(d[15]),"+f"(d[16]),"+f"(d[17]),"+f"(d[18]),"+f"(d[19]),"+f"(d[20]),"+f"(d[21]),"+f"(d[22]),"+f"(d[23]),"+f"(d[24]),"+f"(d[25]),"+f"(d[26]),"+f"(d[27]),"+f"(d[28]),"+f"(d[29]),"+f"(d[30]),"+f"(d[31]),"+f"(d[32]),"+f"(d[33]),"+f"(d[34]),"+f"(d[35]),"+f"(d[36]),"+f"(d[37]),"+f"(d[38]),"+f"(d[39]),"+f"(d[40]),"+f"(d[41]),"+f"(d[42]),"+f"(d[43]),"+f"(d[44]),"+f"(d[45]),"+f"(d[46]),"+f"(d[47]),"+f"(d[48]),"+f"(d[49]),"+f"(d[50]),"+f"(d[51]),"+f"(d[52]),"+f"(d[53]),"+f"(d[54]),"+f"(d[55]),"+f"(d[56]),"+f"(d[57]),"+f"(d[58]),"+f"(d[59]),"+f"(d[60]),"+f"(d[61]),"+f"(d[62]),"+f"(d[63]),"+f"(d[64]),"+f"(d[65]),"+f"(d[66]),"+f"(d[67]),"+f"(d[68]),"+f"(d[69]),"+f"(d[70]),"+f"(d[71]),"+f"(d[72]),"+f"(d[73]),"+f"(d[74]),"+f"(d[75]),"+f"(d[76]),"+f"(d[77]),"+f"(d[78]),"+f"(d[79]),"+f"(d[80]),"+f"(d[81]),"+f"(d[82]),"+f"(d[83]),"+f"(d[84]),"+f"(d[85]),"+f"(d[86]),"+f"(d[87]),"+f"(d[88]),"+f"(d[89]),"+f"(d[90]),"+f"(d[91]),"+f"(d[92]),"+f"(d[93]),"+f"(d[94]),"+f"(d[95])
    : "l"(da), "l"(db), "r"(scale_d));
}
__device__ __forceinline__ void wgmma_ss_n64_k(float (&d)[32], uint64_t da, uint64_t db, int scale_d) {
  asm volatile("{\n.reg .pred p;\nsetp.ne.b32 p, %34, 0;\n"
    "wgmma.mma_async.sync.aligned.m64n64k16.f32.bf16.bf16 {%0,%1,%2,%3,%4,%5,%6,%7,%8,%9,%10,%11,%12,%13,%14,%15,%16,%17,%18,%19,%20,%21,%22,%23,%24,%25,%26,%27,%28,%29,%30,%31}, %32, %33, p, 1, 1, 0, 0;\n}\n"
    : "+f"(d[0]),"+f"(d[1]),"+f"(d[2]),"+f"(d[3]),"+f"(d[4]),"+f"(d[5]),"+f"(d[6]),"+f"(d[7]),"+f"(d[8]),"+f"(d[9]),"+f"(d[10]),"+f"(d[11]),"+f"(d[12]),"+f"(d[13]),"+f"(d[14]),"+f"(d[15]),"+f"(d[16]),"+f"(d[17]),"+f"(d[18]),"+f"(d[19]),"+f"(d[20]),"+f"(d[21]),"+f"(d[22]),"+f"(d[23]),"+f"(d[24]),"+f"(d[25]),"+f"(d[26]),"+f"(d[27]),"+f"(d[28]),"+f"(d[29]),"+f"(d[30]),"+f"(d[31])
    : "l"(da), "l"(db), "r"(scale_d));
}
__device__ __forceinline__ void wgmma_rs_n24_tb(float (&d)[12], uint32_t a0, uint32_t a1, uint32_t a2, uint32_t a3, uint64_t db, int scale_d) {
  asm volatile("{\n.reg .pred p;\nsetp.ne.b32 p, %17, 0;\n"
    "wgmma.mma_async.sync.aligned.m64n24k16.f32.bf16.bf16 {%0,%1,%2,%3,%4,%5,%6,%7,%8,%9,%10,%11}, {%12,%13,%14,%15}, %16, p, 1, 1, 1;\n}\n"
    : "+f"(d[0]),"+f"(d[1]),"+f"(d[2]),"+f"(d[3]),"+f"(d[4]),"+f"(d[5]),"+f"(d[6]),"+f"(d[7]),"+f"(d[8]),"+f"(d[9]),"+f"(d[10]),"+f"(d[11])
    : "r"(a0), "r"(a1), "r"(a2), "r"(a3), "l"(db), "r"(scale_d));
}

__device__ __forceinline__ float2 ln_finish(float mean, float var) {
  float mb = bf_round(mean);
  float s = bf_round(sqrtf(bf_round(bf_round(var) + 1e-5f)));
  return make_float2(mb, 1.0f / s);
}
__device__ __forceinline__ void colsum64(const __nv_bfloat16* __restrict__ w, int ld, int c0, float* __restrict__ dst, float (*red)[65], int tid, int bar_id) {
  const int cg = tid & 7, r0 = tid >> 3;
  float acc[8];
#pragma unroll
  for (int i = 0; i < 8; i++) acc[i] = 0.f;
#pragma unroll 10
  for (int r = r0; r < DM; r += 32) {
    uint4 v = __ldg((const uint4*)(w + (size_t)r * ld + c0 + cg * 8));
    acc[0] += bf_lo(v.x); acc[1] += bf_hi(v.x); acc[2] += bf_lo(v.y); acc[3] += bf_hi(v.y);
    acc[4] += bf_lo(v.z); acc[5] += bf_hi(v.z); acc[6] += bf_lo(v.w); acc[7] += bf_hi(v.w);
  }
#pragma unroll
  for (int i = 0; i < 8; i++) red[r0][cg * 8 + i] = acc[i];
  named_bar(bar_id, 256);
  if (tid < 64) {
    float s = 0.f;
#pragma unroll
    for (int r = 0; r < 32; r++) s += red[r][tid];
    dst[c0 + tid] = s;
  }
  named_bar(bar_id, 256);
}
__global__ void __launch_bounds__(1024) pre_kernel(const __nv_bfloat16* __restrict__ x, const __nv_bfloat16* __restrict__ wqkv) {
  TS_BEGIN(0);
  pdl_launch();
  __shared__ float red[51][161];
  const int tid = threadIdx.x, lane = tid & 31, warp = tid >> 5;
  {
    const int ch = tid % 20, rl = tid / 20;
    if (rl < 51) {
      const __nv_bfloat16* w = wqkv + blockIdx.x * 160 + ch * 8;
      uint4 v[13];
#pragma unroll
      for (int i = 0; i < 13; i++) { const int r = rl + i * 51; v[i] = r < DM ? __ldg((const uint4*)(w + (size_t)r * (3 * DM))) : make_uint4(0, 0, 0, 0); }
      float acc[8];
#pragma unroll
      for (int i = 0; i < 8; i++) acc[i] = 0.f;
#pragma unroll
      for (int i = 0; i < 13; i++) {
        acc[0] += bf_lo(v[i].x); acc[1] += bf_hi(v[i].x); acc[2] += bf_lo(v[i].y); acc[3] += bf_hi(v[i].y);
        acc[4] += bf_lo(v[i].z); acc[5] += bf_hi(v[i].z); acc[6] += bf_lo(v[i].w); acc[7] += bf_hi(v[i].w);
      }
#pragma unroll
      for (int i = 0; i < 8; i++) red[rl][ch * 8 + i] = acc[i];
    }
  }
  const int rbeg = blockIdx.x * 171, rend = min(rbeg + 171, S_LEN);
  for (int row0 = rbeg + warp * 2; row0 < rend; row0 += 64) {
    uint4 v[2][3];
#pragma unroll
    for (int k = 0; k < 2; k++) {
      const int row = min(row0 + k, rend - 1);
      const uint4* p = (const uint4*)(x + (size_t)row * DM);
      v[k][0] = __ldg(p + lane); v[k][1] = __ldg(p + 32 + lane);
      v[k][2] = lane < 16 ? __ldg(p + 64 + lane) : make_uint4(0, 0, 0, 0);
    }
#pragma unroll
    for (int k = 0; k < 2; k++) {
      float f[24];
      const uint32_t u[12] = {v[k][0].x, v[k][0].y, v[k][0].z, v[k][0].w, v[k][1].x, v[k][1].y, v[k][1].z, v[k][1].w, v[k][2].x, v[k][2].y, v[k][2].z, v[k][2].w};
#pragma unroll
      for (int j = 0; j < 12; j++) { f[2 * j] = bf_lo(u[j]); f[2 * j + 1] = bf_hi(u[j]); }
      float s = 0.f;
#pragma unroll
      for (int j = 0; j < 24; j++) s += f[j];
#pragma unroll
      for (int o = 16; o; o >>= 1) s += __shfl_xor_sync(~0u, s, o);
      const float mean = s * (1.0f / DM);
      float q = 0.f;
#pragma unroll
      for (int j = 0; j < 16; j++) { const float d = f[j] - mean; q += d * d; }
      if (lane < 16) {
#pragma unroll
        for (int j = 16; j < 24; j++) { const float d = f[j] - mean; q += d * d; }
      }
#pragma unroll
      for (int o = 16; o; o >>= 1) q += __shfl_xor_sync(~0u, q, o);
      if (lane == 0 && row0 + k < rend) g_stat1[row0 + k] = ln_finish(mean, q * (1.0f / DM));
    }
  }
  __syncthreads();
  if (tid < 160) {
    float s = 0.f;
#pragma unroll 17
    for (int r = 0; r < 51; r++) s += red[r][tid];
    g_cs_qkv[blockIdx.x * 160 + tid] = s;
  }
  TS_END(0);
}

enum { EPI_QKV = 0, EPI_GLU = 2 };
template <int N> struct WG;
template <> struct WG<128> { static __device__ __forceinline__ void mma(float (&d)[64], uint64_t a, uint64_t b, int s) { wgmma_ss_n128(d, a, b, s); } };
template <> struct WG<192> { static __device__ __forceinline__ void mma(float (&d)[96], uint64_t a, uint64_t b, int s) { wgmma_ss_n192(d, a, b, s); } };

template <int BM, int BN, int NB, int STAGES> struct GemmCfg {
  static constexpr int A_BYTES = BM * 128;
  static constexpr int B_BYTES = NB * (BN / 64) * 8192;
  static constexpr int STAGE_BYTES = A_BYTES + B_BYTES;
  static constexpr int SMEM = STAGES * STAGE_BYTES + 1024   + 256   + 4096  ;
};

constexpr float QSCALE = 0.22360679774997896f * 1.4426950408889634f;

template <int BM, int BN, int NB, int KDIM, int STAGES, int EPI>
__global__ void __launch_bounds__(EPI == EPI_GLU ? 384 : 288, 1) gemm_kernel(const __grid_constant__ CUtensorMap tmA, const __grid_constant__ CUtensorMap tmB0,
                                                         const __grid_constant__ CUtensorMap tmB1, __nv_bfloat16* out) {
  using Cfg = GemmCfg<BM, BN, NB, STAGES>;
  constexpr int MB = BM / 128;
  constexpr int KT = KDIM / 64;
  extern __shared__ uint8_t smem_raw[];
  const uint32_t sbase = (smem_u32(smem_raw) + 1023u) & ~1023u;
  uint8_t* sptr = smem_raw + (sbase - smem_u32(smem_raw));
  const uint32_t sbar = sbase + STAGES * Cfg::STAGE_BYTES;
  const int tid = threadIdx.x, warp = tid >> 5, lane = tid & 31;
  const int n0 = blockIdx.x * BN, m0 = blockIdx.y * BM;
  TS_BEGIN(EPI == EPI_QKV ? 1 : EPI + 2);
  TS_MID(EPI == EPI_QKV ? 1 : EPI + 2, 3);
  if (tid == 0) {
    for (int i = 0; i < STAGES; i++) { mbar_init(sbar + 8 * i, 1); mbar_init(sbar + 8 * (STAGES + i), 8); }
    asm volatile("fence.mbarrier_init.release.cluster;" ::: "memory");
  }
  __syncthreads();
  pdl_launch();
  if (warp >= 8) {
    if constexpr (EPI == EPI_GLU) asm volatile("setmaxnreg.dec.sync.aligned.u32 40;");
    if (warp == 8 && lane == 0) {
      auto load_a = [&](int kt, int s) { tma_2d(sbase + s * Cfg::STAGE_BYTES, &tmA, kt * 64, m0, sbar + 8 * s); };
      auto load_b = [&](int kt, int s) {
        const uint32_t sb = sbase + s * Cfg::STAGE_BYTES + Cfg::A_BYTES;
        tma_3d(sb, &tmB0, 0, kt * 64, blockIdx.x * (BN / 64), sbar + 8 * s);
        if constexpr (NB == 2) tma_3d(sb + (BN / 64) * 8192, &tmB1, 0, kt * 64, blockIdx.x * (BN / 64), sbar + 8 * s);
      };
      for (int s = 0; s < STAGES; s++) { mbar_expect_tx(sbar + 8 * s, Cfg::STAGE_BYTES); if (s == 0) load_b(s, s); }
      if (EPI != EPI_QKV) pdl_wait();
      for (int s = 0; s < STAGES; s++) { load_a(s, s); if (s > 0) load_b(s, s); }
      for (int kt = STAGES; kt < KT; kt++) {
        const int s = kt % STAGES;
        mbar_wait(sbar + 8 * (STAGES + s), ((kt / STAGES) - 1) & 1);
        mbar_expect_tx(sbar + 8 * s, Cfg::STAGE_BYTES);
        load_a(kt, s);
        load_b(kt, s);
      }
    }
    if constexpr (EPI == EPI_GLU) {
      if (warp > 8) {
        float2* s_st = (float2*)(sptr + STAGES * Cfg::STAGE_BYTES + 256);
        float* s_cs = (float*)(sptr + STAGES * Cfg::STAGE_BYTES + 256 + 1024);
        pdl_wait();
        for (int r = tid - 288; r < BM; r += 96) {
          const float2* pp = &g_part2[(m0 + r) * 8];
          float s = 0.f;
#pragma unroll
          for (int i = 0; i < 8; i++) s += pp[i].x;
          const float mean = s * (1.0f / DM);
          float q = 0.f;
#pragma unroll
          for (int i = 0; i < 8; i++) { const float2 p = pp[i]; const float d = p.x * (1.0f / 80.f) - mean; q += p.y + 80.f * d * d; }
          s_st[r] = ln_finish(mean, q * (1.0f / DM));
        }
        for (int c = tid - 288; c < BN; c += 96) { s_cs[c] = g_cs_g[n0 + c]; s_cs[BN + c] = g_cs_u[n0 + c]; }
        __threadfence_block();
        asm volatile("bar.arrive 2, 352;" ::: "memory");
      }
    }
    return;
  }
  if constexpr (EPI == EPI_GLU) asm volatile("setmaxnreg.inc.sync.aligned.u32 232;");
  const int wg = warp >> 2, g = lane >> 2, t = lane & 3;
  float acc[MB][NB][BN / 2];
#pragma unroll
  for (int mb = 0; mb < MB; mb++)
#pragma unroll
    for (int nb = 0; nb < NB; nb++)
#pragma unroll
      for (int i = 0; i < BN / 2; i++) acc[mb][nb][i] = 0.f;
  for (int kt = 0; kt < KT; kt++) {
    const int s = kt % STAGES;
    mbar_wait(sbar + 8 * s, (kt / STAGES) & 1);
    if (kt == 0) TS_MID(EPI == EPI_QKV ? 1 : EPI + 2, 0);
    const uint32_t sa = sbase + s * Cfg::STAGE_BYTES + wg * (MB * 64 * 128);
    const uint32_t sb = sbase + s * Cfg::STAGE_BYTES + Cfg::A_BYTES;
    wgmma_fence();
#pragma unroll
    for (int ks = 0; ks < 4; ks++) {
#pragma unroll
      for (int mb = 0; mb < MB; mb++) {
        const uint64_t da = make_desc(sa + mb * 8192 + ks * 32, 16, 1024, 1);
#pragma unroll
        for (int nb = 0; nb < NB; nb++) {
          const uint64_t db = make_desc(sb + nb * (BN / 64) * 8192 + ks * 2048, 8192, 1024, 1);
          WG<BN>::mma(acc[mb][nb], da, db, 1);
        }
      }
    }
    wgmma_commit();
    wgmma_wait<1>();
    if (kt > 0 && kt - 1 + STAGES < KT && lane == 0) mbar_arrive(sbar + 8 * (STAGES + (kt - 1) % STAGES));
  }
  wgmma_wait<0>();
#pragma unroll
  for (int mb = 0; mb < MB; mb++)
#pragma unroll
    for (int nb = 0; nb < NB; nb++)
#pragma unroll
      for (int i = 0; i < BN / 2; i++) asm volatile("" : "+f"(acc[mb][nb][i]) :: "memory");
  TS_MID(EPI == EPI_QKV ? 1 : EPI + 2, 1);
  pdl_wait();
  TS_MID(EPI == EPI_QKV ? 1 : EPI + 2, 2);
  named_bar(1, 256);
  constexpr int LDS = BN * 2 + 16;
  const int ctid = tid;

  if constexpr (EPI == EPI_QKV) {
    const int sec = n0 / DM;
    constexpr int lds = 264;
    __shared__ unsigned int s_kn[8];
    if (ctid < 8) s_kn[ctid] = 0u;
    float2 cs[BN / 8];
#pragma unroll
    for (int j = 0; j < BN / 8; j++) cs[j] = *(const float2*)&g_cs_qkv[n0 + j * 8 + 2 * t];
#pragma unroll
    for (int mb = 0; mb < MB; mb++) {
      const int r0 = wg * (MB * 64) + mb * 64 + (warp & 3) * 16 + g;
      const float2 st0 = g_stat1[m0 + r0], st1 = g_stat1[m0 + r0 + 8];
      const float sc0 = sec == 0 ? st0.y * QSCALE : st0.y, sc1 = sec == 0 ? st1.y * QSCALE : st1.y;
#pragma unroll
      for (int j = 0; j < BN / 8; j++) {
        const float* a = &acc[mb][0][4 * j];
        *(uint32_t*)(sptr + r0 * lds + j * 16 + t * 4) = pack_bf16(fmaf(-st0.x, cs[j].x, a[0]) * sc0, fmaf(-st0.x, cs[j].y, a[1]) * sc0);
        *(uint32_t*)(sptr + (r0 + 8) * lds + j * 16 + t * 4) = pack_bf16(fmaf(-st1.x, cs[j].x, a[2]) * sc1, fmaf(-st1.x, cs[j].y, a[3]) * sc1);
      }
    }
    named_bar(1, 256);
    {
      const int cbase = n0 - sec * DM;
      const int hfirst = cbase / DH;
      const int j = m0 + ctid;
      uint8_t* dst = (uint8_t*)(sec == 0 ? g_q : (sec == 1 ? g_k : g_v)) + (size_t)(j >> 3) * (sec == 0 ? 512 : 384) + (j & 7) * 16;
      const uint8_t* row = sptr + ctid * 264;
#pragma unroll
      for (int i = 0; i < 8; i++) {
        const int hh = hfirst + i;
        const int cr = hh * DH - cbase;
        if (cr < BN) {
          uint2 v[5];
          bool in[5];
          float s = 0.f;
#pragma unroll
          for (int qd = 0; qd < 5; qd++) {
            const int c = cr + 4 * qd;
            in[qd] = c >= 0 && c < BN;
            v[qd] = in[qd] ? *(const uint2*)(row + c * 2) : make_uint2(0u, 0u);
            s += bf_lo(v[qd].x) * bf_lo(v[qd].x) + bf_hi(v[qd].x) * bf_hi(v[qd].x) + bf_lo(v[qd].y) * bf_lo(v[qd].y) + bf_hi(v[qd].y) * bf_hi(v[qd].y);
          }
          uint8_t* p = dst + (size_t)hh * (sec == 0 ? S_LEN * 64 : S_LEN * 48);
          if (in[0] && in[1]) st_g16(p, make_uint4(v[0].x, v[0].y, v[1].x, v[1].y));
          else if (in[0]) st_g8(p, v[0]);
          else if (in[1]) st_g8(p + 8, v[1]);
          if (in[2] && in[3]) st_g16(p + 128, make_uint4(v[2].x, v[2].y, v[3].x, v[3].y));
          else if (in[2]) st_g8(p + 128, v[2]);
          else if (in[3]) st_g8(p + 136, v[3]);
          if (in[4]) {
            st_g16(p + 256, make_uint4(v[4].x, v[4].y, sec == 0 ? 0u : 0x00003f80u, 0u));
            if (sec == 0) st_g16(p + 384, make_uint4(0u, 0u, 0u, 0u));
          }
          if (sec == 1) {
            const unsigned int mxb = __reduce_max_sync(~0u, __float_as_uint(s) & 0x7fffffffu);
            if (lane == 0) atomicMax(&s_kn[i], mxb);
          }
        }
      }
      if (sec == 1) {
        named_bar(1, 256);
        const int hh = hfirst + ctid;
        if (ctid < 8 && hh * DH < cbase + BN) {
          const bool starts_here = hh * DH >= cbase, ends_here = hh * DH + DH <= cbase + BN;
          const float v = __uint_as_float(s_kn[ctid]);
          float* o = &g_kn[(blockIdx.y * NH + hh) * 2];
          if (starts_here) { o[0] = v; if (ends_here) o[1] = 0.f; }
          else o[1] = v;
        }
      }
    }
  } else {
    const int r0 = wg * 64 + (warp & 3) * 16 + g;
    const float2* s_st = (const float2*)(sptr + STAGES * Cfg::STAGE_BYTES + 256);
    const float* s_cs = (const float*)(sptr + STAGES * Cfg::STAGE_BYTES + 256 + 1024);
    named_bar(2, 352);
    float2 st[2] = {s_st[r0], s_st[r0 + 8]};
#pragma unroll
    for (int j = 0; j < BN / 8; j++) {
      const float2 cg = *(const float2*)&s_cs[j * 8 + 2 * t], cu = *(const float2*)&s_cs[BN + j * 8 + 2 * t];
      const float* a = &acc[0][0][4 * j];
      const float* b = &acc[0][1][4 * j];
#pragma unroll
      for (int e = 0; e < 2; e++) {
        const float2 s_ = st[e];
        const uint32_t gp = pack_bf16(fmaf(-s_.x, cg.x, a[2 * e]) * s_.y, fmaf(-s_.x, cg.y, a[2 * e + 1]) * s_.y);
        const uint32_t up = pack_bf16(fmaf(-s_.x, cu.x, b[2 * e]) * s_.y, fmaf(-s_.x, cu.y, b[2 * e + 1]) * s_.y);
        uint32_t r;
        asm("{\n.reg .b32 z;\nmax.bf16x2 z, %1, %3;\nmul.rn.bf16x2 %0, z, %2;\n}" : "=r"(r) : "r"(gp), "r"(up), "r"(0u));
        *(uint32_t*)(sptr + (r0 + 8 * e) * LDS + j * 16 + t * 4) = r;
      }
    }
    named_bar(1, 256);
#pragma unroll
    for (int i = 0; i < BM * (BN / 8) / 256; i++) {
      const int idx = i * 256 + ctid, r = idx / (BN / 8), c = idx % (BN / 8);
      st_g16(out + (size_t)(m0 + r) * DFF + n0 + c * 8, *(const uint4*)(sptr + r * LDS + c * 16));
    }
  }
  TS_END(EPI == EPI_QKV ? 1 : EPI + 2);
}

constexpr int R_STAGES = 8;
constexpr int R_STAGE_BYTES = 16384 + 5 * 2048;
constexpr int R_BAR_OFF = R_STAGES * R_STAGE_BYTES;
constexpr int R_SMEM = R_BAR_OFF + 256 + 1024;
template <int KDIM, bool STATS>
__global__ void __launch_bounds__(288, 1) gemm_res_kernel(const __grid_constant__ CUtensorMap tmA, const __nv_bfloat16* resid, __nv_bfloat16* out) {
  constexpr int KT = KDIM / 64;
  extern __shared__ uint8_t smem_raw[];
  const uint32_t sbase = (smem_u32(smem_raw) + 1023u) & ~1023u;
  uint8_t* sptr = smem_raw + (sbase - smem_u32(smem_raw));
  const uint32_t sbar = sbase + R_BAR_OFF;
  const int tid = threadIdx.x, warp = tid >> 5, lane = tid & 31;
  const int n0 = blockIdx.x * 80, m0 = blockIdx.y * 128;
  TS_BEGIN(STATS ? 3 : 5);
  if (tid == 0) {
    for (int i = 0; i < R_STAGES; i++) { mbar_init(sbar + 8 * i, 1); mbar_init(sbar + 8 * (R_STAGES + i), 8); }
    asm volatile("fence.mbarrier_init.release.cluster;" ::: "memory");
  }
  __syncthreads();
  pdl_launch();
  if (warp == 8) {
    if (lane == 0) {
      const uint8_t* wt = (const uint8_t*)(STATS ? g_wo_t : g_wd_t) + (size_t)blockIdx.x * KT * 10240;
      auto load_b = [&](int kt, int s) { bulk_g2s(sbase + s * R_STAGE_BYTES + 16384, wt + kt * 10240, 10240, sbar + 8 * s); };
      pdl_wait();
      for (int s = 0; s < R_STAGES; s++) { mbar_expect_tx(sbar + 8 * s, R_STAGE_BYTES); tma_2d(sbase + s * R_STAGE_BYTES, &tmA, s * 64, m0, sbar + 8 * s); load_b(s, s); }
      for (int kt = R_STAGES; kt < KT; kt++) {
        const int s = kt % R_STAGES;
        mbar_wait(sbar + 8 * (R_STAGES + s), ((kt / R_STAGES) - 1) & 1);
        mbar_expect_tx(sbar + 8 * s, R_STAGE_BYTES);
        tma_2d(sbase + s * R_STAGE_BYTES, &tmA, kt * 64, m0, sbar + 8 * s);
        load_b(kt, s);
      }
    }
    return;
  }
  const int wg = warp >> 2, g = lane >> 2, t = lane & 3;
  pdl_wait();
  uint4 rv[5];
#pragma unroll
  for (int i = 0; i < 5; i++) {
    const int idx = i * 256 + tid, r = idx / 10, c = idx % 10;
    rv[i] = ld_g16(resid + (size_t)(m0 + r) * DM + n0 + c * 8);
  }
  float acc[40];
#pragma unroll
  for (int i = 0; i < 40; i++) acc[i] = 0.f;
  for (int kt = 0; kt < KT; kt++) {
    const int s = kt % R_STAGES;
    mbar_wait(sbar + 8 * s, (kt / R_STAGES) & 1);
    if (kt == 0) TS_MID(STATS ? 3 : 5, 0);
    const uint32_t sa = sbase + s * R_STAGE_BYTES + wg * 8192;
    const uint32_t sb = sbase + s * R_STAGE_BYTES + 16384;
    wgmma_fence();
#pragma unroll
    for (int ks = 0; ks < 4; ks++)
      wgmma_ss_n80(acc, make_desc(sa + ks * 32, 16, 1024, 1), make_desc(sb + ks * 512, 2048, 256, 3), 1);
    wgmma_commit();
    wgmma_wait<1>();
    if (kt > 0 && kt - 1 + R_STAGES < KT && lane == 0) mbar_arrive(sbar + 8 * (R_STAGES + (kt - 1) % R_STAGES));
  }
  wgmma_wait<0>();
#pragma unroll
  for (int i = 0; i < 40; i++) asm volatile("" : "+f"(acc[i]) :: "memory");
  TS_MID(STATS ? 3 : 5, 1);
  named_bar(1, 256);
  constexpr int LDS = 176;
  const int r0 = wg * 64 + (warp & 3) * 16 + g;
#pragma unroll
  for (int i = 0; i < 10; i++) {
    *(uint32_t*)(sptr + r0 * LDS + i * 16 + t * 4) = pack_bf16(acc[4 * i], acc[4 * i + 1]);
    *(uint32_t*)(sptr + (r0 + 8) * LDS + i * 16 + t * 4) = pack_bf16(acc[4 * i + 2], acc[4 * i + 3]);
  }
  named_bar(1, 256);
  TS_MID(STATS ? 3 : 5, 2);
#pragma unroll
  for (int i = 0; i < 5; i++) {
    const int idx = i * 256 + tid, r = idx / 10, c = idx % 10;
    const uint4 a = *(const uint4*)(sptr + r * LDS + c * 16);
    const uint4 b = rv[i];
    uint4 o;
    o.x = pack_bf16(bf_lo(a.x) + bf_lo(b.x), bf_hi(a.x) + bf_hi(b.x));
    o.y = pack_bf16(bf_lo(a.y) + bf_lo(b.y), bf_hi(a.y) + bf_hi(b.y));
    o.z = pack_bf16(bf_lo(a.z) + bf_lo(b.z), bf_hi(a.z) + bf_hi(b.z));
    o.w = pack_bf16(bf_lo(a.w) + bf_lo(b.w), bf_hi(a.w) + bf_hi(b.w));
    st_g16(out + (size_t)(m0 + r) * DM + n0 + c * 8, o);
    if constexpr (STATS) *(uint4*)(sptr + r * LDS + c * 16) = o;
  }
  TS_MID(STATS ? 3 : 5, 3);
  if constexpr (STATS) {
    named_bar(1, 256);
    const int r = tid >> 1, hf = tid & 1;
    float f[40];
#pragma unroll
    for (int i = 0; i < 5; i++) {
      const uint4 v = *(const uint4*)(sptr + r * LDS + hf * 80 + i * 16);
      f[8 * i] = bf_lo(v.x); f[8 * i + 1] = bf_hi(v.x); f[8 * i + 2] = bf_lo(v.y); f[8 * i + 3] = bf_hi(v.y);
      f[8 * i + 4] = bf_lo(v.z); f[8 * i + 5] = bf_hi(v.z); f[8 * i + 6] = bf_lo(v.w); f[8 * i + 7] = bf_hi(v.w);
    }
    float s = 0.f;
#pragma unroll
    for (int i = 0; i < 40; i++) s += f[i];
    s += __shfl_xor_sync(~0u, s, 1);
    const float mu = s * (1.0f / 80.f);
    float q = 0.f;
#pragma unroll
    for (int i = 0; i < 40; i++) { const float d = f[i] - mu; q += d * d; }
    q += __shfl_xor_sync(~0u, q, 1);
    if (hf == 0) g_part2[(m0 + r) * 8 + blockIdx.x] = make_float2(s, q);
  }
  TS_END(STATS ? 3 : 5);
}

#define POLY_NUM 5
__device__ __forceinline__ float ex2_poly(float x, int shl23) {
  const float MAGIC = 12582912.f;
  const float tt = x + MAGIC;
  const float f = x - (tt - MAGIC);
  float p = fmaf(0.0013276472454890609f, f, 0.009675540961325169f);
  p = fmaf(p, f, 0.05550713092088699f);
  p = fmaf(p, f, 0.24022120237350464f);
  p = fmaf(p, f, 0.6931469440460205f);
  p = fmaf(p, f, 1.0000001192092896f);
  return __int_as_float(__float_as_int(tt) * shl23 + __float_as_int(p));
}
constexpr int KV_BYTES = S_LEN * 48;
constexpr int ATT_SMEM = 2 * KV_BYTES + 256 + 32768;
constexpr int ATT_BODY = 8;

__global__ void __launch_bounds__(512, 1) attn_kernel(int shl23, const __nv_bfloat16* __restrict__ wg_, const __nv_bfloat16* __restrict__ wu_,
                                                      const __grid_constant__ CUtensorMap tmWo, const __grid_constant__ CUtensorMap tmWd) {
  extern __shared__ __align__(1024) uint8_t smem[];
  if (blockIdx.x < 4) {
    pdl_launch();
    const int e = blockIdx.x, half = threadIdx.x >> 8;
    TS_MID(0, 0);
    const uint32_t sb = smem_u32(smem), bar = sb + 200 * 1024;
    auto rt_load = [&](int rd) {
      mbar_expect_tx(bar, 17 * 10240);
      for (int i = 0; i < 17; i++) {
        const int tl = e * 68 + rd * 17 + i;
        if (tl >= 80) tma_3d(sb + i * 10240, &tmWd, 0, ((tl - 80) % 24) * 64, ((tl - 80) / 24) * 5, bar);
        else tma_3d(sb + i * 10240, &tmWo, 0, (tl % 10) * 64, (tl / 10) * 5, bar);
      }
    };
    auto rt_store = [&](int rd) {
      mbar_wait(bar, rd & 1);
      for (int i = 0; i < 17; i++) {
        const int tl = e * 68 + rd * 17 + i;
        uint8_t* dst = tl >= 80 ? (uint8_t*)g_wd_t + (size_t)(tl - 80) * 10240 : (uint8_t*)g_wo_t + (size_t)tl * 10240;
        asm volatile("cp.async.bulk.global.shared::cta.bulk_group [%0], [%1], %2;" :: "l"(dst), "r"(sb + i * 10240), "r"(10240) : "memory");
      }
      asm volatile("cp.async.bulk.commit_group;" ::: "memory");
      asm volatile("cp.async.bulk.wait_group.read 0;" ::: "memory");
    };
    if (threadIdx.x == 0) {
      mbar_init(bar, 1);
      asm volatile("fence.mbarrier_init.release.cluster;" ::: "memory");
      rt_load(0);
    }
    __syncwarp();
    float (*red)[65] = (float (*)[65])(smem + 176 * 1024 + half * 10240);
    for (int i = 0; i < 6; i++) {
      const int b = e * 12 + half + 2 * i;
      if (b < 24) colsum64(wg_, DFF, b * 64, g_cs_g, red, threadIdx.x & 255, 1 + half);
      else colsum64(wu_, DFF, (b - 24) * 64, g_cs_u, red, threadIdx.x & 255, 1 + half);
      if ((i & 1) && threadIdx.x == 0) { rt_store(i >> 1); rt_load((i >> 1) + 1); }
      __syncwarp();
    }
    if (threadIdx.x == 0) { rt_store(3); asm volatile("cp.async.bulk.wait_group 0;" ::: "memory"); }
    TS_MID(0, 2);
    return;
  }
  const int h = (blockIdx.x - 4) >> 2, qb = blockIdx.x & 3;
  const uint32_t sK = smem_u32(smem), sV = sK + KV_BYTES, sBar = sV + KV_BYTES;
  const int tid = threadIdx.x;
  TS_BEGIN(2);
  if (tid == 0) {
    for (int i = 0; i < 9; i++) mbar_init(sBar + 8 * i, 1);
    asm volatile("fence.mbarrier_init.release.cluster;" ::: "memory");
  }
  __syncthreads();
  pdl_launch();
  pdl_wait();
  TS_MID(2, 0);
  const uint8_t* gk = (const uint8_t*)(g_k + (size_t)h * S_LEN * 24);
  const uint8_t* gv = (const uint8_t*)(g_v + (size_t)h * S_LEN * 24);
  auto load_kv = [&](int i0, int i1) {
    for (int i = i0; i < i1; i++) {
      mbar_expect_tx(sBar + 8 * i, 2 * 12288);
      bulk_g2s(sK + i * 12288, gk + i * 12288, 12288, sBar + 8 * i);
      bulk_g2s(sV + i * 12288, gv + i * 12288, 12288, sBar + 8 * i);
    }
  };
  if (tid == 0) {
    mbar_expect_tx(sBar + 64, 32768);
    bulk_g2s(sBar + 256, (const uint8_t*)g_q + ((size_t)h * S_LEN + qb * 512) * 64, 32768, sBar + 64);
    load_kv(0, 2);
  }
  float ka = 0.f, kb = 0.f;
#pragma unroll
  for (int i = 0; i < 8; i++) {
    const float2 v = *(const float2*)&g_kn[(i * NH + h) * 2];
    ka = (v.x > ka || v.x != v.x) ? v.x : ka;
    kb = (v.y > kb || v.y != v.y) ? v.y : kb;
  }
  bool fast;
  {
    const float kn = sqrtf(ka + kb);
    mbar_wait(sBar + 64, 0);
    if (tid == 0) load_kv(2, 8);
    uint8_t* qrow = smem + 2 * KV_BYTES + 256 + (tid >> 3) * 512 + (tid & 7) * 16;
    const uint4 c0 = *(const uint4*)qrow, c1 = *(const uint4*)(qrow + 128);
    const uint2 c2 = *(const uint2*)(qrow + 256);
    auto sq = [](uint32_t u) { const float a = bf_lo(u), b = bf_hi(u); return a * a + b * b; };
    const float n2 = sq(c0.x) + sq(c0.y) + sq(c0.z) + sq(c0.w) + sq(c1.x) + sq(c1.y) + sq(c1.z) + sq(c1.w) + sq(c2.x) + sq(c2.y);
    const float m = ceilf(sqrtf(n2) * kn * 1.001f) + 1.f;
    fast = __syncthreads_or(!(m <= 62.f)) == 0;
    if (fast) *(uint32_t*)(qrow + 256 + 8) = pack_bf16(-m, 0.f);
    asm volatile("fence.proxy.async.shared::cta;" ::: "memory");
    __syncthreads();
  }
  auto write_out = [&](float (&O)[12], int it) {
    uint32_t tid2;
    asm volatile("mov.u32 %0, %%tid.x;" : "=r"(tid2));
    const int lane2 = tid2 & 31, t2 = lane2 & 3;
    const int qq = (blockIdx.x & 3) * 512 + (it * 4 + (tid2 >> 7)) * 64 + ((tid2 >> 5) & 3) * 16 + (lane2 >> 2);
    const float l0 = __shfl_sync(~0u, O[8], (lane2 & ~3) | 2), l1 = __shfl_sync(~0u, O[10], (lane2 & ~3) | 2);
    const float r0 = 1.f / l0, r1 = 1.f / l1;
    uint32_t* o0 = (uint32_t*)(g_o + (size_t)qq * DM + ((blockIdx.x - 4) >> 2) * DH);
    uint32_t* o1 = o0 + 8 * DM / 2;
    o0[t2] = pack_bf16(O[0] * r0, O[1] * r0); o1[t2] = pack_bf16(O[2] * r1, O[3] * r1);
    o0[t2 + 4] = pack_bf16(O[4] * r0, O[5] * r0); o1[t2 + 4] = pack_bf16(O[6] * r1, O[7] * r1);
    if (t2 < 2) { o0[t2 + 8] = pack_bf16(O[8] * r0, O[9] * r0); o1[t2 + 8] = pack_bf16(O[10] * r1, O[11] * r1); }
  };
  TS_MID(2, 1);
  if (fast) {
#pragma unroll 1
    for (int it = 0; it < 2; it++) {
      const uint64_t dq = make_desc(sBar + 256 + (it * 4 + (tid >> 7)) * 4096, 128, 512, 0);
      float O[12];
#pragma unroll
      for (int i = 0; i < 12; i++) { O[i] = 0.f; asm volatile("" : "+f"(O[i]) :: "memory"); }
      float S[2][32];
      uint32_t P[16];
#pragma unroll 1
      for (int jb = 0; jb < 32 / ATT_BODY; jb++) {
        if (it == 0) { for (int c = 0; c < ATT_BODY / 4; c++) mbar_wait(sBar + 8 * (jb * (ATT_BODY / 4) + c), 0); }
        const uint64_t dk0 = make_desc(sK + jb * ATT_BODY * 8 * 384, 128, 384, 0);
        const uint64_t dv0 = make_desc(sV + jb * ATT_BODY * 8 * 384, 384, 128, 0);
        wgmma_fence();
        wgmma_ss_n64_k(S[0], dq, dk0, 0);
        wgmma_ss_n64_k(S[0], dq + (256 >> 4), dk0 + (256 >> 4), 1);
        wgmma_commit();
#pragma unroll
        for (int u = 0; u < ATT_BODY; u++) {
          if (u + 1 < ATT_BODY) {
            const uint64_t dk = dk0 + (((u + 1) * 8 * 384) >> 4);
            wgmma_fence();
            wgmma_ss_n64_k(S[(u + 1) & 1], dq, dk, 0);
            wgmma_ss_n64_k(S[(u + 1) & 1], dq + (256 >> 4), dk + (256 >> 4), 1);
            wgmma_commit();
          }
          if (u == 0 || u == ATT_BODY - 1) wgmma_wait<1>(); else wgmma_wait<2>();
#pragma unroll
          for (int i = 0; i < 32; i++) asm volatile("" : "+f"(S[u & 1][i]) :: "memory");
          const uint64_t dv = dv0 + ((u * 8 * 384) >> 4);
#pragma unroll
          for (int hf = 0; hf < 2; hf++) {
            if (hf == 1 && u > 0) { if (u == ATT_BODY - 1) wgmma_wait<1>(); else wgmma_wait<2>(); }
#pragma unroll
            for (int i = hf * 8; i < hf * 8 + 8; i++) {
              const bool usepoly = ((i + 1) * POLY_NUM / 16) != (i * POLY_NUM / 16);
              float a, b;
              if (usepoly) { a = ex2_poly(S[u & 1][2 * i], shl23); b = ex2_poly(S[u & 1][2 * i + 1], shl23); }
              else { a = ex2_mufu(S[u & 1][2 * i]); b = ex2_mufu(S[u & 1][2 * i + 1]); }
              P[i] = pack_bf16(a, b);
            }
            wgmma_fence();
#pragma unroll
            for (int ks = hf * 2; ks < hf * 2 + 2; ks++)
              wgmma_rs_n24_tb(O, P[4 * ks], P[4 * ks + 1], P[4 * ks + 2], P[4 * ks + 3], dv + ((ks * 768) >> 4), 1);
            wgmma_commit();
          }
        }
        wgmma_wait<0>();
      }
#pragma unroll
      for (int i = 0; i < 12; i++) asm volatile("" : "+f"(O[i]) :: "memory");
      write_out(O, it);
      if (it == 0) TS_MID(2, 2);
    }
  } else {
#pragma unroll 1
    for (int it = 0; it < 2; it++) {
      const uint64_t dq = make_desc(sBar + 256 + (it * 4 + (tid >> 7)) * 4096, 128, 512, 0);
      float O[12];
#pragma unroll
      for (int i = 0; i < 12; i++) { O[i] = 0.f; asm volatile("" : "+f"(O[i]) :: "memory"); }
      float S[32];
      float mx0 = -INFINITY, mx1 = -INFINITY;
#pragma unroll 1
      for (int j = 0; j < 32; j++) {
        if (it == 0 && (j & 3) == 0) mbar_wait(sBar + 8 * (j >> 2), 0);
        const uint64_t dk = make_desc(sK + j * 8 * 384, 128, 384, 0);
        wgmma_fence();
        wgmma_ss_n64_k(S, dq, dk, 0);
        wgmma_ss_n64_k(S, dq + (256 >> 4), dk + (256 >> 4), 1);
        wgmma_commit();
        wgmma_wait<0>();
#pragma unroll
        for (int i = 0; i < 8; i++) {
          mx0 = fmaxf(mx0, fmaxf(S[4 * i], S[4 * i + 1]));
          mx1 = fmaxf(mx1, fmaxf(S[4 * i + 2], S[4 * i + 3]));
        }
      }
      mx0 = fmaxf(mx0, __shfl_xor_sync(~0u, mx0, 1)); mx0 = fmaxf(mx0, __shfl_xor_sync(~0u, mx0, 2));
      mx1 = fmaxf(mx1, __shfl_xor_sync(~0u, mx1, 1)); mx1 = fmaxf(mx1, __shfl_xor_sync(~0u, mx1, 2));
#pragma unroll 1
      for (int j = 0; j < 32; j++) {
        const uint64_t dk = make_desc(sK + j * 8 * 384, 128, 384, 0);
        wgmma_fence();
        wgmma_ss_n64_k(S, dq, dk, 0);
        wgmma_ss_n64_k(S, dq + (256 >> 4), dk + (256 >> 4), 1);
        wgmma_commit();
        wgmma_wait<0>();
        uint32_t P[16];
#pragma unroll
        for (int i = 0; i < 8; i++) {
          P[2 * i] = pack_bf16(ex2_mufu(S[4 * i] - mx0), ex2_mufu(S[4 * i + 1] - mx0));
          P[2 * i + 1] = pack_bf16(ex2_mufu(S[4 * i + 2] - mx1), ex2_mufu(S[4 * i + 3] - mx1));
        }
        wgmma_fence();
        const uint64_t dv = make_desc(sV + j * 8 * 384, 384, 128, 0);
#pragma unroll
        for (int ks = 0; ks < 4; ks++)
          wgmma_rs_n24_tb(O, P[4 * ks], P[4 * ks + 1], P[4 * ks + 2], P[4 * ks + 3], dv + ((ks * 768) >> 4), 1);
        wgmma_commit();
        wgmma_wait<0>();
      }
#pragma unroll
      for (int i = 0; i < 12; i++) asm volatile("" : "+f"(O[i]) :: "memory");
      write_out(O, it);
    }
  }
  TS_END(2);
}

typedef CUresult (*EncodeFn)(CUtensorMap*, CUtensorMapDataType, cuuint32_t, void*, const cuuint64_t*, const cuuint64_t*, const cuuint32_t*,
                             const cuuint32_t*, CUtensorMapInterleave, CUtensorMapSwizzle, CUtensorMapL2promotion, CUtensorMapFloatOOBfill);
static EncodeFn get_encode() {
  static EncodeFn fn = nullptr;
  if (!fn) {
    void* p = nullptr; cudaDriverEntryPointQueryResult st;
    cudaGetDriverEntryPoint("cuTensorMapEncodeTiled", &p, cudaEnableDefault, &st);
    fn = (EncodeFn)p;
  }
  return fn;
}
static CUtensorMap make_map(const void* ptr, int rows, int cols, int box_rows, int box_cols = 64) {
  CUtensorMap m;
  cuuint64_t dims[2] = {(cuuint64_t)cols, (cuuint64_t)rows};
  cuuint64_t strides[1] = {(cuuint64_t)cols * 2};
  cuuint32_t box[2] = {(cuuint32_t)box_cols, (cuuint32_t)box_rows};
  cuuint32_t es[2] = {1, 1};
  get_encode()(&m, CU_TENSOR_MAP_DATA_TYPE_BFLOAT16, 2, const_cast<void*>(ptr), dims, strides, box, es, CU_TENSOR_MAP_INTERLEAVE_NONE,
               box_cols == 64 ? CU_TENSOR_MAP_SWIZZLE_128B : (box_cols == 32 ? CU_TENSOR_MAP_SWIZZLE_64B : CU_TENSOR_MAP_SWIZZLE_32B), CU_TENSOR_MAP_L2_PROMOTION_L2_128B, CU_TENSOR_MAP_FLOAT_OOB_FILL_NONE);
  return m;
}
static CUtensorMap make_map_w(const void* ptr, int rows, int cols, int bc, int nblk) {
  CUtensorMap m;
  cuuint64_t dims[3] = {(cuuint64_t)bc, (cuuint64_t)rows, (cuuint64_t)(cols / bc)};
  cuuint64_t strides[2] = {(cuuint64_t)cols * 2, (cuuint64_t)bc * 2};
  cuuint32_t box[3] = {(cuuint32_t)bc, 64, (cuuint32_t)nblk};
  cuuint32_t es[3] = {1, 1, 1};
  get_encode()(&m, CU_TENSOR_MAP_DATA_TYPE_BFLOAT16, 3, const_cast<void*>(ptr), dims, strides, box, es, CU_TENSOR_MAP_INTERLEAVE_NONE,
               bc == 64 ? CU_TENSOR_MAP_SWIZZLE_128B : (bc == 32 ? CU_TENSOR_MAP_SWIZZLE_64B : CU_TENSOR_MAP_SWIZZLE_32B),
               CU_TENSOR_MAP_L2_PROMOTION_L2_128B, CU_TENSOR_MAP_FLOAT_OOB_FILL_NONE);
  return m;
}
template <typename... KArgs, typename... Args>
static void launch(void (*kern)(KArgs...), dim3 grid, dim3 block, size_t smem, bool pdl, Args... args) {
  cudaLaunchConfig_t cfg = {};
  cfg.gridDim = grid; cfg.blockDim = block; cfg.dynamicSmemBytes = smem; cfg.stream = cudaStreamPerThread;
  cudaLaunchAttribute at[1];
  at[0].id = cudaLaunchAttributeProgrammaticStreamSerialization;
  at[0].val.programmaticStreamSerializationAllowed = 1;
  cfg.attrs = at; cfg.numAttrs = pdl ? 1 : 0;
  cudaLaunchKernelEx(&cfg, kern, KArgs(args)...);
}

extern "C" void kernel_launch(void* const* d_in, const int* in_sizes, int n_in, void* d_out, int out_size) {
  const __nv_bfloat16* x = (const __nv_bfloat16*)d_in[0];
  const __nv_bfloat16* wqkv = (const __nv_bfloat16*)d_in[1];
  const __nv_bfloat16* wo = (const __nv_bfloat16*)d_in[2];
  const __nv_bfloat16* wgate = (const __nv_bfloat16*)d_in[4];
  const __nv_bfloat16* wup = (const __nv_bfloat16*)d_in[5];
  const __nv_bfloat16* wdown = (const __nv_bfloat16*)d_in[6];
  __nv_bfloat16* out = (__nv_bfloat16*)d_out;
  void *p_o, *p_h, *p_act;
  cudaGetSymbolAddress(&p_o, g_o); cudaGetSymbolAddress(&p_h, g_h); cudaGetSymbolAddress(&p_act, g_act);

  auto kA = gemm_kernel<256, 128, 1, DM, 4, EPI_QKV>;
  auto kC = gemm_res_kernel<DM, true>;
  auto kD = gemm_kernel<128, 192, 2, DM, 3, EPI_GLU>;
  auto kE = gemm_res_kernel<DFF, false>;
  constexpr int smA = GemmCfg<256, 128, 1, 4>::SMEM, smC = R_SMEM, smD = GemmCfg<128, 192, 2, 3>::SMEM;
  cudaFuncSetAttribute(kA, cudaFuncAttributeMaxDynamicSharedMemorySize, smA);
  cudaFuncSetAttribute(kC, cudaFuncAttributeMaxDynamicSharedMemorySize, smC);
  cudaFuncSetAttribute(kD, cudaFuncAttributeMaxDynamicSharedMemorySize, smD);
  cudaFuncSetAttribute(kE, cudaFuncAttributeMaxDynamicSharedMemorySize, smC);
  cudaFuncSetAttribute(attn_kernel, cudaFuncAttributeMaxDynamicSharedMemorySize, ATT_SMEM);

  const CUtensorMap tm_x = make_map(x, S_LEN, DM, 256), tm_wqkv = make_map_w(wqkv, DM, 3 * DM, 64, 2);
  const CUtensorMap tm_o = make_map(p_o, S_LEN, DM, 128), tm_wo = make_map_w(wo, DM, DM, 16, 5);
  const CUtensorMap tm_h = make_map(p_h, S_LEN, DM, 128), tm_wg = make_map_w(wgate, DM, DFF, 64, 3), tm_wu = make_map_w(wup, DM, DFF, 64, 3);
  const CUtensorMap tm_act = make_map(p_act, S_LEN, DFF, 128), tm_wd = make_map_w(wdown, DFF, DM, 16, 5);

  launch(pre_kernel, dim3(12), dim3(1024), 0, false, x, wqkv);
  launch(kA, dim3(15, 8), dim3(288), smA, true, tm_x, tm_wqkv, tm_wqkv, (__nv_bfloat16*)nullptr);
  launch(attn_kernel, dim3(132), dim3(512), ATT_SMEM, true, 0x800000, wgate, wup, tm_wo, tm_wd);
  launch(kC, dim3(8, 16), dim3(288), smC, true, tm_o, x, (__nv_bfloat16*)p_h);
  launch(kD, dim3(8, 16), dim3(384), smD, true, tm_h, tm_wg, tm_wu, (__nv_bfloat16*)p_act);
  launch(kE, dim3(8, 16), dim3(288), smC, true, tm_act, (const __nv_bfloat16*)p_h, out);
}
```

```cpp
#include <cuda_runtime.h>
#include <cuda_bf16.h>
#include <cuda.h>
#include <stdint.h>

constexpr int S_LEN = 2048, DM = 640, NH = 32, DH = 20, DFF = 1536;

__device__ __align__(1024) __nv_bfloat16 g_q[NH * S_LEN * 32];
__device__ __align__(1024) __nv_bfloat16 g_k[NH * S_LEN * 24];
__device__ __align__(1024) __nv_bfloat16 g_v[NH * S_LEN * 24];
__device__ __align__(1024) __nv_bfloat16 g_o[S_LEN * DM];
__device__ __align__(1024) __nv_bfloat16 g_h[S_LEN * DM];
__device__ __align__(1024) __nv_bfloat16 g_act[S_LEN * DFF];
__device__ __align__(1024) __nv_bfloat16 g_wo_t[DM * DM];
__device__ __align__(1024) __nv_bfloat16 g_wd_t[DFF * DM];
__device__ float g_kn[8 * NH * 2];
__device__ float2 g_stat1[S_LEN];
__device__ float g_cs_qkv[3 * DM];
__device__ float g_cs_g[DFF];
__device__ float g_cs_u[DFF];
__device__ float2 g_part2[S_LEN * 8];

#define TS_BEGIN(k)
#define TS_END(k)
#define TS_MID(k, i)
__device__ __forceinline__ uint32_t smem_u32(const void* p) { return (uint32_t)__cvta_generic_to_shared(p); }
__device__ __forceinline__ void mbar_init(uint32_t bar, uint32_t cnt) { asm volatile("mbarrier.init.shared::cta.b64 [%0], %1;" :: "r"(bar), "r"(cnt)); }
__device__ __forceinline__ void mbar_expect_tx(uint32_t bar, uint32_t bytes) { asm volatile("mbarrier.arrive.expect_tx.shared::cta.b64 _, [%0], %1;" :: "r"(bar), "r"(bytes) : "memory"); }
__device__ __forceinline__ void mbar_arrive(uint32_t bar) { asm volatile("mbarrier.arrive.shared::cta.b64 _, [%0];" :: "r"(bar) : "memory"); }
__device__ __forceinline__ void mbar_wait(uint32_t bar, uint32_t parity) {
  uint32_t done;
  uint32_t spins = 0;
  do {
    asm volatile("{\n.reg .pred P1;\nmbarrier.try_wait.parity.shared::cta.b64 P1, [%1], %2;\nselp.u32 %0, 1, 0, P1;\n}" : "=r"(done) : "r"(bar), "r"(parity) : "memory");
  } while (!done && ++spins < (1u << 24));
}
__device__ __forceinline__ void bulk_g2s(uint32_t dst, const void* src, uint32_t bytes, uint32_t bar) {
  asm volatile("cp.async.bulk.shared::cluster.global.mbarrier::complete_tx::bytes [%0], [%1], %2, [%3];" :: "r"(dst), "l"(src), "r"(bytes), "r"(bar) : "memory");
}
__device__ __forceinline__ void tma_2d(uint32_t dst, const CUtensorMap* tm, int c0, int c1, uint32_t bar) {
  asm volatile("cp.async.bulk.tensor.2d.shared::cluster.global.mbarrier::complete_tx::bytes [%0], [%1, {%3, %4}], [%2];"
               :: "r"(dst), "l"(tm), "r"(bar), "r"(c0), "r"(c1) : "memory");
}
__device__ __forceinline__ void tma_3d(uint32_t dst, const CUtensorMap* tm, int c0, int c1, int c2, uint32_t bar) {
  asm volatile("cp.async.bulk.tensor.3d.shared::cluster.global.mbarrier::complete_tx::bytes [%0], [%1, {%3, %4, %5}], [%2];"
               :: "r"(dst), "l"(tm), "r"(bar), "r"(c0), "r"(c1), "r"(c2) : "memory");
}
__device__ __forceinline__ void wgmma_fence() { asm volatile("wgmma.fence.sync.aligned;" ::: "memory"); }
__device__ __forceinline__ void wgmma_commit() { asm volatile("wgmma.commit_group.sync.aligned;" ::: "memory"); }
template <int N> __device__ __forceinline__ void wgmma_wait() { asm volatile("wgmma.wait_group.sync.aligned %0;" :: "n"(N) : "memory"); }
__device__ __forceinline__ void pdl_wait() { asm volatile("griddepcontrol.wait;" ::: "memory"); }
__device__ __forceinline__ void pdl_launch() { asm volatile("griddepcontrol.launch_dependents;" ::: "memory"); }
__device__ __forceinline__ void named_bar(int id, int n) { asm volatile("bar.sync %0, %1;" :: "r"(id), "r"(n) : "memory"); }
__device__ __forceinline__ uint64_t make_desc(uint32_t addr, uint32_t lbo, uint32_t sbo, uint32_t swz) {
  return (uint64_t)((addr & 0x3FFFF) >> 4) | ((uint64_t)(lbo >> 4) << 16) | ((uint64_t)(sbo >> 4) << 32) | ((uint64_t)swz << 62);
}
__device__ __forceinline__ void st_g16(void* p, uint4 v) { asm volatile("st.global.v4.b32 [%0], {%1, %2, %3, %4};" :: "l"(p), "r"(v.x), "r"(v.y), "r"(v.z), "r"(v.w) : "memory"); }
__device__ __forceinline__ void st_g8(void* p, uint2 v) { asm volatile("st.global.v2.b32 [%0], {%1, %2};" :: "l"(p), "r"(v.x), "r"(v.y) : "memory"); }
__device__ __forceinline__ uint4 ld_g16(const void* p) { uint4 v; asm volatile("ld.global.v4.b32 {%0, %1, %2, %3}, [%4];" : "=r"(v.x), "=r"(v.y), "=r"(v.z), "=r"(v.w) : "l"(p) : "memory"); return v; }
__device__ __forceinline__ uint32_t pack_bf16(float lo, float hi) { uint32_t r; asm("cvt.rn.bf16x2.f32 %0, %1, %2;" : "=r"(r) : "f"(hi), "f"(lo)); return r; }
__device__ __forceinline__ float bf_lo(uint32_t u) { return __uint_as_float(u << 16); }
__device__ __forceinline__ float bf_hi(uint32_t u) { return __uint_as_float(u & 0xffff0000u); }
__device__ __forceinline__ float bf_round(float x) { return __bfloat162float(__float2bfloat16_rn(x)); }
__device__ __forceinline__ float ex2_mufu(float x) { float y; asm("ex2.approx.ftz.f32 %0, %1;" : "=f"(y) : "f"(x)); return y; }

__device__ __forceinline__ void wgmma_ss_n80(float (&d)[40], uint64_t da, uint64_t db, int scale_d) {
  asm volatile("{\n.reg .pred p;\nsetp.ne.b32 p, %42, 0;\n"
    "wgmma.mma_async.sync.aligned.m64n80k16.f32.bf16.bf16 {%0,%1,%2,%3,%4,%5,%6,%7,%8,%9,%10,%11,%12,%13,%14,%15,%16,%17,%18,%19,%20,%21,%22,%23,%24,%25,%26,%27,%28,%29,%30,%31,%32,%33,%34,%35,%36,%37,%38,%39}, %40, %41, p, 1, 1, 0, 1;\n}\n"
    : "+f"(d[0]),"+f"(d[1]),"+f"(d[2]),"+f"(d[3]),"+f"(d[4]),"+f"(d[5]),"+f"(d[6]),"+f"(d[7]),"+f"(d[8]),"+f"(d[9]),"+f"(d[10]),"+f"(d[11]),"+f"(d[12]),"+f"(d[13]),"+f"(d[14]),"+f"(d[15]),"+f"(d[16]),"+f"(d[17]),"+f"(d[18]),"+f"(d[19]),"+f"(d[20]),"+f"(d[21]),"+f"(d[22]),"+f"(d[23]),"+f"(d[24]),"+f"(d[25]),"+f"(d[26]),"+f"(d[27]),"+f"(d[28]),"+f"(d[29]),"+f"(d[30]),"+f"(d[31]),"+f"(d[32]),"+f"(d[33]),"+f"(d[34]),"+f"(d[35]),"+f"(d[36]),"+f"(d[37]),"+f"(d[38]),"+f"(d[39])
    : "l"(da), "l"(db), "r"(scale_d));
}
__device__ __forceinline__ void wgmma_ss_n128(float (&d)[64], uint64_t da, uint64_t db, int scale_d) {
  asm volatile("{\n.reg .pred p;\nsetp.ne.b32 p, %66, 0;\n"
    "wgmma.mma_async.sync.aligned.m64n128k16.f32.bf16.bf16 {%0,%1,%2,%3,%4,%5,%6,%7,%8,%9,%10,%11,%12,%13,%14,%15,%16,%17,%18,%19,%20,%21,%22,%23,%24,%25,%26,%27,%28,%29,%30,%31,%32,%33,%34,%35,%36,%37,%38,%39,%40,%41,%42,%43,%44,%45,%46,%47,%48,%49,%50,%51,%52,%53,%54,%55,%56,%57,%58,%59,%60,%61,%62,%63}, %64, %65, p, 1, 1, 0, 1;\n}\n"
    : "+f"(d[0]),"+f"(d[1]),"+f"(d[2]),"+f"(d[3]),"+f"(d[4]),"+f"(d[5]),"+f"(d[6]),"+f"(d[7]),"+f"(d[8]),"+f"(d[9]),"+f"(d[10]),"+f"(d[11]),"+f"(d[12]),"+f"(d[13]),"+f"(d[14]),"+f"(d[15]),"+f"(d[16]),"+f"(d[17]),"+f"(d[18]),"+f"(d[19]),"+f"(d[20]),"+f"(d[21]),"+f"(d[22]),"+f"(d[23]),"+f"(d[24]),"+f"(d[25]),"+f"(d[26]),"+f"(d[27]),"+f"(d[28]),"+f"(d[29]),"+f"(d[30]),"+f"(d[31]),"+f"(d[32]),"+f"(d[33]),"+f"(d[34]),"+f"(d[35]),"+f"(d[36]),"+f"(d[37]),"+f"(d[38]),"+f"(d[39]),"+f"(d[40]),"+f"(d[41]),"+f"(d[42]),"+f"(d[43]),"+f"(d[44]),"+f"(d[45]),"+f"(d[46]),"+f"(d[47]),"+f"(d[48]),"+f"(d[49]),"+f"(d[50]),"+f"(d[51]),"+f"(d[52]),"+f"(d[53]),"+f"(d[54]),"+f"(d[55]),"+f"(d[56]),"+f"(d[57]),"+f"(d[58]),"+f"(d[59]),"+f"(d[60]),"+f"(d[61]),"+f"(d[62]),"+f"(d[63])
    : "l"(da), "l"(db), "r"(scale_d));
}
__device__ __forceinline__ void wgmma_ss_n192(float (&d)[96], uint64_t da, uint64_t db, int scale_d) {
  asm volatile("{\n.reg .pred p;\nsetp.ne.b32 p, %98, 0;\n"
    "wgmma.mma_async.sync.aligned.m64n192k16.f32.bf16.bf16 {%0,%1,%2,%3,%4,%5,%6,%7,%8,%9,%10,%11,%12,%13,%14,%15,%16,%17,%18,%19,%20,%21,%22,%23,%24,%25,%26,%27,%28,%29,%30,%31,%32,%33,%34,%35,%36,%37,%38,%39,%40,%41,%42,%43,%44,%45,%46,%47,%48,%49,%50,%51,%52,%53,%54,%55,%56,%57,%58,%59,%60,%61,%62,%63,%64,%65,%66,%67,%68,%69,%70,%71,%72,%73,%74,%75,%76,%77,%78,%79,%80,%81,%82,%83,%84,%85,%86,%87,%88,%89,%90,%91,%92,%93,%94,%95}, %96, %97, p, 1, 1, 0, 1;\n}\n"
    : "+f"(d[0]),"+f"(d[1]),"+f"(d[2]),"+f"(d[3]),"+f"(d[4]),"+f"(d[5]),"+f"(d[6]),"+f"(d[7]),"+f"(d[8]),"+f"(d[9]),"+f"(d[10]),"+f"(d[11]),"+f"(d[12]),"+f"(d[13]),"+f"(d[14]),"+f"(d[15]),"+f"(d[16]),"+f"(d[17]),"+f"(d[18]),"+f"(d[19]),"+f"(d[20]),"+f"(d[21]),"+f"(d[22]),"+f"(d[23]),"+f"(d[24]),"+f"(d[25]),"+f"(d[26]),"+f"(d[27]),"+f"(d[28]),"+f"(d[29]),"+f"(d[30]),"+f"(d[31]),"+f"(d[32]),"+f"(d[33]),"+f"(d[34]),"+f"(d[35]),"+f"(d[36]),"+f"(d[37]),"+f"(d[38]),"+f"(d[39]),"+f"(d[40]),"+f"(d[41]),"+f"(d[42]),"+f"(d[43]),"+f"(d[44]),"+f"(d[45]),"+f"(d[46]),"+f"(d[47]),"+f"(d[48]),"+f"(d[49]),"+f"(d[50]),"+f"(d[51]),"+f"(d[52]),"+f"(d[53]),"+f"(d[54]),"+f"(d[55]),"+f"(d[56]),"+f"(d[57]),"+f"(d[58]),"+f"(d[59]),"+f"(d[60]),"+f"(d[61]),"+f"(d[62]),"+f"(d[63]),"+f"(d[64]),"+f"(d[65]),"+f"(d[66]),"+f"(d[67]),"+f"(d[68]),"+f"(d[69]),"+f"(d[70]),"+f"(d[71]),"+f"(d[72]),"+f"(d[73]),"+f"(d[74]),"+f"(d[75]),"+f"(d[76]),"+f"(d[77]),"+f"(d[78]),"+f"(d[79]),"+f"(d[80]),"+f"(d[81]),"+f"(d[82]),"+f"(d[83]),"+f"(d[84]),"+f"(d[85]),"+f"(d[86]),"+f"(d[87]),"+f"(d[88]),"+f"(d[89]),"+f"(d[90]),"+f"(d[91]),"+f"(d[92]),"+f"(d[93]),"+f"(d[94]),"+f"(d[95])
    : "l"(da), "l"(db), "r"(scale_d));
}
__device__ __forceinline__ void wgmma_ss_n64_k(float (&d)[32], uint64_t da, uint64_t db, int scale_d) {
  asm volatile("{\n.reg .pred p;\nsetp.ne.b32 p, %34, 0;\n"
    "wgmma.mma_async.sync.aligned.m64n64k16.f32.bf16.bf16 {%0,%1,%2,%3,%4,%5,%6,%7,%8,%9,%10,%11,%12,%13,%14,%15,%16,%17,%18,%19,%20,%21,%22,%23,%24,%25,%26,%27,%28,%29,%30,%31}, %32, %33, p, 1, 1, 0, 0;\n}\n"
    : "+f"(d[0]),"+f"(d[1]),"+f"(d[2]),"+f"(d[3]),"+f"(d[4]),"+f"(d[5]),"+f"(d[6]),"+f"(d[7]),"+f"(d[8]),"+f"(d[9]),"+f"(d[10]),"+f"(d[11]),"+f"(d[12]),"+f"(d[13]),"+f"(d[14]),"+f"(d[15]),"+f"(d[16]),"+f"(d[17]),"+f"(d[18]),"+f"(d[19]),"+f"(d[20]),"+f"(d[21]),"+f"(d[22]),"+f"(d[23]),"+f"(d[24]),"+f"(d[25]),"+f"(d[26]),"+f"(d[27]),"+f"(d[28]),"+f"(d[29]),"+f"(d[30]),"+f"(d[31])
    : "l"(da), "l"(db), "r"(scale_d));
}
__device__ __forceinline__ void wgmma_rs_n24_tb(float (&d)[12], uint32_t a0, uint32_t a1, uint32_t a2, uint32_t a3, uint64_t db, int scale_d) {
  asm volatile("{\n.reg .pred p;\nsetp.ne.b32 p, %17, 0;\n"
    "wgmma.mma_async.sync.aligned.m64n24k16.f32.bf16.bf16 {%0,%1,%2,%3,%4,%5,%6,%7,%8,%9,%10,%11}, {%12,%13,%14,%15}, %16, p, 1, 1, 1;\n}\n"
    : "+f"(d[0]),"+f"(d[1]),"+f"(d[2]),"+f"(d[3]),"+f"(d[4]),"+f"(d[5]),"+f"(d[6]),"+f"(d[7]),"+f"(d[8]),"+f"(d[9]),"+f"(d[10]),"+f"(d[11])
    : "r"(a0), "r"(a1), "r"(a2), "r"(a3), "l"(db), "r"(scale_d));
}

__device__ __forceinline__ float2 ln_finish(float mean, float var) {
  float mb = bf_round(mean);
  float s = bf_round(sqrtf(bf_round(bf_round(var) + 1e-5f)));
  return make_float2(mb, 1.0f / s);
}
__device__ __forceinline__ void colsum64(const __nv_bfloat16* __restrict__ w, int ld, int c0, float* __restrict__ dst, float (*red)[65], int tid, int bar_id) {
  const int cg = tid & 7, r0 = tid >> 3;
  float acc[8];
#pragma unroll
  for (int i = 0; i < 8; i++) acc[i] = 0.f;
#pragma unroll 10
  for (int r = r0; r < DM; r += 32) {
    uint4 v = __ldg((const uint4*)(w + (size_t)r * ld + c0 + cg * 8));
    acc[0] += bf_lo(v.x); acc[1] += bf_hi(v.x); acc[2] += bf_lo(v.y); acc[3] += bf_hi(v.y);
    acc[4] += bf_lo(v.z); acc[5] += bf_hi(v.z); acc[6] += bf_lo(v.w); acc[7] += bf_hi(v.w);
  }
#pragma unroll
  for (int i = 0; i < 8; i++) red[r0][cg * 8 + i] = acc[i];
  named_bar(bar_id, 256);
  if (tid < 64) {
    float s = 0.f;
#pragma unroll
    for (int r = 0; r < 32; r++) s += red[r][tid];
    dst[c0 + tid] = s;
  }
  named_bar(bar_id, 256);
}
constexpr int PRE_SMEM = 171 * 1280 + 64;
__global__ void __launch_bounds__(1024) pre_kernel(const __nv_bfloat16* __restrict__ x, const __nv_bfloat16* __restrict__ wqkv) {
  extern __shared__ __align__(128) uint8_t psm[];
  TS_BEGIN(0);
  pdl_launch();
  const int tid = threadIdx.x, lane = tid & 31, warp = tid >> 5;
  const int rbeg = blockIdx.x * 171, nrows = min(171, S_LEN - rbeg);
  const uint32_t bar = smem_u32(psm) + 171 * 1280;
  if (tid == 0) {
    mbar_init(bar, 1);
    asm volatile("fence.mbarrier_init.release.cluster;" ::: "memory");
    mbar_expect_tx(bar, nrows * 1280);
    for (int r = 0; r < nrows; r += 19) bulk_g2s(smem_u32(psm) + r * 1280, x + (size_t)(rbeg + r) * DM, min(19, nrows - r) * 1280, bar);
  }
  const int ch = tid % 20, rl = tid / 20;
  float acc[8];
#pragma unroll
  for (int i = 0; i < 8; i++) acc[i] = 0.f;
  if (rl < 51) {
    const __nv_bfloat16* w = wqkv + blockIdx.x * 160 + ch * 8;
    uint4 v[13];
#pragma unroll
    for (int i = 0; i < 13; i++) { const int r = rl + i * 51; v[i] = r < DM ? __ldg((const uint4*)(w + (size_t)r * (3 * DM))) : make_uint4(0, 0, 0, 0); }
#pragma unroll
    for (int i = 0; i < 13; i++) {
      acc[0] += bf_lo(v[i].x); acc[1] += bf_hi(v[i].x); acc[2] += bf_lo(v[i].y); acc[3] += bf_hi(v[i].y);
      acc[4] += bf_lo(v[i].z); acc[5] += bf_hi(v[i].z); acc[6] += bf_lo(v[i].w); acc[7] += bf_hi(v[i].w);
    }
  }
  __syncthreads();
  mbar_wait(bar, 0);
  for (int r = warp; r < nrows; r += 32) {
    const uint4* p = (const uint4*)(psm + r * 1280);
    const uint4 v0 = p[lane], v1 = p[32 + lane], v2 = lane < 16 ? p[64 + lane] : make_uint4(0, 0, 0, 0);
    float f[24];
    const uint32_t u[12] = {v0.x, v0.y, v0.z, v0.w, v1.x, v1.y, v1.z, v1.w, v2.x, v2.y, v2.z, v2.w};
#pragma unroll
    for (int j = 0; j < 12; j++) { f[2 * j] = bf_lo(u[j]); f[2 * j + 1] = bf_hi(u[j]); }
    float s = 0.f;
#pragma unroll
    for (int j = 0; j < 24; j++) s += f[j];
#pragma unroll
    for (int o = 16; o; o >>= 1) s += __shfl_xor_sync(~0u, s, o);
    const float mean = s * (1.0f / DM);
    float q = 0.f;
#pragma unroll
    for (int j = 0; j < 16; j++) { const float d = f[j] - mean; q += d * d; }
    if (lane < 16) {
#pragma unroll
      for (int j = 16; j < 24; j++) { const float d = f[j] - mean; q += d * d; }
    }
#pragma unroll
    for (int o = 16; o; o >>= 1) q += __shfl_xor_sync(~0u, q, o);
    if (lane == 0) g_stat1[rbeg + r] = ln_finish(mean, q * (1.0f / DM));
  }
  __syncthreads();
  float (*red)[161] = (float (*)[161])psm;
  if (rl < 51) {
#pragma unroll
    for (int i = 0; i < 8; i++) red[rl][ch * 8 + i] = acc[i];
  }
  __syncthreads();
  if (tid < 160) {
    float s = 0.f;
#pragma unroll 17
    for (int r = 0; r < 51; r++) s += red[r][tid];
    g_cs_qkv[blockIdx.x * 160 + tid] = s;
  }
  TS_END(0);
}

enum { EPI_QKV = 0, EPI_GLU = 2 };
template <int N> struct WG;
template <> struct WG<128> { static __device__ __forceinline__ void mma(float (&d)[64], uint64_t a, uint64_t b, int s) { wgmma_ss_n128(d, a, b, s); } };
template <> struct WG<192> { static __device__ __forceinline__ void mma(float (&d)[96], uint64_t a, uint64_t b, int s) { wgmma_ss_n192(d, a, b, s); } };

template <int BM, int BN, int NB, int STAGES> struct GemmCfg {
  static constexpr int A_BYTES = BM * 128;
  static constexpr int B_BYTES = NB * (BN / 64) * 8192;
  static constexpr int STAGE_BYTES = A_BYTES + B_BYTES;
  static constexpr int SMEM = STAGES * STAGE_BYTES + 1024   + 256   + 4096  ;
};

constexpr float QSCALE = 0.22360679774997896f * 1.4426950408889634f;

template <int BM, int BN, int NB, int KDIM, int STAGES, int EPI>
__global__ void __launch_bounds__(EPI == EPI_GLU ? 384 : 288, 1) gemm_kernel(const __grid_constant__ CUtensorMap tmA, const __grid_constant__ CUtensorMap tmB0,
                                                         const __grid_constant__ CUtensorMap tmB1, __nv_bfloat16* out) {
  using Cfg = GemmCfg<BM, BN, NB, STAGES>;
  constexpr int MB = BM / 128;
  constexpr int KT = KDIM / 64;
  extern __shared__ uint8_t smem_raw[];
  const uint32_t sbase = (smem_u32(smem_raw) + 1023u) & ~1023u;
  uint8_t* sptr = smem_raw + (sbase - smem_u32(smem_raw));
  const uint32_t sbar = sbase + STAGES * Cfg::STAGE_BYTES;
  const int tid = threadIdx.x, warp = tid >> 5, lane = tid & 31;
  const int n0 = blockIdx.x * BN, m0 = blockIdx.y * BM;
  TS_BEGIN(EPI == EPI_QKV ? 1 : EPI + 2);
  TS_MID(EPI == EPI_QKV ? 1 : EPI + 2, 3);
  if (tid == 0) {
    for (int i = 0; i < STAGES; i++) { mbar_init(sbar + 8 * i, 1); mbar_init(sbar + 8 * (STAGES + i), 8); }
    asm volatile("fence.mbarrier_init.release.cluster;" ::: "memory");
  }
  __syncthreads();
  pdl_launch();
  if (warp >= 8) {
    if constexpr (EPI == EPI_GLU) asm volatile("setmaxnreg.dec.sync.aligned.u32 40;");
    if (warp == 8 && lane == 0) {
      auto load_a = [&](int kt, int s) { tma_2d(sbase + s * Cfg::STAGE_BYTES, &tmA, kt * 64, m0, sbar + 8 * s); };
      auto load_b = [&](int kt, int s) {
        const uint32_t sb = sbase + s * Cfg::STAGE_BYTES + Cfg::A_BYTES;
        tma_3d(sb, &tmB0, 0, kt * 64, blockIdx.x * (BN / 64), sbar + 8 * s);
        if constexpr (NB == 2) tma_3d(sb + (BN / 64) * 8192, &tmB1, 0, kt * 64, blockIdx.x * (BN / 64), sbar + 8 * s);
      };
      for (int s = 0; s < STAGES; s++) { mbar_expect_tx(sbar + 8 * s, Cfg::STAGE_BYTES); if (s == 0) load_b(s, s); }
      if (EPI != EPI_QKV) pdl_wait();
      for (int s = 0; s < STAGES; s++) { load_a(s, s); if (s > 0) load_b(s, s); }
      for (int kt = STAGES; kt < KT; kt++) {
        const int s = kt % STAGES;
        mbar_wait(sbar + 8 * (STAGES + s), ((kt / STAGES) - 1) & 1);
        mbar_expect_tx(sbar + 8 * s, Cfg::STAGE_BYTES);
        load_a(kt, s);
        load_b(kt, s);
      }
    }
    if constexpr (EPI == EPI_GLU) {
      if (warp > 8) {
        float2* s_st = (float2*)(sptr + STAGES * Cfg::STAGE_BYTES + 256);
        float* s_cs = (float*)(sptr + STAGES * Cfg::STAGE_BYTES + 256 + 1024);
        pdl_wait();
        for (int r = tid - 288; r < BM; r += 96) {
          const float2* pp = &g_part2[(m0 + r) * 8];
          float s = 0.f;
#pragma unroll
          for (int i = 0; i < 8; i++) s += pp[i].x;
          const float mean = s * (1.0f / DM);
          float q = 0.f;
#pragma unroll
          for (int i = 0; i < 8; i++) { const float2 p = pp[i]; const float d = p.x * (1.0f / 80.f) - mean; q += p.y + 80.f * d * d; }
          s_st[r] = ln_finish(mean, q * (1.0f / DM));
        }
        for (int c = tid - 288; c < BN; c += 96) { s_cs[c] = g_cs_g[n0 + c]; s_cs[BN + c] = g_cs_u[n0 + c]; }
        __threadfence_block();
        asm volatile("bar.arrive 2, 352;" ::: "memory");
      }
    }
    return;
  }
  if constexpr (EPI == EPI_GLU) asm volatile("setmaxnreg.inc.sync.aligned.u32 232;");
  const int wg = warp >> 2, g = lane >> 2, t = lane & 3;
  float acc[MB][NB][BN / 2];
#pragma unroll
  for (int mb = 0; mb < MB; mb++)
#pragma unroll
    for (int nb = 0; nb < NB; nb++)
#pragma unroll
      for (int i = 0; i < BN / 2; i++) acc[mb][nb][i] = 0.f;
  for (int kt = 0; kt < KT; kt++) {
    const int s = kt % STAGES;
    mbar_wait(sbar + 8 * s, (kt / STAGES) & 1);
    if (kt == 0) TS_MID(EPI == EPI_QKV ? 1 : EPI + 2, 0);
    const uint32_t sa = sbase + s * Cfg::STAGE_BYTES + wg * (MB * 64 * 128);
    const uint32_t sb = sbase + s * Cfg::STAGE_BYTES + Cfg::A_BYTES;
    wgmma_fence();
#pragma unroll
    for (int ks = 0; ks < 4; ks++) {
#pragma unroll
      for (int mb = 0; mb < MB; mb++) {
        const uint64_t da = make_desc(sa + mb * 8192 + ks * 32, 16, 1024, 1);
#pragma unroll
        for (int nb = 0; nb < NB; nb++) {
          const uint64_t db = make_desc(sb + nb * (BN / 64) * 8192 + ks * 2048, 8192, 1024, 1);
          WG<BN>::mma(acc[mb][nb], da, db, 1);
        }
      }
    }
    wgmma_commit();
    wgmma_wait<1>();
    if (kt > 0 && kt - 1 + STAGES < KT && lane == 0) mbar_arrive(sbar + 8 * (STAGES + (kt - 1) % STAGES));
  }
  wgmma_wait<0>();
#pragma unroll
  for (int mb = 0; mb < MB; mb++)
#pragma unroll
    for (int nb = 0; nb < NB; nb++)
#pragma unroll
      for (int i = 0; i < BN / 2; i++) asm volatile("" : "+f"(acc[mb][nb][i]) :: "memory");
  TS_MID(EPI == EPI_QKV ? 1 : EPI + 2, 1);
  pdl_wait();
  TS_MID(EPI == EPI_QKV ? 1 : EPI + 2, 2);
  named_bar(1, 256);
  constexpr int LDS = BN * 2 + 16;
  const int ctid = tid;

  if constexpr (EPI == EPI_QKV) {
    const int sec = n0 / DM;
    constexpr int lds = 264;
    __shared__ unsigned int s_kn[8];
    if (ctid < 8) s_kn[ctid] = 0u;
    float2 cs[BN / 8];
#pragma unroll
    for (int j = 0; j < BN / 8; j++) cs[j] = *(const float2*)&g_cs_qkv[n0 + j * 8 + 2 * t];
#pragma unroll
    for (int mb = 0; mb < MB; mb++) {
      const int r0 = wg * (MB * 64) + mb * 64 + (warp & 3) * 16 + g;
      const float2 st0 = g_stat1[m0 + r0], st1 = g_stat1[m0 + r0 + 8];
      const float sc0 = sec == 0 ? st0.y * QSCALE : st0.y, sc1 = sec == 0 ? st1.y * QSCALE : st1.y;
#pragma unroll
      for (int j = 0; j < BN / 8; j++) {
        const float* a = &acc[mb][0][4 * j];
        *(uint32_t*)(sptr + r0 * lds + j * 16 + t * 4) = pack_bf16(fmaf(-st0.x, cs[j].x, a[0]) * sc0, fmaf(-st0.x, cs[j].y, a[1]) * sc0);
        *(uint32_t*)(sptr + (r0 + 8) * lds + j * 16 + t * 4) = pack_bf16(fmaf(-st1.x, cs[j].x, a[2]) * sc1, fmaf(-st1.x, cs[j].y, a[3]) * sc1);
      }
    }
    named_bar(1, 256);
    {
      const int cbase = n0 - sec * DM;
      const int hfirst = cbase / DH;
      const int j = m0 + ctid;
      uint8_t* dst = (uint8_t*)(sec == 0 ? g_q : (sec == 1 ? g_k : g_v)) + (size_t)(j >> 3) * (sec == 0 ? 512 : 384) + (j & 7) * 16;
      const uint8_t* row = sptr + ctid * 264;
#pragma unroll
      for (int i = 0; i < 8; i++) {
        const int hh = hfirst + i;
        const int cr = hh * DH - cbase;
        if (cr < BN) {
          uint2 v[5];
          bool in[5];
          float s = 0.f;
#pragma unroll
          for (int qd = 0; qd < 5; qd++) {
            const int c = cr + 4 * qd;
            in[qd] = c >= 0 && c < BN;
            v[qd] = in[qd] ? *(const uint2*)(row + c * 2) : make_uint2(0u, 0u);
            s += bf_lo(v[qd].x) * bf_lo(v[qd].x) + bf_hi(v[qd].x) * bf_hi(v[qd].x) + bf_lo(v[qd].y) * bf_lo(v[qd].y) + bf_hi(v[qd].y) * bf_hi(v[qd].y);
          }
          uint8_t* p = dst + (size_t)hh * (sec == 0 ? S_LEN * 64 : S_LEN * 48);
          if (in[0] && in[1]) st_g16(p, make_uint4(v[0].x, v[0].y, v[1].x, v[1].y));
          else if (in[0]) st_g8(p, v[0]);
          else if (in[1]) st_g8(p + 8, v[1]);
          if (in[2] && in[3]) st_g16(p + 128, make_uint4(v[2].x, v[2].y, v[3].x, v[3].y));
          else if (in[2]) st_g8(p + 128, v[2]);
          else if (in[3]) st_g8(p + 136, v[3]);
          if (in[4]) {
            st_g16(p + 256, make_uint4(v[4].x, v[4].y, sec == 0 ? 0u : 0x00003f80u, 0u));
            if (sec == 0) st_g16(p + 384, make_uint4(0u, 0u, 0u, 0u));
          }
          if (sec == 1) {
            const unsigned int mxb = __reduce_max_sync(~0u, __float_as_uint(s) & 0x7fffffffu);
            if (lane == 0) atomicMax(&s_kn[i], mxb);
          }
        }
      }
      if (sec == 1) {
        named_bar(1, 256);
        const int hh = hfirst + ctid;
        if (ctid < 8 && hh * DH < cbase + BN) {
          const bool starts_here = hh * DH >= cbase, ends_here = hh * DH + DH <= cbase + BN;
          const float v = __uint_as_float(s_kn[ctid]);
          float* o = &g_kn[(blockIdx.y * NH + hh) * 2];
          if (starts_here) { o[0] = v; if (ends_here) o[1] = 0.f; }
          else o[1] = v;
        }
      }
    }
  } else {
    const int r0 = wg * 64 + (warp & 3) * 16 + g;
    const float2* s_st = (const float2*)(sptr + STAGES * Cfg::STAGE_BYTES + 256);
    const float* s_cs = (const float*)(sptr + STAGES * Cfg::STAGE_BYTES + 256 + 1024);
    named_bar(2, 352);
    float2 st[2] = {s_st[r0], s_st[r0 + 8]};
#pragma unroll
    for (int j = 0; j < BN / 8; j++) {
      const float2 cg = *(const float2*)&s_cs[j * 8 + 2 * t], cu = *(const float2*)&s_cs[BN + j * 8 + 2 * t];
      const float* a = &acc[0][0][4 * j];
      const float* b = &acc[0][1][4 * j];
#pragma unroll
      for (int e = 0; e < 2; e++) {
        const float2 s_ = st[e];
        const uint32_t gp = pack_bf16(fmaf(-s_.x, cg.x, a[2 * e]) * s_.y, fmaf(-s_.x, cg.y, a[2 * e + 1]) * s_.y);
        const uint32_t up = pack_bf16(fmaf(-s_.x, cu.x, b[2 * e]) * s_.y, fmaf(-s_.x, cu.y, b[2 * e + 1]) * s_.y);
        uint32_t r;
        asm("{\n.reg .b32 z;\nmax.bf16x2 z, %1, %3;\nmul.rn.bf16x2 %0, z, %2;\n}" : "=r"(r) : "r"(gp), "r"(up), "r"(0u));
        *(uint32_t*)(sptr + (r0 + 8 * e) * LDS + j * 16 + t * 4) = r;
      }
    }
    named_bar(1, 256);
#pragma unroll
    for (int i = 0; i < BM * (BN / 8) / 256; i++) {
      const int idx = i * 256 + ctid, r = idx / (BN / 8), c = idx % (BN / 8);
      st_g16(out + (size_t)(m0 + r) * DFF + n0 + c * 8, *(const uint4*)(sptr + r * LDS + c * 16));
    }
  }
  TS_END(EPI == EPI_QKV ? 1 : EPI + 2);
}

constexpr int R_STAGES = 8;
constexpr int R_STAGE_BYTES = 16384 + 5 * 2048;
constexpr int R_BAR_OFF = R_STAGES * R_STAGE_BYTES;
constexpr int R_SMEM = R_BAR_OFF + 256 + 1024;
template <int KDIM, bool STATS>
__global__ void __launch_bounds__(288, 1) gemm_res_kernel(const __grid_constant__ CUtensorMap tmA, const __nv_bfloat16* resid, __nv_bfloat16* out) {
  constexpr int KT = KDIM / 64;
  extern __shared__ uint8_t smem_raw[];
  const uint32_t sbase = (smem_u32(smem_raw) + 1023u) & ~1023u;
  uint8_t* sptr = smem_raw + (sbase - smem_u32(smem_raw));
  const uint32_t sbar = sbase + R_BAR_OFF;
  const int tid = threadIdx.x, warp = tid >> 5, lane = tid & 31;
  const int n0 = blockIdx.x * 80, m0 = blockIdx.y * 128;
  TS_BEGIN(STATS ? 3 : 5);
  if (tid == 0) {
    for (int i = 0; i < R_STAGES; i++) { mbar_init(sbar + 8 * i, 1); mbar_init(sbar + 8 * (R_STAGES + i), 8); }
    asm volatile("fence.mbarrier_init.release.cluster;" ::: "memory");
  }
  __syncthreads();
  pdl_launch();
  if (warp == 8) {
    if (lane == 0) {
      const uint8_t* wt = (const uint8_t*)(STATS ? g_wo_t : g_wd_t) + (size_t)blockIdx.x * KT * 10240;
      auto load_b = [&](int kt, int s) { bulk_g2s(sbase + s * R_STAGE_BYTES + 16384, wt + kt * 10240, 10240, sbar + 8 * s); };
      pdl_wait();
      for (int s = 0; s < R_STAGES; s++) { mbar_expect_tx(sbar + 8 * s, R_STAGE_BYTES); tma_2d(sbase + s * R_STAGE_BYTES, &tmA, s * 64, m0, sbar + 8 * s); load_b(s, s); }
      for (int kt = R_STAGES; kt < KT; kt++) {
        const int s = kt % R_STAGES;
        mbar_wait(sbar + 8 * (R_STAGES + s), ((kt / R_STAGES) - 1) & 1);
        mbar_expect_tx(sbar + 8 * s, R_STAGE_BYTES);
        tma_2d(sbase + s * R_STAGE_BYTES, &tmA, kt * 64, m0, sbar + 8 * s);
        load_b(kt, s);
      }
    }
    return;
  }
  const int wg = warp >> 2, g = lane >> 2, t = lane & 3;
  pdl_wait();
  uint4 rv[5];
#pragma unroll
  for (int i = 0; i < 5; i++) {
    const int idx = i * 256 + tid, r = idx / 10, c = idx % 10;
    rv[i] = ld_g16(resid + (size_t)(m0 + r) * DM + n0 + c * 8);
  }
  float acc[40];
#pragma unroll
  for (int i = 0; i < 40; i++) acc[i] = 0.f;
  for (int kt = 0; kt < KT; kt++) {
    const int s = kt % R_STAGES;
    mbar_wait(sbar + 8 * s, (kt / R_STAGES) & 1);
    if (kt == 0) TS_MID(STATS ? 3 : 5, 0);
    const uint32_t sa = sbase + s * R_STAGE_BYTES + wg * 8192;
    const uint32_t sb = sbase + s * R_STAGE_BYTES + 16384;
    wgmma_fence();
#pragma unroll
    for (int ks = 0; ks < 4; ks++)
      wgmma_ss_n80(acc, make_desc(sa + ks * 32, 16, 1024, 1), make_desc(sb + ks * 512, 2048, 256, 3), 1);
    wgmma_commit();
    wgmma_wait<1>();
    if (kt > 0 && kt - 1 + R_STAGES < KT && lane == 0) mbar_arrive(sbar + 8 * (R_STAGES + (kt - 1) % R_STAGES));
  }
  wgmma_wait<0>();
#pragma unroll
  for (int i = 0; i < 40; i++) asm volatile("" : "+f"(acc[i]) :: "memory");
  TS_MID(STATS ? 3 : 5, 1);
  named_bar(1, 256);
  constexpr int LDS = 176;
  const int r0 = wg * 64 + (warp & 3) * 16 + g;
#pragma unroll
  for (int i = 0; i < 10; i++) {
    *(uint32_t*)(sptr + r0 * LDS + i * 16 + t * 4) = pack_bf16(acc[4 * i], acc[4 * i + 1]);
    *(uint32_t*)(sptr + (r0 + 8) * LDS + i * 16 + t * 4) = pack_bf16(acc[4 * i + 2], acc[4 * i + 3]);
  }
  named_bar(1, 256);
  TS_MID(STATS ? 3 : 5, 2);
#pragma unroll
  for (int i = 0; i < 5; i++) {
    const int idx = i * 256 + tid, r = idx / 10, c = idx % 10;
    const uint4 a = *(const uint4*)(sptr + r * LDS + c * 16);
    const uint4 b = rv[i];
    uint4 o;
    o.x = pack_bf16(bf_lo(a.x) + bf_lo(b.x), bf_hi(a.x) + bf_hi(b.x));
    o.y = pack_bf16(bf_lo(a.y) + bf_lo(b.y), bf_hi(a.y) + bf_hi(b.y));
    o.z = pack_bf16(bf_lo(a.z) + bf_lo(b.z), bf_hi(a.z) + bf_hi(b.z));
    o.w = pack_bf16(bf_lo(a.w) + bf_lo(b.w), bf_hi(a.w) + bf_hi(b.w));
    st_g16(out + (size_t)(m0 + r) * DM + n0 + c * 8, o);
    if constexpr (STATS) *(uint4*)(sptr + r * LDS + c * 16) = o;
  }
  TS_MID(STATS ? 3 : 5, 3);
  if constexpr (STATS) {
    named_bar(1, 256);
    const int r = tid >> 1, hf = tid & 1;
    float f[40];
#pragma unroll
    for (int i = 0; i < 5; i++) {
      const uint4 v = *(const uint4*)(sptr + r * LDS + hf * 80 + i * 16);
      f[8 * i] = bf_lo(v.x); f[8 * i + 1] = bf_hi(v.x); f[8 * i + 2] = bf_lo(v.y); f[8 * i + 3] = bf_hi(v.y);
      f[8 * i + 4] = bf_lo(v.z); f[8 * i + 5] = bf_hi(v.z); f[8 * i + 6] = bf_lo(v.w); f[8 * i + 7] = bf_hi(v.w);
    }
    float s = 0.f;
#pragma unroll
    for (int i = 0; i < 40; i++) s += f[i];
    s += __shfl_xor_sync(~0u, s, 1);
    const float mu = s * (1.0f / 80.f);
    float q = 0.f;
#pragma unroll
    for (int i = 0; i < 40; i++) { const float d = f[i] - mu; q += d * d; }
    q += __shfl_xor_sync(~0u, q, 1);
    if (hf == 0) g_part2[(m0 + r) * 8 + blockIdx.x] = make_float2(s, q);
  }
  TS_END(STATS ? 3 : 5);
}

#define POLY_NUM 5
__device__ __forceinline__ float ex2_poly(float x, int shl23) {
  const float MAGIC = 12582912.f;
  const float tt = x + MAGIC;
  const float f = x - (tt - MAGIC);
  float p = fmaf(0.0013276472454890609f, f, 0.009675540961325169f);
  p = fmaf(p, f, 0.05550713092088699f);
  p = fmaf(p, f, 0.24022120237350464f);
  p = fmaf(p, f, 0.6931469440460205f);
  p = fmaf(p, f, 1.0000001192092896f);
  return __int_as_float(__float_as_int(tt) * shl23 + __float_as_int(p));
}
constexpr int KV_BYTES = S_LEN * 48;
constexpr int ATT_SMEM = 2 * KV_BYTES + 256 + 32768;
constexpr int ATT_BODY = 8;

__global__ void __launch_bounds__(512, 1) attn_kernel(int shl23, const __nv_bfloat16* __restrict__ wg_, const __nv_bfloat16* __restrict__ wu_,
                                                      const __grid_constant__ CUtensorMap tmWo, const __grid_constant__ CUtensorMap tmWd) {
  extern __shared__ __align__(1024) uint8_t smem[];
  if (blockIdx.x < 4) {
    pdl_launch();
    const int e = blockIdx.x, half = threadIdx.x >> 8;
    TS_MID(0, 0);
    const uint32_t sb = smem_u32(smem), bar = sb + 200 * 1024;
    auto rt_load = [&](int rd) {
      mbar_expect_tx(bar, 17 * 10240);
      for (int i = 0; i < 17; i++) {
        const int tl = e * 68 + rd * 17 + i;
        if (tl >= 80) tma_3d(sb + i * 10240, &tmWd, 0, ((tl - 80) % 24) * 64, ((tl - 80) / 24) * 5, bar);
        else tma_3d(sb + i * 10240, &tmWo, 0, (tl % 10) * 64, (tl / 10) * 5, bar);
      }
    };
    auto rt_store = [&](int rd) {
      mbar_wait(bar, rd & 1);
      for (int i = 0; i < 17; i++) {
        const int tl = e * 68 + rd * 17 + i;
        uint8_t* dst = tl >= 80 ? (uint8_t*)g_wd_t + (size_t)(tl - 80) * 10240 : (uint8_t*)g_wo_t + (size_t)tl * 10240;
        asm volatile("cp.async.bulk.global.shared::cta.bulk_group [%0], [%1], %2;" :: "l"(dst), "r"(sb + i * 10240), "r"(10240) : "memory");
      }
      asm volatile("cp.async.bulk.commit_group;" ::: "memory");
      asm volatile("cp.async.bulk.wait_group.read 0;" ::: "memory");
    };
    if (threadIdx.x == 0) {
      mbar_init(bar, 1);
      asm volatile("fence.mbarrier_init.release.cluster;" ::: "memory");
      rt_load(0);
    }
    __syncwarp();
    float (*red)[65] = (float (*)[65])(smem + 176 * 1024 + half * 10240);
    for (int i = 0; i < 6; i++) {
      const int b = e * 12 + half + 2 * i;
      if (b < 24) colsum64(wg_, DFF, b * 64, g_cs_g, red, threadIdx.x & 255, 1 + half);
      else colsum64(wu_, DFF, (b - 24) * 64, g_cs_u, red, threadIdx.x & 255, 1 + half);
      if ((i & 1) && threadIdx.x == 0) { rt_store(i >> 1); rt_load((i >> 1) + 1); }
      __syncwarp();
    }
    if (threadIdx.x == 0) { rt_store(3); asm volatile("cp.async.bulk.wait_group 0;" ::: "memory"); }
    TS_MID(0, 2);
    return;
  }
  const int h = (blockIdx.x - 4) >> 2, qb = blockIdx.x & 3;
  const uint32_t sK = smem_u32(smem), sV = sK + KV_BYTES, sBar = sV + KV_BYTES;
  const int tid = threadIdx.x;
  TS_BEGIN(2);
  if (tid == 0) {
    for (int i = 0; i < 9; i++) mbar_init(sBar + 8 * i, 1);
    asm volatile("fence.mbarrier_init.release.cluster;" ::: "memory");
  }
  __syncthreads();
  pdl_launch();
  pdl_wait();
  TS_MID(2, 0);
  const uint8_t* gk = (const uint8_t*)(g_k + (size_t)h * S_LEN * 24);
  const uint8_t* gv = (const uint8_t*)(g_v + (size_t)h * S_LEN * 24);
  auto load_kv = [&](int i0, int i1) {
    for (int i = i0; i < i1; i++) {
      mbar_expect_tx(sBar + 8 * i, 2 * 12288);
      bulk_g2s(sK + i * 12288, gk + i * 12288, 12288, sBar + 8 * i);
      bulk_g2s(sV + i * 12288, gv + i * 12288, 12288, sBar + 8 * i);
    }
  };
  if (tid == 0) {
    mbar_expect_tx(sBar + 64, 32768);
    bulk_g2s(sBar + 256, (const uint8_t*)g_q + ((size_t)h * S_LEN + qb * 512) * 64, 32768, sBar + 64);
    load_kv(0, 2);
  }
  float ka = 0.f, kb = 0.f;
#pragma unroll
  for (int i = 0; i < 8; i++) {
    const float2 v = *(const float2*)&g_kn[(i * NH + h) * 2];
    ka = (v.x > ka || v.x != v.x) ? v.x : ka;
    kb = (v.y > kb || v.y != v.y) ? v.y : kb;
  }
  bool fast;
  {
    const float kn = sqrtf(ka + kb);
    mbar_wait(sBar + 64, 0);
    if (tid == 0) load_kv(2, 8);
    uint8_t* qrow = smem + 2 * KV_BYTES + 256 + (tid >> 3) * 512 + (tid & 7) * 16;
    const uint4 c0 = *(const uint4*)qrow, c1 = *(const uint4*)(qrow + 128);
    const uint2 c2 = *(const uint2*)(qrow + 256);
    auto sq = [](uint32_t u) { const float a = bf_lo(u), b = bf_hi(u); return a * a + b * b; };
    const float n2 = sq(c0.x) + sq(c0.y) + sq(c0.z) + sq(c0.w) + sq(c1.x) + sq(c1.y) + sq(c1.z) + sq(c1.w) + sq(c2.x) + sq(c2.y);
    const float m = ceilf(sqrtf(n2) * kn * 1.001f) + 1.f;
    fast = __syncthreads_or(!(m <= 62.f)) == 0;
    if (fast) *(uint32_t*)(qrow + 256 + 8) = pack_bf16(-m, 0.f);
    asm volatile("fence.proxy.async.shared::cta;" ::: "memory");
    __syncthreads();
  }
  auto write_out = [&](float (&O)[12], int it) {
    uint32_t tid2;
    asm volatile("mov.u32 %0, %%tid.x;" : "=r"(tid2));
    const int lane2 = tid2 & 31, t2 = lane2 & 3;
    const int qq = (blockIdx.x & 3) * 512 + (it * 4 + (tid2 >> 7)) * 64 + ((tid2 >> 5) & 3) * 16 + (lane2 >> 2);
    const float l0 = __shfl_sync(~0u, O[8], (lane2 & ~3) | 2), l1 = __shfl_sync(~0u, O[10], (lane2 & ~3) | 2);
    const float r0 = 1.f / l0, r1 = 1.f / l1;
    uint32_t* o0 = (uint32_t*)(g_o + (size_t)qq * DM + ((blockIdx.x - 4) >> 2) * DH);
    uint32_t* o1 = o0 + 8 * DM / 2;
    o0[t2] = pack_bf16(O[0] * r0, O[1] * r0); o1[t2] = pack_bf16(O[2] * r1, O[3] * r1);
    o0[t2 + 4] = pack_bf16(O[4] * r0, O[5] * r0); o1[t2 + 4] = pack_bf16(O[6] * r1, O[7] * r1);
    if (t2 < 2) { o0[t2 + 8] = pack_bf16(O[8] * r0, O[9] * r0); o1[t2 + 8] = pack_bf16(O[10] * r1, O[11] * r1); }
  };
  TS_MID(2, 1);
  if (fast) {
#pragma unroll 1
    for (int it = 0; it < 2; it++) {
      const uint64_t dq = make_desc(sBar + 256 + (it * 4 + (tid >> 7)) * 4096, 128, 512, 0);
      float O[12];
#pragma unroll
      for (int i = 0; i < 12; i++) { O[i] = 0.f; asm volatile("" : "+f"(O[i]) :: "memory"); }
      float S[2][32];
      uint32_t P[16];
#pragma unroll 1
      for (int jb = 0; jb < 32 / ATT_BODY; jb++) {
        if (it == 0) { for (int c = 0; c < ATT_BODY / 4; c++) mbar_wait(sBar + 8 * (jb * (ATT_BODY / 4) + c), 0); }
        const uint64_t dk0 = make_desc(sK + jb * ATT_BODY * 8 * 384, 128, 384, 0);
        const uint64_t dv0 = make_desc(sV + jb * ATT_BODY * 8 * 384, 384, 128, 0);
        wgmma_fence();
        wgmma_ss_n64_k(S[0], dq, dk0, 0);
        wgmma_ss_n64_k(S[0], dq + (256 >> 4), dk0 + (256 >> 4), 1);
        wgmma_commit();
#pragma unroll
        for (int u = 0; u < ATT_BODY; u++) {
          if (u + 1 < ATT_BODY) {
            const uint64_t dk = dk0 + (((u + 1) * 8 * 384) >> 4);
            wgmma_fence();
            wgmma_ss_n64_k(S[(u + 1) & 1], dq, dk, 0);
            wgmma_ss_n64_k(S[(u + 1) & 1], dq + (256 >> 4), dk + (256 >> 4), 1);
            wgmma_commit();
          }
          if (u == 0 || u == ATT_BODY - 1) wgmma_wait<1>(); else wgmma_wait<2>();
#pragma unroll
          for (int i = 0; i < 32; i++) asm volatile("" : "+f"(S[u & 1][i]) :: "memory");
          const uint64_t dv = dv0 + ((u * 8 * 384) >> 4);
#pragma unroll
          for (int hf = 0; hf < 2; hf++) {
            if (hf == 1 && u > 0) { if (u == ATT_BODY - 1) wgmma_wait<1>(); else wgmma_wait<2>(); }
#pragma unroll
            for (int i = hf * 8; i < hf * 8 + 8; i++) {
              const bool usepoly = ((i + 1) * POLY_NUM / 16) != (i * POLY_NUM / 16);
              float a, b;
              if (usepoly) { a = ex2_poly(S[u & 1][2 * i], shl23); b = ex2_poly(S[u & 1][2 * i + 1], shl23); }
              else { a = ex2_mufu(S[u & 1][2 * i]); b = ex2_mufu(S[u & 1][2 * i + 1]); }
              P[i] = pack_bf16(a, b);
            }
            wgmma_fence();
#pragma unroll
            for (int ks = hf * 2; ks < hf * 2 + 2; ks++)
              wgmma_rs_n24_tb(O, P[4 * ks], P[4 * ks + 1], P[4 * ks + 2], P[4 * ks + 3], dv + ((ks * 768) >> 4), 1);
            wgmma_commit();
          }
        }
        wgmma_wait<0>();
      }
#pragma unroll
      for (int i = 0; i < 12; i++) asm volatile("" : "+f"(O[i]) :: "memory");
      write_out(O, it);
      if (it == 0) TS_MID(2, 2);
    }
  } else {
#pragma unroll 1
    for (int it = 0; it < 2; it++) {
      const uint64_t dq = make_desc(sBar + 256 + (it * 4 + (tid >> 7)) * 4096, 128, 512, 0);
      float O[12];
#pragma unroll
      for (int i = 0; i < 12; i++) { O[i] = 0.f; asm volatile("" : "+f"(O[i]) :: "memory"); }
      float S[32];
      float mx0 = -INFINITY, mx1 = -INFINITY;
#pragma unroll 1
      for (int j = 0; j < 32; j++) {
        if (it == 0 && (j & 3) == 0) mbar_wait(sBar + 8 * (j >> 2), 0);
        const uint64_t dk = make_desc(sK + j * 8 * 384, 128, 384, 0);
        wgmma_fence();
        wgmma_ss_n64_k(S, dq, dk, 0);
        wgmma_ss_n64_k(S, dq + (256 >> 4), dk + (256 >> 4), 1);
        wgmma_commit();
        wgmma_wait<0>();
#pragma unroll
        for (int i = 0; i < 8; i++) {
          mx0 = fmaxf(mx0, fmaxf(S[4 * i], S[4 * i + 1]));
          mx1 = fmaxf(mx1, fmaxf(S[4 * i + 2], S[4 * i + 3]));
        }
      }
      mx0 = fmaxf(mx0, __shfl_xor_sync(~0u, mx0, 1)); mx0 = fmaxf(mx0, __shfl_xor_sync(~0u, mx0, 2));
      mx1 = fmaxf(mx1, __shfl_xor_sync(~0u, mx1, 1)); mx1 = fmaxf(mx1, __shfl_xor_sync(~0u, mx1, 2));
#pragma unroll 1
      for (int j = 0; j < 32; j++) {
        const uint64_t dk = make_desc(sK + j * 8 * 384, 128, 384, 0);
        wgmma_fence();
        wgmma_ss_n64_k(S, dq, dk, 0);
        wgmma_ss_n64_k(S, dq + (256 >> 4), dk + (256 >> 4), 1);
        wgmma_commit();
        wgmma_wait<0>();
        uint32_t P[16];
#pragma unroll
        for (int i = 0; i < 8; i++) {
          P[2 * i] = pack_bf16(ex2_mufu(S[4 * i] - mx0), ex2_mufu(S[4 * i + 1] - mx0));
          P[2 * i + 1] = pack_bf16(ex2_mufu(S[4 * i + 2] - mx1), ex2_mufu(S[4 * i + 3] - mx1));
        }
        wgmma_fence();
        const uint64_t dv = make_desc(sV + j * 8 * 384, 384, 128, 0);
#pragma unroll
        for (int ks = 0; ks < 4; ks++)
          wgmma_rs_n24_tb(O, P[4 * ks], P[4 * ks + 1], P[4 * ks + 2], P[4 * ks + 3], dv + ((ks * 768) >> 4), 1);
        wgmma_commit();
        wgmma_wait<0>();
      }
#pragma unroll
      for (int i = 0; i < 12; i++) asm volatile("" : "+f"(O[i]) :: "memory");
      write_out(O, it);
    }
  }
  TS_END(2);
}

typedef CUresult (*EncodeFn)(CUtensorMap*, CUtensorMapDataType, cuuint32_t, void*, const cuuint64_t*, const cuuint64_t*, const cuuint32_t*,
                             const cuuint32_t*, CUtensorMapInterleave, CUtensorMapSwizzle, CUtensorMapL2promotion, CUtensorMapFloatOOBfill);
static EncodeFn get_encode() {
  static EncodeFn fn = nullptr;
  if (!fn) {
    void* p = nullptr; cudaDriverEntryPointQueryResult st;
    cudaGetDriverEntryPoint("cuTensorMapEncodeTiled", &p, cudaEnableDefault, &st);
    fn = (EncodeFn)p;
  }
  return fn;
}
static CUtensorMap make_map(const void* ptr, int rows, int cols, int box_rows, int box_cols = 64) {
  CUtensorMap m;
  cuuint64_t dims[2] = {(cuuint64_t)cols, (cuuint64_t)rows};
  cuuint64_t strides[1] = {(cuuint64_t)cols * 2};
  cuuint32_t box[2] = {(cuuint32_t)box_cols, (cuuint32_t)box_rows};
  cuuint32_t es[2] = {1, 1};
  get_encode()(&m, CU_TENSOR_MAP_DATA_TYPE_BFLOAT16, 2, const_cast<void*>(ptr), dims, strides, box, es, CU_TENSOR_MAP_INTERLEAVE_NONE,
               box_cols == 64 ? CU_TENSOR_MAP_SWIZZLE_128B : (box_cols == 32 ? CU_TENSOR_MAP_SWIZZLE_64B : CU_TENSOR_MAP_SWIZZLE_32B), CU_TENSOR_MAP_L2_PROMOTION_L2_128B, CU_TENSOR_MAP_FLOAT_OOB_FILL_NONE);
  return m;
}
static CUtensorMap make_map_w(const void* ptr, int rows, int cols, int bc, int nblk) {
  CUtensorMap m;
  cuuint64_t dims[3] = {(cuuint64_t)bc, (cuuint64_t)rows, (cuuint64_t)(cols / bc)};
  cuuint64_t strides[2] = {(cuuint64_t)cols * 2, (cuuint64_t)bc * 2};
  cuuint32_t box[3] = {(cuuint32_t)bc, 64, (cuuint32_t)nblk};
  cuuint32_t es[3] = {1, 1, 1};
  get_encode()(&m, CU_TENSOR_MAP_DATA_TYPE_BFLOAT16, 3, const_cast<void*>(ptr), dims, strides, box, es, CU_TENSOR_MAP_INTERLEAVE_NONE,
               bc == 64 ? CU_TENSOR_MAP_SWIZZLE_128B : (bc == 32 ? CU_TENSOR_MAP_SWIZZLE_64B : CU_TENSOR_MAP_SWIZZLE_32B),
               CU_TENSOR_MAP_L2_PROMOTION_L2_128B, CU_TENSOR_MAP_FLOAT_OOB_FILL_NONE);
  return m;
}
template <typename... KArgs, typename... Args>
static void launch(void (*kern)(KArgs...), dim3 grid, dim3 block, size_t smem, bool pdl, Args... args) {
  cudaLaunchConfig_t cfg = {};
  cfg.gridDim = grid; cfg.blockDim = block; cfg.dynamicSmemBytes = smem; cfg.stream = cudaStreamPerThread;
  cudaLaunchAttribute at[1];
  at[0].id = cudaLaunchAttributeProgrammaticStreamSerialization;
  at[0].val.programmaticStreamSerializationAllowed = 1;
  cfg.attrs = at; cfg.numAttrs = pdl ? 1 : 0;
  cudaLaunchKernelEx(&cfg, kern, KArgs(args)...);
}

extern "C" void kernel_launch(void* const* d_in, const int* in_sizes, int n_in, void* d_out, int out_size) {
  const __nv_bfloat16* x = (const __nv_bfloat16*)d_in[0];
  const __nv_bfloat16* wqkv = (const __nv_bfloat16*)d_in[1];
  const __nv_bfloat16* wo = (const __nv_bfloat16*)d_in[2];
  const __nv_bfloat16* wgate = (const __nv_bfloat16*)d_in[4];
  const __nv_bfloat16* wup = (const __nv_bfloat16*)d_in[5];
  const __nv_bfloat16* wdown = (const __nv_bfloat16*)d_in[6];
  __nv_bfloat16* out = (__nv_bfloat16*)d_out;
  void *p_o, *p_h, *p_act;
  cudaGetSymbolAddress(&p_o, g_o); cudaGetSymbolAddress(&p_h, g_h); cudaGetSymbolAddress(&p_act, g_act);

  auto kA = gemm_kernel<256, 128, 1, DM, 4, EPI_QKV>;
  auto kC = gemm_res_kernel<DM, true>;
  auto kD = gemm_kernel<128, 192, 2, DM, 3, EPI_GLU>;
  auto kE = gemm_res_kernel<DFF, false>;
  constexpr int smA = GemmCfg<256, 128, 1, 4>::SMEM, smC = R_SMEM, smD = GemmCfg<128, 192, 2, 3>::SMEM;
  cudaFuncSetAttribute(kA, cudaFuncAttributeMaxDynamicSharedMemorySize, smA);
  cudaFuncSetAttribute(kC, cudaFuncAttributeMaxDynamicSharedMemorySize, smC);
  cudaFuncSetAttribute(kD, cudaFuncAttributeMaxDynamicSharedMemorySize, smD);
  cudaFuncSetAttribute(kE, cudaFuncAttributeMaxDynamicSharedMemorySize, smC);
  cudaFuncSetAttribute(attn_kernel, cudaFuncAttributeMaxDynamicSharedMemorySize, ATT_SMEM);

  const CUtensorMap tm_x = make_map(x, S_LEN, DM, 256), tm_wqkv = make_map_w(wqkv, DM, 3 * DM, 64, 2);
  const CUtensorMap tm_o = make_map(p_o, S_LEN, DM, 128), tm_wo = make_map_w(wo, DM, DM, 16, 5);
  const CUtensorMap tm_h = make_map(p_h, S_LEN, DM, 128), tm_wg = make_map_w(wgate, DM, DFF, 64, 3), tm_wu = make_map_w(wup, DM, DFF, 64, 3);
  const CUtensorMap tm_act = make_map(p_act, S_LEN, DFF, 128), tm_wd = make_map_w(wdown, DFF, DM, 16, 5);

  cudaFuncSetAttribute(pre_kernel, cudaFuncAttributeMaxDynamicSharedMemorySize, PRE_SMEM);
  launch(pre_kernel, dim3(12), dim3(1024), PRE_SMEM, false, x, wqkv);
  launch(kA, dim3(15, 8), dim3(288), smA, true, tm_x, tm_wqkv, tm_wqkv, (__nv_bfloat16*)nullptr);
  launch(attn_kernel, dim3(132), dim3(512), ATT_SMEM, true, 0x800000, wgate, wup, tm_wo, tm_wd);
  launch(kC, dim3(8, 16), dim3(288), smC, true, tm_o, x, (__nv_bfloat16*)p_h);
  launch(kD, dim3(8, 16), dim3(384), smD, true, tm_h, tm_wg, tm_wu, (__nv_bfloat16*)p_act);
  launch(kE, dim3(8, 16), dim3(288), smC, true, tm_act, (const __nv_bfloat16*)p_h, out);
}
```

```cpp
#include <cuda_runtime.h>
#include <cuda_bf16.h>
#include <cuda.h>
#include <stdint.h>

constexpr int S_LEN = 2048, DM = 640, NH = 32, DH = 20, DFF = 1536;

__device__ __align__(1024) __nv_bfloat16 g_q[NH * S_LEN * 32];
__device__ __align__(1024) __nv_bfloat16 g_k[NH * S_LEN * 24];
__device__ __align__(1024) __nv_bfloat16 g_v[NH * S_LEN * 24];
__device__ __align__(1024) __nv_bfloat16 g_o[S_LEN * DM];
__device__ __align__(1024) __nv_bfloat16 g_h[S_LEN * DM];
__device__ __align__(1024) __nv_bfloat16 g_act[S_LEN * DFF];
__device__ __align__(1024) __nv_bfloat16 g_wo_t[DM * DM];
__device__ __align__(1024) __nv_bfloat16 g_wd_t[DFF * DM];
__device__ float g_kn[8 * NH * 2];
__device__ float2 g_stat1[S_LEN];
__device__ float g_cs_qkv[3 * DM];
__device__ float g_cs_g[DFF];
__device__ float g_cs_u[DFF];
__device__ float2 g_part2[S_LEN * 8];

#define TS_BEGIN(k)
#define TS_END(k)
#define TS_MID(k, i)
__device__ __forceinline__ uint32_t smem_u32(const void* p) { return (uint32_t)__cvta_generic_to_shared(p); }
__device__ __forceinline__ void mbar_init(uint32_t bar, uint32_t cnt) { asm volatile("mbarrier.init.shared::cta.b64 [%0], %1;" :: "r"(bar), "r"(cnt)); }
__device__ __forceinline__ void mbar_expect_tx(uint32_t bar, uint32_t bytes) { asm volatile("mbarrier.arrive.expect_tx.shared::cta.b64 _, [%0], %1;" :: "r"(bar), "r"(bytes) : "memory"); }
__device__ __forceinline__ void mbar_arrive(uint32_t bar) { asm volatile("mbarrier.arrive.shared::cta.b64 _, [%0];" :: "r"(bar) : "memory"); }
__device__ __forceinline__ void mbar_wait(uint32_t bar, uint32_t parity) {
  uint32_t done;
  uint32_t spins = 0;
  do {
    asm volatile("{\n.reg .pred P1;\nmbarrier.try_wait.parity.shared::cta.b64 P1, [%1], %2;\nselp.u32 %0, 1, 0, P1;\n}" : "=r"(done) : "r"(bar), "r"(parity) : "memory");
  } while (!done && ++spins < (1u << 24));
}
__device__ __forceinline__ void bulk_g2s(uint32_t dst, const void* src, uint32_t bytes, uint32_t bar) {
  asm volatile("cp.async.bulk.shared::cluster.global.mbarrier::complete_tx::bytes [%0], [%1], %2, [%3];" :: "r"(dst), "l"(src), "r"(bytes), "r"(bar) : "memory");
}
__device__ __forceinline__ void tma_2d(uint32_t dst, const CUtensorMap* tm, int c0, int c1, uint32_t bar) {
  asm volatile("cp.async.bulk.tensor.2d.shared::cluster.global.mbarrier::complete_tx::bytes [%0], [%1, {%3, %4}], [%2];"
               :: "r"(dst), "l"(tm), "r"(bar), "r"(c0), "r"(c1) : "memory");
}
__device__ __forceinline__ void tma_3d(uint32_t dst, const CUtensorMap* tm, int c0, int c1, int c2, uint32_t bar) {
  asm volatile("cp.async.bulk.tensor.3d.shared::cluster.global.mbarrier::complete_tx::bytes [%0], [%1, {%3, %4, %5}], [%2];"
               :: "r"(dst), "l"(tm), "r"(bar), "r"(c0), "r"(c1), "r"(c2) : "memory");
}
__device__ __forceinline__ void wgmma_fence() { asm volatile("wgmma.fence.sync.aligned;" ::: "memory"); }
__device__ __forceinline__ void wgmma_commit() { asm volatile("wgmma.commit_group.sync.aligned;" ::: "memory"); }
template <int N> __device__ __forceinline__ void wgmma_wait() { asm volatile("wgmma.wait_group.sync.aligned %0;" :: "n"(N) : "memory"); }
__device__ __forceinline__ void pdl_wait() { asm volatile("griddepcontrol.wait;" ::: "memory"); }
__device__ __forceinline__ void pdl_launch() { asm volatile("griddepcontrol.launch_dependents;" ::: "memory"); }
__device__ __forceinline__ void named_bar(int id, int n) { asm volatile("bar.sync %0, %1;" :: "r"(id), "r"(n) : "memory"); }
__device__ __forceinline__ uint64_t make_desc(uint32_t addr, uint32_t lbo, uint32_t sbo, uint32_t swz) {
  return (uint64_t)((addr & 0x3FFFF) >> 4) | ((uint64_t)(lbo >> 4) << 16) | ((uint64_t)(sbo >> 4) << 32) | ((uint64_t)swz << 62);
}
__device__ __forceinline__ void st_g16(void* p, uint4 v) { asm volatile("st.global.v4.b32 [%0], {%1, %2, %3, %4};" :: "l"(p), "r"(v.x), "r"(v.y), "r"(v.z), "r"(v.w) : "memory"); }
__device__ __forceinline__ void st_g8(void* p, uint2 v) { asm volatile("st.global.v2.b32 [%0], {%1, %2};" :: "l"(p), "r"(v.x), "r"(v.y) : "memory"); }
__device__ __forceinline__ uint4 ld_g16(const void* p) { uint4 v; asm volatile("ld.global.v4.b32 {%0, %1, %2, %3}, [%4];" : "=r"(v.x), "=r"(v.y), "=r"(v.z), "=r"(v.w) : "l"(p) : "memory"); return v; }
__device__ __forceinline__ uint32_t pack_bf16(float lo, float hi) { uint32_t r; asm("cvt.rn.bf16x2.f32 %0, %1, %2;" : "=r"(r) : "f"(hi), "f"(lo)); return r; }
__device__ __forceinline__ float bf_lo(uint32_t u) { return __uint_as_float(u << 16); }
__device__ __forceinline__ float bf_hi(uint32_t u) { return __uint_as_float(u & 0xffff0000u); }
__device__ __forceinline__ float bf_round(float x) { return __bfloat162float(__float2bfloat16_rn(x)); }
__device__ __forceinline__ float ex2_mufu(float x) { float y; asm("ex2.approx.ftz.f32 %0, %1;" : "=f"(y) : "f"(x)); return y; }

__device__ __forceinline__ void wgmma_ss_n80(float (&d)[40], uint64_t da, uint64_t db, int scale_d) {
  asm volatile("{\n.reg .pred p;\nsetp.ne.b32 p, %42, 0;\n"
    "wgmma.mma_async.sync.aligned.m64n80k16.f32.bf16.bf16 {%0,%1,%2,%3,%4,%5,%6,%7,%8,%9,%10,%11,%12,%13,%14,%15,%16,%17,%18,%19,%20,%21,%22,%23,%24,%25,%26,%27,%28,%29,%30,%31,%32,%33,%34,%35,%36,%37,%38,%39}, %40, %41, p, 1, 1, 0, 1;\n}\n"
    : "+f"(d[0]),"+f"(d[1]),"+f"(d[2]),"+f"(d[3]),"+f"(d[4]),"+f"(d[5]),"+f"(d[6]),"+f"(d[7]),"+f"(d[8]),"+f"(d[9]),"+f"(d[10]),"+f"(d[11]),"+f"(d[12]),"+f"(d[13]),"+f"(d[14]),"+f"(d[15]),"+f"(d[16]),"+f"(d[17]),"+f"(d[18]),"+f"(d[19]),"+f"(d[20]),"+f"(d[21]),"+f"(d[22]),"+f"(d[23]),"+f"(d[24]),"+f"(d[25]),"+f"(d[26]),"+f"(d[27]),"+f"(d[28]),"+f"(d[29]),"+f"(d[30]),"+f"(d[31]),"+f"(d[32]),"+f"(d[33]),"+f"(d[34]),"+f"(d[35]),"+f"(d[36]),"+f"(d[37]),"+f"(d[38]),"+f"(d[39])
    : "l"(da), "l"(db), "r"(scale_d));
}
__device__ __forceinline__ void wgmma_ss_n128(float (&d)[64], uint64_t da, uint64_t db, int scale_d) {
  asm volatile("{\n.reg .pred p;\nsetp.ne.b32 p, %66, 0;\n"
    "wgmma.mma_async.sync.aligned.m64n128k16.f32.bf16.bf16 {%0,%1,%2,%3,%4,%5,%6,%7,%8,%9,%10,%11,%12,%13,%14,%15,%16,%17,%18,%19,%20,%21,%22,%23,%24,%25,%26,%27,%28,%29,%30,%31,%32,%33,%34,%35,%36,%37,%38,%39,%40,%41,%42,%43,%44,%45,%46,%47,%48,%49,%50,%51,%52,%53,%54,%55,%56,%57,%58,%59,%60,%61,%62,%63}, %64, %65, p, 1, 1, 0, 1;\n}\n"
    : "+f"(d[0]),"+f"(d[1]),"+f"(d[2]),"+f"(d[3]),"+f"(d[4]),"+f"(d[5]),"+f"(d[6]),"+f"(d[7]),"+f"(d[8]),"+f"(d[9]),"+f"(d[10]),"+f"(d[11]),"+f"(d[12]),"+f"(d[13]),"+f"(d[14]),"+f"(d[15]),"+f"(d[16]),"+f"(d[17]),"+f"(d[18]),"+f"(d[19]),"+f"(d[20]),"+f"(d[21]),"+f"(d[22]),"+f"(d[23]),"+f"(d[24]),"+f"(d[25]),"+f"(d[26]),"+f"(d[27]),"+f"(d[28]),"+f"(d[29]),"+f"(d[30]),"+f"(d[31]),"+f"(d[32]),"+f"(d[33]),"+f"(d[34]),"+f"(d[35]),"+f"(d[36]),"+f"(d[37]),"+f"(d[38]),"+f"(d[39]),"+f"(d[40]),"+f"(d[41]),"+f"(d[42]),"+f"(d[43]),"+f"(d[44]),"+f"(d[45]),"+f"(d[46]),"+f"(d[47]),"+f"(d[48]),"+f"(d[49]),"+f"(d[50]),"+f"(d[51]),"+f"(d[52]),"+f"(d[53]),"+f"(d[54]),"+f"(d[55]),"+f"(d[56]),"+f"(d[57]),"+f"(d[58]),"+f"(d[59]),"+f"(d[60]),"+f"(d[61]),"+f"(d[62]),"+f"(d[63])
    : "l"(da), "l"(db), "r"(scale_d));
}
__device__ __forceinline__ void wgmma_ss_n192(float (&d)[96], uint64_t da, uint64_t db, int scale_d) {
  asm volatile("{\n.reg .pred p;\nsetp.ne.b32 p, %98, 0;\n"
    "wgmma.mma_async.sync.aligned.m64n192k16.f32.bf16.bf16 {%0,%1,%2,%3,%4,%5,%6,%7,%8,%9,%10,%11,%12,%13,%14,%15,%16,%17,%18,%19,%20,%21,%22,%23,%24,%25,%26,%27,%28,%29,%30,%31,%32,%33,%34,%35,%36,%37,%38,%39,%40,%41,%42,%43,%44,%45,%46,%47,%48,%49,%50,%51,%52,%53,%54,%55,%56,%57,%58,%59,%60,%61,%62,%63,%64,%65,%66,%67,%68,%69,%70,%71,%72,%73,%74,%75,%76,%77,%78,%79,%80,%81,%82,%83,%84,%85,%86,%87,%88,%89,%90,%91,%92,%93,%94,%95}, %96, %97, p, 1, 1, 0, 1;\n}\n"
    : "+f"(d[0]),"+f"(d[1]),"+f"(d[2]),"+f"(d[3]),"+f"(d[4]),"+f"(d[5]),"+f"(d[6]),"+f"(d[7]),"+f"(d[8]),"+f"(d[9]),"+f"(d[10]),"+f"(d[11]),"+f"(d[12]),"+f"(d[13]),"+f"(d[14]),"+f"(d[15]),"+f"(d[16]),"+f"(d[17]),"+f"(d[18]),"+f"(d[19]),"+f"(d[20]),"+f"(d[21]),"+f"(d[22]),"+f"(d[23]),"+f"(d[24]),"+f"(d[25]),"+f"(d[26]),"+f"(d[27]),"+f"(d[28]),"+f"(d[29]),"+f"(d[30]),"+f"(d[31]),"+f"(d[32]),"+f"(d[33]),"+f"(d[34]),"+f"(d[35]),"+f"(d[36]),"+f"(d[37]),"+f"(d[38]),"+f"(d[39]),"+f"(d[40]),"+f"(d[41]),"+f"(d[42]),"+f"(d[43]),"+f"(d[44]),"+f"(d[45]),"+f"(d[46]),"+f"(d[47]),"+f"(d[48]),"+f"(d[49]),"+f"(d[50]),"+f"(d[51]),"+f"(d[52]),"+f"(d[53]),"+f"(d[54]),"+f"(d[55]),"+f"(d[56]),"+f"(d[57]),"+f"(d[58]),"+f"(d[59]),"+f"(d[60]),"+f"(d[61]),"+f"(d[62]),"+f"(d[63]),"+f"(d[64]),"+f"(d[65]),"+f"(d[66]),"+f"(d[67]),"+f"(d[68]),"+f"(d[69]),"+f"(d[70]),"+f"(d[71]),"+f"(d[72]),"+f"(d[73]),"+f"(d[74]),"+f"(d[75]),"+f"(d[76]),"+f"(d[77]),"+f"(d[78]),"+f"(d[79]),"+f"(d[80]),"+f"(d[81]),"+f"(d[82]),"+f"(d[83]),"+f"(d[84]),"+f"(d[85]),"+f"(d[86]),"+f"(d[87]),"+f"(d[88]),"+f"(d[89]),"+f"(d[90]),"+f"(d[91]),"+f"(d[92]),"+f"(d[93]),"+f"(d[94]),"+f"(d[95])
    : "l"(da), "l"(db), "r"(scale_d));
}
__device__ __forceinline__ void wgmma_ss_n64_k(float (&d)[32], uint64_t da, uint64_t db, int scale_d) {
  asm volatile("{\n.reg .pred p;\nsetp.ne.b32 p, %34, 0;\n"
    "wgmma.mma_async.sync.aligned.m64n64k16.f32.bf16.bf16 {%0,%1,%2,%3,%4,%5,%6,%7,%8,%9,%10,%11,%12,%13,%14,%15,%16,%17,%18,%19,%20,%21,%22,%23,%24,%25,%26,%27,%28,%29,%30,%31}, %32, %33, p, 1, 1, 0, 0;\n}\n"
    : "+f"(d[0]),"+f"(d[1]),"+f"(d[2]),"+f"(d[3]),"+f"(d[4]),"+f"(d[5]),"+f"(d[6]),"+f"(d[7]),"+f"(d[8]),"+f"(d[9]),"+f"(d[10]),"+f"(d[11]),"+f"(d[12]),"+f"(d[13]),"+f"(d[14]),"+f"(d[15]),"+f"(d[16]),"+f"(d[17]),"+f"(d[18]),"+f"(d[19]),"+f"(d[20]),"+f"(d[21]),"+f"(d[22]),"+f"(d[23]),"+f"(d[24]),"+f"(d[25]),"+f"(d[26]),"+f"(d[27]),"+f"(d[28]),"+f"(d[29]),"+f"(d[30]),"+f"(d[31])
    : "l"(da), "l"(db), "r"(scale_d));
}
__device__ __forceinline__ void wgmma_rs_n24_tb(float (&d)[12], uint32_t a0, uint32_t a1, uint32_t a2, uint32_t a3, uint64_t db, int scale_d) {
  asm volatile("{\n.reg .pred p;\nsetp.ne.b32 p, %17, 0;\n"
    "wgmma.mma_async.sync.aligned.m64n24k16.f32.bf16.bf16 {%0,%1,%2,%3,%4,%5,%6,%7,%8,%9,%10,%11}, {%12,%13,%14,%15}, %16, p, 1, 1, 1;\n}\n"
    : "+f"(d[0]),"+f"(d[1]),"+f"(d[2]),"+f"(d[3]),"+f"(d[4]),"+f"(d[5]),"+f"(d[6]),"+f"(d[7]),"+f"(d[8]),"+f"(d[9]),"+f"(d[10]),"+f"(d[11])
    : "r"(a0), "r"(a1), "r"(a2), "r"(a3), "l"(db), "r"(scale_d));
}

__device__ __forceinline__ float2 ln_finish(float mean, float var) {
  float mb = bf_round(mean);
  float s = bf_round(sqrtf(bf_round(bf_round(var) + 1e-5f)));
  return make_float2(mb, 1.0f / s);
}
__device__ __forceinline__ void colsum64(const __nv_bfloat16* __restrict__ w, int ld, int c0, float* __restrict__ dst, float (*red)[65], int tid, int bar_id) {
  const int cg = tid & 7, r0 = tid >> 3;
  float acc[8];
#pragma unroll
  for (int i = 0; i < 8; i++) acc[i] = 0.f;
#pragma unroll 10
  for (int r = r0; r < DM; r += 32) {
    uint4 v = __ldg((const uint4*)(w + (size_t)r * ld + c0 + cg * 8));
    acc[0] += bf_lo(v.x); acc[1] += bf_hi(v.x); acc[2] += bf_lo(v.y); acc[3] += bf_hi(v.y);
    acc[4] += bf_lo(v.z); acc[5] += bf_hi(v.z); acc[6] += bf_lo(v.w); acc[7] += bf_hi(v.w);
  }
#pragma unroll
  for (int i = 0; i < 8; i++) red[r0][cg * 8 + i] = acc[i];
  named_bar(bar_id, 256);
  if (tid < 64) {
    float s = 0.f;
#pragma unroll
    for (int r = 0; r < 32; r++) s += red[r][tid];
    dst[c0 + tid] = s;
  }
  named_bar(bar_id, 256);
}
__global__ void __launch_bounds__(1024) pre_kernel(const __nv_bfloat16* __restrict__ x, const __nv_bfloat16* __restrict__ wqkv) {
  TS_BEGIN(0);
  pdl_launch();
  __shared__ float red[51][161];
  const int tid = threadIdx.x, lane = tid & 31, warp = tid >> 5;
  {
    const int ch = tid % 20, rl = tid / 20;
    if (rl < 51) {
      const __nv_bfloat16* w = wqkv + blockIdx.x * 160 + ch * 8;
      uint4 v[13];
#pragma unroll
      for (int i = 0; i < 13; i++) { const int r = rl + i * 51; v[i] = r < DM ? __ldg((const uint4*)(w + (size_t)r * (3 * DM))) : make_uint4(0, 0, 0, 0); }
      float acc[8];
#pragma unroll
      for (int i = 0; i < 8; i++) acc[i] = 0.f;
#pragma unroll
      for (int i = 0; i < 13; i++) {
        acc[0] += bf_lo(v[i].x); acc[1] += bf_hi(v[i].x); acc[2] += bf_lo(v[i].y); acc[3] += bf_hi(v[i].y);
        acc[4] += bf_lo(v[i].z); acc[5] += bf_hi(v[i].z); acc[6] += bf_lo(v[i].w); acc[7] += bf_hi(v[i].w);
      }
#pragma unroll
      for (int i = 0; i < 8; i++) red[rl][ch * 8 + i] = acc[i];
    }
  }
  const int rbeg = blockIdx.x * 171, rend = min(rbeg + 171, S_LEN);
  for (int row0 = rbeg + warp * 3; row0 < rend; row0 += 96) {
    uint4 v[3][3];
#pragma unroll
    for (int k = 0; k < 3; k++) {
      const int row = min(row0 + k, rend - 1);
      const uint4* p = (const uint4*)(x + (size_t)row * DM);
      v[k][0] = __ldg(p + lane); v[k][1] = __ldg(p + 32 + lane);
      v[k][2] = lane < 16 ? __ldg(p + 64 + lane) : make_uint4(0, 0, 0, 0);
    }
#pragma unroll
    for (int k = 0; k < 3; k++) {
      float f[24];
      const uint32_t u[12] = {v[k][0].x, v[k][0].y, v[k][0].z, v[k][0].w, v[k][1].x, v[k][1].y, v[k][1].z, v[k][1].w, v[k][2].x, v[k][2].y, v[k][2].z, v[k][2].w};
#pragma unroll
      for (int j = 0; j < 12; j++) { f[2 * j] = bf_lo(u[j]); f[2 * j + 1] = bf_hi(u[j]); }
      float s = 0.f;
#pragma unroll
      for (int j = 0; j < 24; j++) s += f[j];
#pragma unroll
      for (int o = 16; o; o >>= 1) s += __shfl_xor_sync(~0u, s, o);
      const float mean = s * (1.0f / DM);
      float q = 0.f;
#pragma unroll
      for (int j = 0; j < 16; j++) { const float d = f[j] - mean; q += d * d; }
      if (lane < 16) {
#pragma unroll
        for (int j = 16; j < 24; j++) { const float d = f[j] - mean; q += d * d; }
      }
#pragma unroll
      for (int o = 16; o; o >>= 1) q += __shfl_xor_sync(~0u, q, o);
      if (lane == 0 && row0 + k < rend) g_stat1[row0 + k] = ln_finish(mean, q * (1.0f / DM));
    }
  }
  __syncthreads();
  if (tid < 160) {
    float s = 0.f;
#pragma unroll 17
    for (int r = 0; r < 51; r++) s += red[r][tid];
    g_cs_qkv[blockIdx.x * 160 + tid] = s;
  }
  TS_END(0);
}

enum { EPI_QKV = 0, EPI_GLU = 2 };
template <int N> struct WG;
template <> struct WG<128> { static __device__ __forceinline__ void mma(float (&d)[64], uint64_t a, uint64_t b, int s) { wgmma_ss_n128(d, a, b, s); } };
template <> struct WG<192> { static __device__ __forceinline__ void mma(float (&d)[96], uint64_t a, uint64_t b, int s) { wgmma_ss_n192(d, a, b, s); } };

template <int BM, int BN, int NB, int STAGES> struct GemmCfg {
  static constexpr int A_BYTES = BM * 128;
  static constexpr int B_BYTES = NB * (BN / 64) * 8192;
  static constexpr int STAGE_BYTES = A_BYTES + B_BYTES;
  static constexpr int SMEM = STAGES * STAGE_BYTES + 1024   + 256   + 4096  ;
};

constexpr float QSCALE = 0.22360679774997896f * 1.4426950408889634f;

template <int BM, int BN, int NB, int KDIM, int STAGES, int EPI>
__global__ void __launch_bounds__(EPI == EPI_GLU ? 384 : 288, 1) gemm_kernel(const __grid_constant__ CUtensorMap tmA, const __grid_constant__ CUtensorMap tmB0,
                                                         const __grid_constant__ CUtensorMap tmB1, __nv_bfloat16* out) {
  using Cfg = GemmCfg<BM, BN, NB, STAGES>;
  constexpr int MB = BM / 128;
  constexpr int KT = KDIM / 64;
  extern __shared__ uint8_t smem_raw[];
  const uint32_t sbase = (smem_u32(smem_raw) + 1023u) & ~1023u;
  uint8_t* sptr = smem_raw + (sbase - smem_u32(smem_raw));
  const uint32_t sbar = sbase + STAGES * Cfg::STAGE_BYTES;
  const int tid = threadIdx.x, warp = tid >> 5, lane = tid & 31;
  const int n0 = blockIdx.x * BN, m0 = blockIdx.y * BM;
  TS_BEGIN(EPI == EPI_QKV ? 1 : EPI + 2);
  TS_MID(EPI == EPI_QKV ? 1 : EPI + 2, 3);
  if (tid == 0) {
    for (int i = 0; i < STAGES; i++) { mbar_init(sbar + 8 * i, 1); mbar_init(sbar + 8 * (STAGES + i), 8); }
    asm volatile("fence.mbarrier_init.release.cluster;" ::: "memory");
  }
  __syncthreads();
  pdl_launch();
  if (warp >= 8) {
    if constexpr (EPI == EPI_GLU) asm volatile("setmaxnreg.dec.sync.aligned.u32 40;");
    if (warp == 8 && lane == 0) {
      auto load_a = [&](int kt, int s) { tma_2d(sbase + s * Cfg::STAGE_BYTES, &tmA, kt * 64, m0, sbar + 8 * s); };
      auto load_b = [&](int kt, int s) {
        const uint32_t sb = sbase + s * Cfg::STAGE_BYTES + Cfg::A_BYTES;
        tma_3d(sb, &tmB0, 0, kt * 64, blockIdx.x * (BN / 64), sbar + 8 * s);
        if constexpr (NB == 2) tma_3d(sb + (BN / 64) * 8192, &tmB1, 0, kt * 64, blockIdx.x * (BN / 64), sbar + 8 * s);
      };
      for (int s = 0; s < STAGES; s++) { mbar_expect_tx(sbar + 8 * s, Cfg::STAGE_BYTES); if (s == 0) load_b(s, s); }
      if (EPI != EPI_QKV) pdl_wait();
      for (int s = 0; s < STAGES; s++) { load_a(s, s); if (s > 0) load_b(s, s); }
      for (int kt = STAGES; kt < KT; kt++) {
        const int s = kt % STAGES;
        mbar_wait(sbar + 8 * (STAGES + s), ((kt / STAGES) - 1) & 1);
        mbar_expect_tx(sbar + 8 * s, Cfg::STAGE_BYTES);
        load_a(kt, s);
        load_b(kt, s);
      }
    }
    if constexpr (EPI == EPI_GLU) {
      if (warp > 8) {
        float2* s_st = (float2*)(sptr + STAGES * Cfg::STAGE_BYTES + 256);
        float* s_cs = (float*)(sptr + STAGES * Cfg::STAGE_BYTES + 256 + 1024);
        pdl_wait();
        for (int r = tid - 288; r < BM; r += 96) {
          const float2* pp = &g_part2[(m0 + r) * 8];
          float s = 0.f;
#pragma unroll
          for (int i = 0; i < 8; i++) s += pp[i].x;
          const float mean = s * (1.0f / DM);
          float q = 0.f;
#pragma unroll
          for (int i = 0; i < 8; i++) { const float2 p = pp[i]; const float d = p.x * (1.0f / 80.f) - mean; q += p.y + 80.f * d * d; }
          s_st[r] = ln_finish(mean, q * (1.0f / DM));
        }
        for (int c = tid - 288; c < BN; c += 96) { s_cs[c] = g_cs_g[n0 + c]; s_cs[BN + c] = g_cs_u[n0 + c]; }
        __threadfence_block();
        asm volatile("bar.arrive 2, 352;" ::: "memory");
      }
    }
    return;
  }
  if constexpr (EPI == EPI_GLU) asm volatile("setmaxnreg.inc.sync.aligned.u32 232;");
  const int wg = warp >> 2, g = lane >> 2, t = lane & 3;
  float acc[MB][NB][BN / 2];
#pragma unroll
  for (int mb = 0; mb < MB; mb++)
#pragma unroll
    for (int nb = 0; nb < NB; nb++)
#pragma unroll
      for (int i = 0; i < BN / 2; i++) acc[mb][nb][i] = 0.f;
  for (int kt = 0; kt < KT; kt++) {
    const int s = kt % STAGES;
    mbar_wait(sbar + 8 * s, (kt / STAGES) & 1);
    if (kt == 0) TS_MID(EPI == EPI_QKV ? 1 : EPI + 2, 0);
    const uint32_t sa = sbase + s * Cfg::STAGE_BYTES + wg * (MB * 64 * 128);
    const uint32_t sb = sbase + s * Cfg::STAGE_BYTES + Cfg::A_BYTES;
    wgmma_fence();
#pragma unroll
    for (int ks = 0; ks < 4; ks++) {
#pragma unroll
      for (int mb = 0; mb < MB; mb++) {
        const uint64_t da = make_desc(sa + mb * 8192 + ks * 32, 16, 1024, 1);
#pragma unroll
        for (int nb = 0; nb < NB; nb++) {
          const uint64_t db = make_desc(sb + nb * (BN / 64) * 8192 + ks * 2048, 8192, 1024, 1);
          WG<BN>::mma(acc[mb][nb], da, db, 1);
        }
      }
    }
    wgmma_commit();
    wgmma_wait<1>();
    if (kt > 0 && kt - 1 + STAGES < KT && lane == 0) mbar_arrive(sbar + 8 * (STAGES + (kt - 1) % STAGES));
  }
  wgmma_wait<0>();
#pragma unroll
  for (int mb = 0; mb < MB; mb++)
#pragma unroll
    for (int nb = 0; nb < NB; nb++)
#pragma unroll
      for (int i = 0; i < BN / 2; i++) asm volatile("" : "+f"(acc[mb][nb][i]) :: "memory");
  TS_MID(EPI == EPI_QKV ? 1 : EPI + 2, 1);
  pdl_wait();
  TS_MID(EPI == EPI_QKV ? 1 : EPI + 2, 2);
  named_bar(1, 256);
  constexpr int LDS = BN * 2 + 16;
  const int ctid = tid;

  if constexpr (EPI == EPI_QKV) {
    const int sec = n0 / DM;
    constexpr int lds = 264;
    __shared__ unsigned int s_kn[8];
    if (ctid < 8) s_kn[ctid] = 0u;
    float2 cs[BN / 8];
#pragma unroll
    for (int j = 0; j < BN / 8; j++) cs[j] = *(const float2*)&g_cs_qkv[n0 + j * 8 + 2 * t];
#pragma unroll
    for (int mb = 0; mb < MB; mb++) {
      const int r0 = wg * (MB * 64) + mb * 64 + (warp & 3) * 16 + g;
      const float2 st0 = g_stat1[m0 + r0], st1 = g_stat1[m0 + r0 + 8];
      const float sc0 = sec == 0 ? st0.y * QSCALE : st0.y, sc1 = sec == 0 ? st1.y * QSCALE : st1.y;
#pragma unroll
      for (int j = 0; j < BN / 8; j++) {
        const float* a = &acc[mb][0][4 * j];
        *(uint32_t*)(sptr + r0 * lds + j * 16 + t * 4) = pack_bf16(fmaf(-st0.x, cs[j].x, a[0]) * sc0, fmaf(-st0.x, cs[j].y, a[1]) * sc0);
        *(uint32_t*)(sptr + (r0 + 8) * lds + j * 16 + t * 4) = pack_bf16(fmaf(-st1.x, cs[j].x, a[2]) * sc1, fmaf(-st1.x, cs[j].y, a[3]) * sc1);
      }
    }
    named_bar(1, 256);
    {
      const int cbase = n0 - sec * DM;
      const int hfirst = cbase / DH;
      const int j = m0 + ctid;
      uint8_t* dst = (uint8_t*)(sec == 0 ? g_q : (sec == 1 ? g_k : g_v)) + (size_t)(j >> 3) * (sec == 0 ? 512 : 384) + (j & 7) * 16;
      const uint8_t* row = sptr + ctid * 264;
#pragma unroll
      for (int i = 0; i < 8; i++) {
        const int hh = hfirst + i;
        const int cr = hh * DH - cbase;
        if (cr < BN) {
          uint2 v[5];
          bool in[5];
          float s = 0.f;
#pragma unroll
          for (int qd = 0; qd < 5; qd++) {
            const int c = cr + 4 * qd;
            in[qd] = c >= 0 && c < BN;
            v[qd] = in[qd] ? *(const uint2*)(row + c * 2) : make_uint2(0u, 0u);
            s += bf_lo(v[qd].x) * bf_lo(v[qd].x) + bf_hi(v[qd].x) * bf_hi(v[qd].x) + bf_lo(v[qd].y) * bf_lo(v[qd].y) + bf_hi(v[qd].y) * bf_hi(v[qd].y);
          }
          uint8_t* p = dst + (size_t)hh * (sec == 0 ? S_LEN * 64 : S_LEN * 48);
          if (in[0] && in[1]) st_g16(p, make_uint4(v[0].x, v[0].y, v[1].x, v[1].y));
          else if (in[0]) st_g8(p, v[0]);
          else if (in[1]) st_g8(p + 8, v[1]);
          if (in[2] && in[3]) st_g16(p + 128, make_uint4(v[2].x, v[2].y, v[3].x, v[3].y));
          else if (in[2]) st_g8(p + 128, v[2]);
          else if (in[3]) st_g8(p + 136, v[3]);
          if (in[4]) {
            st_g16(p + 256, make_uint4(v[4].x, v[4].y, sec == 0 ? 0u : 0x00003f80u, 0u));
            if (sec == 0) st_g16(p + 384, make_uint4(0u, 0u, 0u, 0u));
          }
          if (sec == 1) {
            const unsigned int mxb = __reduce_max_sync(~0u, __float_as_uint(s) & 0x7fffffffu);
            if (lane == 0) atomicMax(&s_kn[i], mxb);
          }
        }
      }
      if (sec == 1) {
        named_bar(1, 256);
        const int hh = hfirst + ctid;
        if (ctid < 8 && hh * DH < cbase + BN) {
          const bool starts_here = hh * DH >= cbase, ends_here = hh * DH + DH <= cbase + BN;
          const float v = __uint_as_float(s_kn[ctid]);
          float* o = &g_kn[(blockIdx.y * NH + hh) * 2];
          if (starts_here) { o[0] = v; if (ends_here) o[1] = 0.f; }
          else o[1] = v;
        }
      }
    }
  } else {
    const int r0 = wg * 64 + (warp & 3) * 16 + g;
    const float2* s_st = (const float2*)(sptr + STAGES * Cfg::STAGE_BYTES + 256);
    const float* s_cs = (const float*)(sptr + STAGES * Cfg::STAGE_BYTES + 256 + 1024);
    named_bar(2, 352);
    float2 st[2] = {s_st[r0], s_st[r0 + 8]};
#pragma unroll
    for (int j = 0; j < BN / 8; j++) {
      const float2 cg = *(const float2*)&s_cs[j * 8 + 2 * t], cu = *(const float2*)&s_cs[BN + j * 8 + 2 * t];
      const float* a = &acc[0][0][4 * j];
      const float* b = &acc[0][1][4 * j];
#pragma unroll
      for (int e = 0; e < 2; e++) {
        const float2 s_ = st[e];
        const uint32_t gp = pack_bf16(fmaf(-s_.x, cg.x, a[2 * e]) * s_.y, fmaf(-s_.x, cg.y, a[2 * e + 1]) * s_.y);
        const uint32_t up = pack_bf16(fmaf(-s_.x, cu.x, b[2 * e]) * s_.y, fmaf(-s_.x, cu.y, b[2 * e + 1]) * s_.y);
        uint32_t r;
        asm("{\n.reg .b32 z;\nmax.bf16x2 z, %1, %3;\nmul.rn.bf16x2 %0, z, %2;\n}" : "=r"(r) : "r"(gp), "r"(up), "r"(0u));
        *(uint32_t*)(sptr + (r0 + 8 * e) * LDS + j * 16 + t * 4) = r;
      }
    }
    named_bar(1, 256);
#pragma unroll
    for (int i = 0; i < BM * (BN / 8) / 256; i++) {
      const int idx = i * 256 + ctid, r = idx / (BN / 8), c = idx % (BN / 8);
      st_g16(out + (size_t)(m0 + r) * DFF + n0 + c * 8, *(const uint4*)(sptr + r * LDS + c * 16));
    }
  }
  TS_END(EPI == EPI_QKV ? 1 : EPI + 2);
}

constexpr int R_STAGES = 8;
constexpr int R_STAGE_BYTES = 16384 + 5 * 2048;
constexpr int R_BAR_OFF = R_STAGES * R_STAGE_BYTES;
constexpr int R_SMEM = R_BAR_OFF + 256 + 1024;
template <int KDIM, bool STATS>
__global__ void __launch_bounds__(288, 1) gemm_res_kernel(const __grid_constant__ CUtensorMap tmA, const __nv_bfloat16* resid, __nv_bfloat16* out) {
  constexpr int KT = KDIM / 64;
  extern __shared__ uint8_t smem_raw[];
  const uint32_t sbase = (smem_u32(smem_raw) + 1023u) & ~1023u;
  uint8_t* sptr = smem_raw + (sbase - smem_u32(smem_raw));
  const uint32_t sbar = sbase + R_BAR_OFF;
  const int tid = threadIdx.x, warp = tid >> 5, lane = tid & 31;
  const int n0 = blockIdx.x * 80, m0 = blockIdx.y * 128;
  TS_BEGIN(STATS ? 3 : 5);
  if (tid == 0) {
    for (int i = 0; i < R_STAGES; i++) { mbar_init(sbar + 8 * i, 1); mbar_init(sbar + 8 * (R_STAGES + i), 8); }
    asm volatile("fence.mbarrier_init.release.cluster;" ::: "memory");
  }
  __syncthreads();
  pdl_launch();
  if (warp == 8) {
    if (lane == 0) {
      const uint8_t* wt = (const uint8_t*)(STATS ? g_wo_t : g_wd_t) + (size_t)blockIdx.x * KT * 10240;
      auto load_b = [&](int kt, int s) { bulk_g2s(sbase + s * R_STAGE_BYTES + 16384, wt + kt * 10240, 10240, sbar + 8 * s); };
      pdl_wait();
      for (int s = 0; s < R_STAGES; s++) { mbar_expect_tx(sbar + 8 * s, R_STAGE_BYTES); tma_2d(sbase + s * R_STAGE_BYTES, &tmA, s * 64, m0, sbar + 8 * s); load_b(s, s); }
      for (int kt = R_STAGES; kt < KT; kt++) {
        const int s = kt % R_STAGES;
        mbar_wait(sbar + 8 * (R_STAGES + s), ((kt / R_STAGES) - 1) & 1);
        mbar_expect_tx(sbar + 8 * s, R_STAGE_BYTES);
        tma_2d(sbase + s * R_STAGE_BYTES, &tmA, kt * 64, m0, sbar + 8 * s);
        load_b(kt, s);
      }
    }
    return;
  }
  const int wg = warp >> 2, g = lane >> 2, t = lane & 3;
  pdl_wait();
  uint4 rv[5];
#pragma unroll
  for (int i = 0; i < 5; i++) {
    const int idx = i * 256 + tid, r = idx / 10, c = idx % 10;
    rv[i] = ld_g16(resid + (size_t)(m0 + r) * DM + n0 + c * 8);
  }
  float acc[40];
#pragma unroll
  for (int i = 0; i < 40; i++) acc[i] = 0.f;
  for (int kt = 0; kt < KT; kt++) {
    const int s = kt % R_STAGES;
    mbar_wait(sbar + 8 * s, (kt / R_STAGES) & 1);
    if (kt == 0) TS_MID(STATS ? 3 : 5, 0);
    const uint32_t sa = sbase + s * R_STAGE_BYTES + wg * 8192;
    const uint32_t sb = sbase + s * R_STAGE_BYTES + 16384;
    wgmma_fence();
#pragma unroll
    for (int ks = 0; ks < 4; ks++)
      wgmma_ss_n80(acc, make_desc(sa + ks * 32, 16, 1024, 1), make_desc(sb + ks * 512, 2048, 256, 3), 1);
    wgmma_commit();
    wgmma_wait<1>();
    if (kt > 0 && kt - 1 + R_STAGES < KT && lane == 0) mbar_arrive(sbar + 8 * (R_STAGES + (kt - 1) % R_STAGES));
  }
  wgmma_wait<0>();
#pragma unroll
  for (int i = 0; i < 40; i++) asm volatile("" : "+f"(acc[i]) :: "memory");
  TS_MID(STATS ? 3 : 5, 1);
  named_bar(1, 256);
  constexpr int LDS = 176;
  const int r0 = wg * 64 + (warp & 3) * 16 + g;
#pragma unroll
  for (int i = 0; i < 10; i++) {
    *(uint32_t*)(sptr + r0 * LDS + i * 16 + t * 4) = pack_bf16(acc[4 * i], acc[4 * i + 1]);
    *(uint32_t*)(sptr + (r0 + 8) * LDS + i * 16 + t * 4) = pack_bf16(acc[4 * i + 2], acc[4 * i + 3]);
  }
  named_bar(1, 256);
  TS_MID(STATS ? 3 : 5, 2);
#pragma unroll
  for (int i = 0; i < 5; i++) {
    const int idx = i * 256 + tid, r = idx / 10, c = idx % 10;
    const uint4 a = *(const uint4*)(sptr + r * LDS + c * 16);
    const uint4 b = rv[i];
    uint4 o;
    o.x = pack_bf16(bf_lo(a.x) + bf_lo(b.x), bf_hi(a.x) + bf_hi(b.x));
    o.y = pack_bf16(bf_lo(a.y) + bf_lo(b.y), bf_hi(a.y) + bf_hi(b.y));
    o.z = pack_bf16(bf_lo(a.z) + bf_lo(b.z), bf_hi(a.z) + bf_hi(b.z));
    o.w = pack_bf16(bf_lo(a.w) + bf_lo(b.w), bf_hi(a.w) + bf_hi(b.w));
    st_g16(out + (size_t)(m0 + r) * DM + n0 + c * 8, o);
    if constexpr (STATS) *(uint4*)(sptr + r * LDS + c * 16) = o;
  }
  TS_MID(STATS ? 3 : 5, 3);
  if constexpr (STATS) {
    named_bar(1, 256);
    const int r = tid >> 1, hf = tid & 1;
    float f[40];
#pragma unroll
    for (int i = 0; i < 5; i++) {
      const uint4 v = *(const uint4*)(sptr + r * LDS + hf * 80 + i * 16);
      f[8 * i] = bf_lo(v.x); f[8 * i + 1] = bf_hi(v.x); f[8 * i + 2] = bf_lo(v.y); f[8 * i + 3] = bf_hi(v.y);
      f[8 * i + 4] = bf_lo(v.z); f[8 * i + 5] = bf_hi(v.z); f[8 * i + 6] = bf_lo(v.w); f[8 * i + 7] = bf_hi(v.w);
    }
    float s = 0.f;
#pragma unroll
    for (int i = 0; i < 40; i++) s += f[i];
    s += __shfl_xor_sync(~0u, s, 1);
    const float mu = s * (1.0f / 80.f);
    float q = 0.f;
#pragma unroll
    for (int i = 0; i < 40; i++) { const float d = f[i] - mu; q += d * d; }
    q += __shfl_xor_sync(~0u, q, 1);
    if (hf == 0) g_part2[(m0 + r) * 8 + blockIdx.x] = make_float2(s, q);
  }
  TS_END(STATS ? 3 : 5);
}

#define POLY_NUM 5
__device__ __forceinline__ float ex2_poly(float x, int shl23) {
  const float MAGIC = 12582912.f;
  const float tt = x + MAGIC;
  const float f = x - (tt - MAGIC);
  float p = fmaf(0.0013276472454890609f, f, 0.009675540961325169f);
  p = fmaf(p, f, 0.05550713092088699f);
  p = fmaf(p, f, 0.24022120237350464f);
  p = fmaf(p, f, 0.6931469440460205f);
  p = fmaf(p, f, 1.0000001192092896f);
  return __int_as_float(__float_as_int(tt) * shl23 + __float_as_int(p));
}
constexpr int KV_BYTES = S_LEN * 48;
constexpr int ATT_SMEM = 2 * KV_BYTES + 256 + 32768;
#define ATT_BODY_V 8
constexpr int ATT_BODY = ATT_BODY_V;

__global__ void __launch_bounds__(512, 1) attn_kernel(int shl23, const __nv_bfloat16* __restrict__ wg_, const __nv_bfloat16* __restrict__ wu_,
                                                      const __grid_constant__ CUtensorMap tmWo, const __grid_constant__ CUtensorMap tmWd) {
  extern __shared__ __align__(1024) uint8_t smem[];
  if (blockIdx.x < 4) {
    pdl_launch();
    const int e = blockIdx.x, half = threadIdx.x >> 8;
    TS_MID(0, 0);
    const uint32_t sb = smem_u32(smem), bar = sb + 200 * 1024;
    auto rt_load = [&](int rd) {
      mbar_expect_tx(bar, 17 * 10240);
      for (int i = 0; i < 17; i++) {
        const int tl = e * 68 + rd * 17 + i;
        if (tl >= 80) tma_3d(sb + i * 10240, &tmWd, 0, ((tl - 80) % 24) * 64, ((tl - 80) / 24) * 5, bar);
        else tma_3d(sb + i * 10240, &tmWo, 0, (tl % 10) * 64, (tl / 10) * 5, bar);
      }
    };
    auto rt_store = [&](int rd) {
      mbar_wait(bar, rd & 1);
      for (int i = 0; i < 17; i++) {
        const int tl = e * 68 + rd * 17 + i;
        uint8_t* dst = tl >= 80 ? (uint8_t*)g_wd_t + (size_t)(tl - 80) * 10240 : (uint8_t*)g_wo_t + (size_t)tl * 10240;
        asm volatile("cp.async.bulk.global.shared::cta.bulk_group [%0], [%1], %2;" :: "l"(dst), "r"(sb + i * 10240), "r"(10240) : "memory");
      }
      asm volatile("cp.async.bulk.commit_group;" ::: "memory");
      asm volatile("cp.async.bulk.wait_group.read 0;" ::: "memory");
    };
    if (threadIdx.x == 0) {
      mbar_init(bar, 1);
      asm volatile("fence.mbarrier_init.release.cluster;" ::: "memory");
      rt_load(0);
    }
    __syncwarp();
    float (*red)[65] = (float (*)[65])(smem + 176 * 1024 + half * 10240);
    for (int i = 0; i < 6; i++) {
      const int b = e * 12 + half + 2 * i;
      if (b < 24) colsum64(wg_, DFF, b * 64, g_cs_g, red, threadIdx.x & 255, 1 + half);
      else colsum64(wu_, DFF, (b - 24) * 64, g_cs_u, red, threadIdx.x & 255, 1 + half);
      if ((i & 1) && threadIdx.x == 0) { rt_store(i >> 1); rt_load((i >> 1) + 1); }
      __syncwarp();
    }
    if (threadIdx.x == 0) { rt_store(3); asm volatile("cp.async.bulk.wait_group 0;" ::: "memory"); }
    TS_MID(0, 2);
    return;
  }
  const int h = (blockIdx.x - 4) >> 2, qb = blockIdx.x & 3;
  const uint32_t sK = smem_u32(smem), sV = sK + KV_BYTES, sBar = sV + KV_BYTES;
  const int tid = threadIdx.x;
  TS_BEGIN(2);
  if (tid == 0) {
    for (int i = 0; i < 9; i++) mbar_init(sBar + 8 * i, 1);
    asm volatile("fence.mbarrier_init.release.cluster;" ::: "memory");
  }
  __syncthreads();
  pdl_launch();
  pdl_wait();
  TS_MID(2, 0);
  const uint8_t* gk = (const uint8_t*)(g_k + (size_t)h * S_LEN * 24);
  const uint8_t* gv = (const uint8_t*)(g_v + (size_t)h * S_LEN * 24);
  auto load_kv = [&](int i0, int i1) {
    for (int i = i0; i < i1; i++) {
      mbar_expect_tx(sBar + 8 * i, 2 * 12288);
      bulk_g2s(sK + i * 12288, gk + i * 12288, 12288, sBar + 8 * i);
      bulk_g2s(sV + i * 12288, gv + i * 12288, 12288, sBar + 8 * i);
    }
  };
  if (tid == 0) {
    mbar_expect_tx(sBar + 64, 32768);
    bulk_g2s(sBar + 256, (const uint8_t*)g_q + ((size_t)h * S_LEN + qb * 512) * 64, 32768, sBar + 64);
    load_kv(0, 2);
  }
  float ka = 0.f, kb = 0.f;
#pragma unroll
  for (int i = 0; i < 8; i++) {
    const float2 v = *(const float2*)&g_kn[(i * NH + h) * 2];
    ka = (v.x > ka || v.x != v.x) ? v.x : ka;
    kb = (v.y > kb || v.y != v.y) ? v.y : kb;
  }
  bool fast;
  {
    const float kn = sqrtf(ka + kb);
    mbar_wait(sBar + 64, 0);
    if (tid == 0) load_kv(2, 8);
    uint8_t* qrow = smem + 2 * KV_BYTES + 256 + (tid >> 3) * 512 + (tid & 7) * 16;
    const uint4 c0 = *(const uint4*)qrow, c1 = *(const uint4*)(qrow + 128);
    const uint2 c2 = *(const uint2*)(qrow + 256);
    auto sq = [](uint32_t u) { const float a = bf_lo(u), b = bf_hi(u); return a * a + b * b; };
    const float n2 = sq(c0.x) + sq(c0.y) + sq(c0.z) + sq(c0.w) + sq(c1.x) + sq(c1.y) + sq(c1.z) + sq(c1.w) + sq(c2.x) + sq(c2.y);
    const float m = ceilf(sqrtf(n2) * kn * 1.001f) + 1.f;
    fast = __syncthreads_or(!(m <= 62.f)) == 0;
    if (fast) *(uint32_t*)(qrow + 256 + 8) = pack_bf16(-m, 0.f);
    asm volatile("fence.proxy.async.shared::cta;" ::: "memory");
    __syncthreads();
  }
  auto write_out = [&](float (&O)[12], int it) {
    uint32_t tid2;
    asm volatile("mov.u32 %0, %%tid.x;" : "=r"(tid2));
    const int lane2 = tid2 & 31, t2 = lane2 & 3;
    const int qq = (blockIdx.x & 3) * 512 + (it * 4 + (tid2 >> 7)) * 64 + ((tid2 >> 5) & 3) * 16 + (lane2 >> 2);
    const float l0 = __shfl_sync(~0u, O[8], (lane2 & ~3) | 2), l1 = __shfl_sync(~0u, O[10], (lane2 & ~3) | 2);
    const float r0 = 1.f / l0, r1 = 1.f / l1;
    uint32_t* o0 = (uint32_t*)(g_o + (size_t)qq * DM + ((blockIdx.x - 4) >> 2) * DH);
    uint32_t* o1 = o0 + 8 * DM / 2;
    o0[t2] = pack_bf16(O[0] * r0, O[1] * r0); o1[t2] = pack_bf16(O[2] * r1, O[3] * r1);
    o0[t2 + 4] = pack_bf16(O[4] * r0, O[5] * r0); o1[t2 + 4] = pack_bf16(O[6] * r1, O[7] * r1);
    if (t2 < 2) { o0[t2 + 8] = pack_bf16(O[8] * r0, O[9] * r0); o1[t2 + 8] = pack_bf16(O[10] * r1, O[11] * r1); }
  };
  TS_MID(2, 1);
  if (fast) {
#pragma unroll 1
    for (int it = 0; it < 2; it++) {
      const uint64_t dq = make_desc(sBar + 256 + (it * 4 + (tid >> 7)) * 4096, 128, 512, 0);
      float O[12];
#pragma unroll
      for (int i = 0; i < 12; i++) { O[i] = 0.f; asm volatile("" : "+f"(O[i]) :: "memory"); }
      float S[2][32];
      uint32_t P[16];
#pragma unroll 1
      for (int jb = 0; jb < 32 / ATT_BODY; jb++) {
        if (it == 0) { for (int c = 0; c < ATT_BODY / 4; c++) mbar_wait(sBar + 8 * (jb * (ATT_BODY / 4) + c), 0); }
        const uint64_t dk0 = make_desc(sK + jb * ATT_BODY * 8 * 384, 128, 384, 0);
        const uint64_t dv0 = make_desc(sV + jb * ATT_BODY * 8 * 384, 384, 128, 0);
        wgmma_fence();
        wgmma_ss_n64_k(S[0], dq, dk0, 0);
        wgmma_ss_n64_k(S[0], dq + (256 >> 4), dk0 + (256 >> 4), 1);
        wgmma_commit();
#pragma unroll
        for (int u = 0; u < ATT_BODY; u++) {
          if (u + 1 < ATT_BODY) {
            const uint64_t dk = dk0 + (((u + 1) * 8 * 384) >> 4);
            wgmma_fence();
            wgmma_ss_n64_k(S[(u + 1) & 1], dq, dk, 0);
            wgmma_ss_n64_k(S[(u + 1) & 1], dq + (256 >> 4), dk + (256 >> 4), 1);
            wgmma_commit();
          }
          if (u == 0 || u == ATT_BODY - 1) wgmma_wait<1>(); else wgmma_wait<2>();
#pragma unroll
          for (int i = 0; i < 32; i++) asm volatile("" : "+f"(S[u & 1][i]) :: "memory");
          const uint64_t dv = dv0 + ((u * 8 * 384) >> 4);
#pragma unroll
          for (int hf = 0; hf < 2; hf++) {
            if (hf == 1 && u > 0) { if (u == ATT_BODY - 1) wgmma_wait<1>(); else wgmma_wait<2>(); }
#pragma unroll
            for (int i = hf * 8; i < hf * 8 + 8; i++) {
              const bool usepoly = ((i + 1) * POLY_NUM / 16) != (i * POLY_NUM / 16);
              float a, b;
              if (usepoly) { a = ex2_poly(S[u & 1][2 * i], shl23); b = ex2_poly(S[u & 1][2 * i + 1], shl23); }
              else { a = ex2_mufu(S[u & 1][2 * i]); b = ex2_mufu(S[u & 1][2 * i + 1]); }
              P[i] = pack_bf16(a, b);
            }
            wgmma_fence();
#pragma unroll
            for (int ks = hf * 2; ks < hf * 2 + 2; ks++)
              wgmma_rs_n24_tb(O, P[4 * ks], P[4 * ks + 1], P[4 * ks + 2], P[4 * ks + 3], dv + ((ks * 768) >> 4), 1);
            wgmma_commit();
          }
        }
        wgmma_wait<0>();
      }
#pragma unroll
      for (int i = 0; i < 12; i++) asm volatile("" : "+f"(O[i]) :: "memory");
      write_out(O, it);
      if (it == 0) TS_MID(2, 2);
    }
  } else {
#pragma unroll 1
    for (int it = 0; it < 2; it++) {
      const uint64_t dq = make_desc(sBar + 256 + (it * 4 + (tid >> 7)) * 4096, 128, 512, 0);
      float O[12];
#pragma unroll
      for (int i = 0; i < 12; i++) { O[i] = 0.f; asm volatile("" : "+f"(O[i]) :: "memory"); }
      float S[32];
      float mx0 = -INFINITY, mx1 = -INFINITY;
#pragma unroll 1
      for (int j = 0; j < 32; j++) {
        if (it == 0 && (j & 3) == 0) mbar_wait(sBar + 8 * (j >> 2), 0);
        const uint64_t dk = make_desc(sK + j * 8 * 384, 128, 384, 0);
        wgmma_fence();
        wgmma_ss_n64_k(S, dq, dk, 0);
        wgmma_ss_n64_k(S, dq + (256 >> 4), dk + (256 >> 4), 1);
        wgmma_commit();
        wgmma_wait<0>();
#pragma unroll
        for (int i = 0; i < 8; i++) {
          mx0 = fmaxf(mx0, fmaxf(S[4 * i], S[4 * i + 1]));
          mx1 = fmaxf(mx1, fmaxf(S[4 * i + 2], S[4 * i + 3]));
        }
      }
      mx0 = fmaxf(mx0, __shfl_xor_sync(~0u, mx0, 1)); mx0 = fmaxf(mx0, __shfl_xor_sync(~0u, mx0, 2));
      mx1 = fmaxf(mx1, __shfl_xor_sync(~0u, mx1, 1)); mx1 = fmaxf(mx1, __shfl_xor_sync(~0u, mx1, 2));
#pragma unroll 1
      for (int j = 0; j < 32; j++) {
        const uint64_t dk = make_desc(sK + j * 8 * 384, 128, 384, 0);
        wgmma_fence();
        wgmma_ss_n64_k(S, dq, dk, 0);
        wgmma_ss_n64_k(S, dq + (256 >> 4), dk + (256 >> 4), 1);
        wgmma_commit();
        wgmma_wait<0>();
        uint32_t P[16];
#pragma unroll
        for (int i = 0; i < 8; i++) {
          P[2 * i] = pack_bf16(ex2_mufu(S[4 * i] - mx0), ex2_mufu(S[4 * i + 1] - mx0));
          P[2 * i + 1] = pack_bf16(ex2_mufu(S[4 * i + 2] - mx1), ex2_mufu(S[4 * i + 3] - mx1));
        }
        wgmma_fence();
        const uint64_t dv = make_desc(sV + j * 8 * 384, 384, 128, 0);
#pragma unroll
        for (int ks = 0; ks < 4; ks++)
          wgmma_rs_n24_tb(O, P[4 * ks], P[4 * ks + 1], P[4 * ks + 2], P[4 * ks + 3], dv + ((ks * 768) >> 4), 1);
        wgmma_commit();
        wgmma_wait<0>();
      }
#pragma unroll
      for (int i = 0; i < 12; i++) asm volatile("" : "+f"(O[i]) :: "memory");
      write_out(O, it);
    }
  }
  TS_END(2);
}

typedef CUresult (*EncodeFn)(CUtensorMap*, CUtensorMapDataType, cuuint32_t, void*, const cuuint64_t*, const cuuint64_t*, const cuuint32_t*,
                             const cuuint32_t*, CUtensorMapInterleave, CUtensorMapSwizzle, CUtensorMapL2promotion, CUtensorMapFloatOOBfill);
static EncodeFn get_encode() {
  static EncodeFn fn = nullptr;
  if (!fn) {
    void* p = nullptr; cudaDriverEntryPointQueryResult st;
    cudaGetDriverEntryPoint("cuTensorMapEncodeTiled", &p, cudaEnableDefault, &st);
    fn = (EncodeFn)p;
  }
  return fn;
}
static CUtensorMap make_map(const void* ptr, int rows, int cols, int box_rows, int box_cols = 64) {
  CUtensorMap m;
  cuuint64_t dims[2] = {(cuuint64_t)cols, (cuuint64_t)rows};
  cuuint64_t strides[1] = {(cuuint64_t)cols * 2};
  cuuint32_t box[2] = {(cuuint32_t)box_cols, (cuuint32_t)box_rows};
  cuuint32_t es[2] = {1, 1};
  get_encode()(&m, CU_TENSOR_MAP_DATA_TYPE_BFLOAT16, 2, const_cast<void*>(ptr), dims, strides, box, es, CU_TENSOR_MAP_INTERLEAVE_NONE,
               box_cols == 64 ? CU_TENSOR_MAP_SWIZZLE_128B : (box_cols == 32 ? CU_TENSOR_MAP_SWIZZLE_64B : CU_TENSOR_MAP_SWIZZLE_32B), CU_TENSOR_MAP_L2_PROMOTION_L2_128B, CU_TENSOR_MAP_FLOAT_OOB_FILL_NONE);
  return m;
}
static CUtensorMap make_map_w(const void* ptr, int rows, int cols, int bc, int nblk) {
  CUtensorMap m;
  cuuint64_t dims[3] = {(cuuint64_t)bc, (cuuint64_t)rows, (cuuint64_t)(cols / bc)};
  cuuint64_t strides[2] = {(cuuint64_t)cols * 2, (cuuint64_t)bc * 2};
  cuuint32_t box[3] = {(cuuint32_t)bc, 64, (cuuint32_t)nblk};
  cuuint32_t es[3] = {1, 1, 1};
  get_encode()(&m, CU_TENSOR_MAP_DATA_TYPE_BFLOAT16, 3, const_cast<void*>(ptr), dims, strides, box, es, CU_TENSOR_MAP_INTERLEAVE_NONE,
               bc == 64 ? CU_TENSOR_MAP_SWIZZLE_128B : (bc == 32 ? CU_TENSOR_MAP_SWIZZLE_64B : CU_TENSOR_MAP_SWIZZLE_32B),
               CU_TENSOR_MAP_L2_PROMOTION_L2_128B, CU_TENSOR_MAP_FLOAT_OOB_FILL_NONE);
  return m;
}
template <typename... KArgs, typename... Args>
static void launch(void (*kern)(KArgs...), dim3 grid, dim3 block, size_t smem, bool pdl, Args... args) {
  cudaLaunchConfig_t cfg = {};
  cfg.gridDim = grid; cfg.blockDim = block; cfg.dynamicSmemBytes = smem; cfg.stream = cudaStreamPerThread;
  cudaLaunchAttribute at[1];
  at[0].id = cudaLaunchAttributeProgrammaticStreamSerialization;
  at[0].val.programmaticStreamSerializationAllowed = 1;
  cfg.attrs = at; cfg.numAttrs = pdl ? 1 : 0;
  cudaLaunchKernelEx(&cfg, kern, KArgs(args)...);
}

extern "C" void kernel_launch(void* const* d_in, const int* in_sizes, int n_in, void* d_out, int out_size) {
  const __nv_bfloat16* x = (const __nv_bfloat16*)d_in[0];
  const __nv_bfloat16* wqkv = (const __nv_bfloat16*)d_in[1];
  const __nv_bfloat16* wo = (const __nv_bfloat16*)d_in[2];
  const __nv_bfloat16* wgate = (const __nv_bfloat16*)d_in[4];
  const __nv_bfloat16* wup = (const __nv_bfloat16*)d_in[5];
  const __nv_bfloat16* wdown = (const __nv_bfloat16*)d_in[6];
  __nv_bfloat16* out = (__nv_bfloat16*)d_out;
  void *p_o, *p_h, *p_act;
  cudaGetSymbolAddress(&p_o, g_o); cudaGetSymbolAddress(&p_h, g_h); cudaGetSymbolAddress(&p_act, g_act);

  auto kA = gemm_kernel<256, 128, 1, DM, 4, EPI_QKV>;
  auto kC = gemm_res_kernel<DM, true>;
  auto kD = gemm_kernel<128, 192, 2, DM, 3, EPI_GLU>;
  auto kE = gemm_res_kernel<DFF, false>;
  constexpr int smA = GemmCfg<256, 128, 1, 4>::SMEM, smC = R_SMEM, smD = GemmCfg<128, 192, 2, 3>::SMEM;
  cudaFuncSetAttribute(kA, cudaFuncAttributeMaxDynamicSharedMemorySize, smA);
  cudaFuncSetAttribute(kC, cudaFuncAttributeMaxDynamicSharedMemorySize, smC);
  cudaFuncSetAttribute(kD, cudaFuncAttributeMaxDynamicSharedMemorySize, smD);
  cudaFuncSetAttribute(kE, cudaFuncAttributeMaxDynamicSharedMemorySize, smC);
  cudaFuncSetAttribute(attn_kernel, cudaFuncAttributeMaxDynamicSharedMemorySize, ATT_SMEM);

  const CUtensorMap tm_x = make_map(x, S_LEN, DM, 256), tm_wqkv = make_map_w(wqkv, DM, 3 * DM, 64, 2);
  const CUtensorMap tm_o = make_map(p_o, S_LEN, DM, 128), tm_wo = make_map_w(wo, DM, DM, 16, 5);
  const CUtensorMap tm_h = make_map(p_h, S_LEN, DM, 128), tm_wg = make_map_w(wgate, DM, DFF, 64, 3), tm_wu = make_map_w(wup, DM, DFF, 64, 3);
  const CUtensorMap tm_act = make_map(p_act, S_LEN, DFF, 128), tm_wd = make_map_w(wdown, DFF, DM, 16, 5);

  launch(pre_kernel, dim3(12), dim3(1024), 0, false, x, wqkv);
  launch(kA, dim3(15, 8), dim3(288), smA, true, tm_x, tm_wqkv, tm_wqkv, (__nv_bfloat16*)nullptr);
  launch(attn_kernel, dim3(132), dim3(512), ATT_SMEM, true, 0x800000, wgate, wup, tm_wo, tm_wd);
  launch(kC, dim3(8, 16), dim3(288), smC, true, tm_o, x, (__nv_bfloat16*)p_h);
  launch(kD, dim3(8, 16), dim3(384), smD, true, tm_h, tm_wg, tm_wu, (__nv_bfloat16*)p_act);
  launch(kE, dim3(8, 16), dim3(288), smC, true, tm_act, (const __nv_bfloat16*)p_h, out);
}
```
